```python
import torch

def _softmax(x, axis=-1):
    return torch.softmax(x, dim=axis)

def _gelu(x):
    return torch.nn.functional.gelu(x, approximate='tanh')

def _silu(x):
    return torch.nn.functional.silu(x)

def _sigmoid(x):
    return torch.sigmoid(x)

def _layernorm(x, axis=-1, eps=1e-05):
    m = x.mean(dim=axis, keepdim=True)
    v = x.var(dim=axis, keepdim=True, unbiased=False)
    return (x - m) / torch.sqrt(v + eps)

def _scatter_add(tgt, idx, src, axis=0):
    return tgt.clone().index_add_(axis, idx, src)

def _segment_sum(src, seg, n):
    out = torch.zeros((n,) + src.shape[1:], dtype=src.dtype)
    return out.index_add_(0, seg, src)

def _pad(x, pw):
    flat = tuple((v for pair in reversed(pw) for v in pair))
    return torch.nn.functional.pad(x, flat)
kernel_name = 'interleave_layers__memory_aug_recurrent_mem_tr__glu_gated_swiglu__prompt'

def setup_inputs():

    _w = lambda a: (lambda t: t.to(torch.bfloat16) if t.is_floating_point() else t)(torch.as_tensor(a))

    def _A_setup():
        B, S, Dm = (1, 2048, 576)
        H, Dh = (32, 128)
        M, seg = (8, 32)
        seg = min(seg, S)
        S = S // seg * seg
        return {'x': _w((lambda *s: torch.randn(*s, dtype=torch.bfloat16) * 0.05)(B, S, Dm)), 'mem0': _w((lambda *s: torch.randn(*s, dtype=torch.bfloat16) * 0.2)(B, M, Dm)), 'Wq': _w((lambda *s: torch.randn(*s, dtype=torch.bfloat16) * 1.6)(Dm, H, Dh) * Dm ** (-0.5)), 'Wk': _w((lambda *s: torch.randn(*s, dtype=torch.bfloat16) * 1.6)(Dm, H, Dh) * Dm ** (-0.5)), 'Wv': _w((lambda *s: torch.randn(*s, dtype=torch.bfloat16) * 0.2)(Dm, H, Dh) * Dm ** (-0.5)), 'Wo': _w((lambda *s: torch.randn(*s, dtype=torch.bfloat16) * 0.2)(H, Dh, Dm) * (H * Dh) ** (-0.5)), 'seg_len': seg}
    _A_in = _A_setup()

    def _B_setup():
        B, S, D, F = (1, 2048, 576, 4608)
        return {'x': _w((lambda *s: torch.randn(*s, dtype=torch.bfloat16) * 0.05)(B, S, D)), 'w1': _w((lambda *s: torch.randn(*s, dtype=torch.bfloat16) * 0.2)(D, F) * (2.0 / D) ** 0.5), 'w3': _w((lambda *s: torch.randn(*s, dtype=torch.bfloat16) * 0.2)(D, F) * (2.0 / D) ** 0.5), 'w2': _w((lambda *s: torch.randn(*s, dtype=torch.bfloat16) * 0.2)(F, D) * (2.0 / F) ** 0.5)}
    _B_in = _B_setup()
    return {'A_x': _A_in['x'], 'A_mem0': _A_in['mem0'], 'A_Wq': _A_in['Wq'], 'A_Wk': _A_in['Wk'], 'A_Wv': _A_in['Wv'], 'A_Wo': _A_in['Wo'], 'A_seg_len': _A_in['seg_len'], 'B_x': _B_in['x'], 'B_w1': _B_in['w1'], 'B_w3': _B_in['w3'], 'B_w2': _B_in['w2']}

def reference(A_x, A_mem0, A_Wq, A_Wk, A_Wv, A_Wo, A_seg_len, B_x, B_w1, B_w3, B_w2):

    def _A_ref(x, mem0, Wq, Wk, Wv, Wo, seg_len):
        B, S, Dm = x.shape
        H, Dh = (Wq.shape[1], Wq.shape[2])
        M = mem0.shape[1]
        scale = Dh ** (-0.5)
        n_seg = S // seg_len
        L = M + seg_len
        idx = torch.arange(L)
        mask = (idx[:, None] < M) | (idx[:, None] >= idx[None, :])
        mem = mem0
        outs = []
        for s in range(n_seg):
            xs = x[:, s * seg_len:(s + 1) * seg_len, :].clone()
            h = torch.concatenate([mem, xs], axis=1)
            q = torch.einsum('btd,dhe->bhte', h, Wq)
            k = torch.einsum('btd,dhe->bhte', h, Wk)
            v = torch.einsum('btd,dhe->bhte', h, Wv)
            scores = torch.einsum('bhqe,bhke->bhqk', q, k) * scale
            scores = torch.where(mask[None, None], scores, -1000000000.0)
            p = _softmax(scores, axis=-1)
            o = torch.einsum('bhqk,bhke->bhqe', p, v)
            o = torch.einsum('bhte,hed->btd', o, Wo)
            mem = o[:, :M, :].clone()
            outs.append(o[:, M:, :])
        return torch.concatenate(outs, axis=1)

    def _B_ref(x, w1, w3, w2):
        gate = torch.einsum('bsd,df->bsf', x, w1)
        up = torch.einsum('bsd,df->bsf', x, w3)
        h = _silu(gate) * up
        out = torch.einsum('bsf,fd->bsd', h, w2)
        return out
    x = A_x
    x = x + _A_ref(_layernorm(x, axis=-1), A_mem0, A_Wq, A_Wk, A_Wv, A_Wo, A_seg_len)
    x = x + _B_ref(_layernorm(x, axis=-1), B_w1, B_w3, B_w2)
    x = x + _A_ref(_layernorm(x, axis=-1), A_mem0, A_Wq, A_Wk, A_Wv, A_Wo, A_seg_len)
    x = x + _B_ref(_layernorm(x, axis=-1), B_w1, B_w3, B_w2)
    return x
```

```cpp
#include <cuda_runtime.h>
#include <cuda_bf16.h>
#include <cuda.h>
#include <stdint.h>

typedef __nv_bfloat16 bf16;

namespace {

constexpr int DM = 576, FF = 4608, NSEG = 64;
constexpr int NENG = 64, NF1 = 36, ND = 32, NCTA = NENG + NF1 + ND;
constexpr int NTHREADS = 512;
#define LAG 7
#define RING 8
static_assert(RING > LAG, "ring too short");
constexpr int NSTEP = NSEG + LAG;

enum { F_X0 = 0, F_X1, F_O, F_P1, F_XF, F_H, F_P2, F_COUNT };
__device__ uint32_t g_flag[F_COUNT][96][8];
__device__ uint32_t g_epoch[NCTA][8];
constexpr int XIMG = 9 * 4096;
constexpr int O_BYTES = 65 * 8192;
constexpr int H_BYTES = 73 * 8192;
constexpr int PART = 32 * DM * 4;
constexpr int NP1 = 5, NP2 = 7;
__device__ __align__(1024) uint8_t g_x0[NSEG * XIMG];
__device__ __align__(1024) uint8_t g_x1[NSEG * XIMG];
__device__ __align__(1024) uint8_t g_xf[RING * 9 * 8192];
__device__ __align__(1024) uint8_t g_o[RING * O_BYTES];
__device__ __align__(1024) uint8_t g_h[RING * H_BYTES];
__device__ __align__(1024) uint8_t g_p1[RING * NP1 * PART];
__device__ __align__(1024) uint8_t g_p2[RING * NP2 * PART];
__device__ __align__(1024) uint8_t g_r1[RING * PART];
__device__ __align__(1024) uint8_t g_r2[NSEG * PART / 2];
#define AR_STR 4352
constexpr int AR_SLOT = 144 * AR_STR;
__device__ __align__(1024) uint8_t g_ar[4 * AR_SLOT];

struct Params {
    CUtensorMap tmWq, tmWk, tmWv, tmWo, tmW2;
    const bf16 *x, *mem0, *w1, *w3;
    bf16* out;
};

constexpr uint32_t SM_ORG = 1024;
extern __shared__ __align__(1024) uint8_t smem_raw[];
#define sb ((uint32_t)__cvta_generic_to_shared(smem_raw))
#define bars (sb + SM_BAR)
constexpr int SM_BAR = 231936;
constexpr int SM_TOTAL = SM_BAR + 512;
#define NRQ 27
#define NRK 23
#define NRV 25
#define REGQ 168
#define REGK 160
#define REGV 160
constexpr int E_WQ = 0;
constexpr int E_WK = E_WQ + (36 - NRQ) * 2048;
constexpr int E_WV = E_WK + (36 - NRK) * 2048;
constexpr int E_WO = E_WV + (36 - NRV) * 2048;
constexpr int E_MEM = E_WO + 36 * 2048;
constexpr int E_R0 = E_MEM + 18432;
constexpr int E_R1 = E_R0 + 8192, E_R2 = E_R1 + 8192;
constexpr int E_SX = E_R1;
constexpr int E_QT = E_R2 + 8192;
constexpr int E_KT = E_QT + 8192;
constexpr int E_VT = E_KT + 10240;
constexpr int E_VP = E_VT + 10240;
constexpr int E_VF = E_VP + 8192;
constexpr int E_QM = E_VF + 4096;
constexpr int E_SR = E_QM + 2048;
constexpr int E_SL = E_SR + 2560;
constexpr int E_END = E_SL + 2048;
constexpr int E_OM = E_MEM + 16384, OM_STR = E_QM - E_OM;
static_assert(E_END <= SM_BAR, "engine smem overflow");
static_assert(E_WO + (NRQ + NRK + NRV) * 2048 <= SM_BAR, "weight staging overflow");
enum {
    EB_FULL = 0, EB_EMPTY = 11  , EB_V0 = 15, EB_WL, EB_WO, EB_STEP, EB_VX, EB_SM, EB_SX, EB_VM, EB_QF, EB_KF, EB_CONS, EB_OST, EB_OFREE,
    EB_MEM, EB_PRDY
};
enum { NB_G = 1, NB_LEAD, NB_QK, NB_S, NB_OM, NB_W, NB_R, NB_T, NB_PV, NB_WO, NB_V, NB_KT, NB_S2, NB_VL };
constexpr int NB_VT = NB_R, NB_VL2 = NB_LEAD;
constexpr int NRF = 35;
constexpr int F_W = 0;
constexpr int F_X = 2 * (72 - NRF) * 2048;
constexpr int F_RED = F_X + 9 * 8192;
static_assert(F_RED + 512 <= SM_BAR, "F1 smem overflow");
enum { FB_FULL = 0, FB_EMPTY = 9, FB_H = 18, FB_RACK, FB_JOB, FB_RDONE };
constexpr int NRD = 25;
constexpr int D_B = 3 * (52 - NRD) * 2048;
static_assert(D_B + 8 * 8192 <= SM_BAR, "D smem overflow");
enum { DB_FULL = 0, DB_EMPTY = 8, DB_WL = 16, DB_P };
constexpr int SM_DONE = SM_BAR + 384;

#define SPIN_CHECK(n, code)

#define TS(thr, step, k)
#define TX(thr, k)
#define TG(step, k)

__device__ __forceinline__ uint32_t mapa(uint32_t a, uint32_t r) {
    uint32_t o; asm("mapa.shared::cluster.u32 %0, %1, %2;" : "=r"(o) : "r"(a), "r"(r)); return o;
}
__device__ __forceinline__ void mbar_init(uint32_t b, uint32_t cnt) {
    asm volatile("mbarrier.init.shared::cta.b64 [%0], %1;" :: "r"(b), "r"(cnt) : "memory");
}
__device__ __forceinline__ void mbar_arrive(uint32_t b) {
    asm volatile("mbarrier.arrive.shared::cta.b64 _, [%0];" :: "r"(b) : "memory");
}
__device__ __forceinline__ void mbar_arrive_warp(uint32_t b) {
    asm volatile("{.reg .pred p; bar.warp.sync -1; elect.sync _|p, -1; @p mbarrier.arrive.shared::cta.b64 _, [%0];}" :: "r"(b) : "memory");
}
__device__ __forceinline__ void mbar_arrive_remote(uint32_t b) {
    asm volatile("mbarrier.arrive.release.cluster.shared::cluster.b64 _, [%0];" :: "r"(b) : "memory");
}
__device__ __forceinline__ void mbar_expect(uint32_t b, uint32_t bytes) {
    asm volatile("mbarrier.arrive.expect_tx.shared::cta.b64 _, [%0], %1;" :: "r"(b), "r"(bytes) : "memory");
}
__device__ __forceinline__ void mbar_wait(uint32_t b, uint32_t par) {
    uint32_t ok; [[maybe_unused]] int n = 0;
    while (true) {
        asm volatile("{.reg .pred p; mbarrier.try_wait.parity.shared::cta.b64 p, [%1], %2; selp.u32 %0, 1, 0, p;}"
                     : "=r"(ok) : "r"(b), "r"(par) : "memory");
        if (ok) break;
        SPIN_CHECK(n, 1000 + ((b & 511) >> 3));
    }
}
__device__ __forceinline__ void mbar_wait_cl(uint32_t b, uint32_t par) {
    uint32_t ok; [[maybe_unused]] int n = 0;
    while (true) {
        asm volatile("{.reg .pred p; mbarrier.try_wait.parity.relaxed.cluster.shared::cta.b64 p, [%1], %2; selp.u32 %0, 1, 0, p;}"
                     : "=r"(ok) : "r"(b), "r"(par) : "memory");
        if (ok) break;
        SPIN_CHECK(n, 1000 + ((b & 511) >> 3));
    }
    asm volatile("fence.acquire.sync_restrict::shared::cluster.cluster;" ::: "memory");
}
__device__ __forceinline__ void nbar_sync(int id, int n) { asm volatile("bar.sync %0, %1;" :: "r"(id), "r"(n) : "memory"); }
__device__ __forceinline__ void nbar_arrive(int id, int n) { asm volatile("bar.arrive %0, %1;" :: "r"(id), "r"(n) : "memory"); }
__device__ __forceinline__ void cluster_sync_all() {
    asm volatile("barrier.cluster.arrive.release.aligned; barrier.cluster.wait.acquire.aligned;" ::: "memory");
}
__device__ __forceinline__ void fence_async_smem() { asm volatile("fence.proxy.async.shared::cta;" ::: "memory"); }
__device__ __forceinline__ void fence_async_glb() { asm volatile("fence.proxy.async.global;" ::: "memory"); }
__device__ __forceinline__ void fence_rel_gpu() { asm volatile("fence.release.gpu;" ::: "memory"); }
__device__ __forceinline__ void fence_acq_gpu() { asm volatile("fence.acquire.gpu;" ::: "memory"); }
__device__ __forceinline__ void fence_gpu() { asm volatile("fence.acq_rel.gpu;" ::: "memory"); }
__device__ __forceinline__ int fresh_tid() { int t; asm volatile("mov.u32 %0, %%tid.x;" : "=r"(t)); return t; }
__device__ __forceinline__ int fresh_bid() { int t; asm volatile("mov.u32 %0, %%ctaid.x;" : "=r"(t)); return t; }
__device__ __forceinline__ uint32_t pin(uint32_t v) { asm volatile("" : "+r"(v)); return v; }
__device__ __forceinline__ uint32_t keep(uint32_t v) { return __shfl_xor_sync(~0u, v, 0); }
__device__ __forceinline__ void red_add_u32(uint32_t* p, uint32_t v) {
    asm volatile("red.relaxed.gpu.global.add.u32 [%0], %1;" :: "l"(p), "r"(v) : "memory");
}
__device__ __forceinline__ uint32_t ld_rlx(const void* p) {
    uint32_t v; asm volatile("ld.relaxed.gpu.global.u32 %0, [%1];" : "=r"(v) : "l"(p) : "memory"); return v;
}
__device__ __forceinline__ uint2 ld_rlx64(const void* p) {
    uint2 v; asm volatile("ld.relaxed.gpu.global.v2.u32 {%0,%1}, [%2];" : "=r"(v.x), "=r"(v.y) : "l"(p) : "memory"); return v;
}
__device__ __forceinline__ uint4 ld_rlx128(const void* p) {
    uint4 v;
    asm volatile("ld.relaxed.gpu.global.v4.u32 {%0,%1,%2,%3}, [%4];" : "=r"(v.x), "=r"(v.y), "=r"(v.z), "=r"(v.w) : "l"(p) : "memory");
    return v;
}
__device__ __forceinline__ void stg128(void* p, uint4 v) {
    asm volatile("st.global.v4.b32 [%0], {%1,%2,%3,%4};" :: "l"(p), "r"(v.x), "r"(v.y), "r"(v.z), "r"(v.w) : "memory");
}
__device__ __forceinline__ void stg64(void* p, uint32_t a, uint32_t b) {
    asm volatile("st.global.v2.b32 [%0], {%1,%2};" :: "l"(p), "r"(a), "r"(b) : "memory");
}
__device__ __forceinline__ void st_async128(uint32_t a, uint32_t x, uint32_t y, uint32_t z, uint32_t w, uint32_t mb) {
    asm volatile("st.async.shared::cluster.mbarrier::complete_tx::bytes.v4.b32 [%0], {%1,%2,%3,%4}, [%5];"
                 :: "r"(a), "r"(x), "r"(y), "r"(z), "r"(w), "r"(mb) : "memory");
}
__device__ __forceinline__ void st_async64(uint32_t a, uint32_t x, uint32_t y, uint32_t mb) {
    asm volatile("st.async.shared::cluster.mbarrier::complete_tx::bytes.v2.b32 [%0], {%1,%2}, [%3];"
                 :: "r"(a), "r"(x), "r"(y), "r"(mb) : "memory");
}
__device__ __forceinline__ void sts128(uint32_t a, uint32_t x, uint32_t y, uint32_t z, uint32_t w) {
    asm volatile("st.shared.v4.b32 [%0], {%1,%2,%3,%4};" :: "r"(a), "r"(x), "r"(y), "r"(z), "r"(w) : "memory");
}
__device__ __forceinline__ void sts32(uint32_t a, uint32_t v) { asm volatile("st.shared.b32 [%0], %1;" :: "r"(a), "r"(v) : "memory"); }
__device__ __forceinline__ uint4 lds128(uint32_t a) {
    uint4 v; asm volatile("ld.shared.v4.b32 {%0,%1,%2,%3}, [%4];" : "=r"(v.x), "=r"(v.y), "=r"(v.z), "=r"(v.w) : "r"(a) : "memory"); return v;
}
__device__ __forceinline__ uint2 lds64(uint32_t a) {
    uint2 v; asm volatile("ld.shared.v2.b32 {%0,%1}, [%2];" : "=r"(v.x), "=r"(v.y) : "r"(a) : "memory"); return v;
}
__device__ __forceinline__ uint32_t lds32(uint32_t a) {
    uint32_t v; asm volatile("ld.shared.b32 %0, [%1];" : "=r"(v) : "r"(a) : "memory"); return v;
}
__device__ __forceinline__ void bulk_g2s(uint32_t dst, const void* src, uint32_t bytes, uint32_t mb) {
    asm volatile("cp.async.bulk.shared::cluster.global.mbarrier::complete_tx::bytes [%0], [%1], %2, [%3];"
                 :: "r"(dst), "l"(src), "r"(bytes), "r"(mb) : "memory");
}
__device__ __forceinline__ void bulk_s2g(void* dst, uint32_t src, uint32_t bytes) {
    asm volatile("cp.async.bulk.global.shared::cta.bulk_group [%0], [%1], %2;" :: "l"(dst), "r"(src), "r"(bytes) : "memory");
}
__device__ __forceinline__ void bulk_s2peer(uint32_t dst, uint32_t src, uint32_t bytes, uint32_t mb) {
    asm volatile("cp.async.bulk.shared::cluster.shared::cta.mbarrier::complete_tx::bytes [%0], [%1], %2, [%3];"
                 :: "r"(dst), "r"(src), "r"(bytes), "r"(mb) : "memory");
}
__device__ __forceinline__ void tma_unit(uint32_t dst, const CUtensorMap* tm, int kstep, int mgroup, uint32_t mb) {
    asm volatile("cp.async.bulk.tensor.2d.shared::cluster.global.mbarrier::complete_tx::bytes [%0], [%1, {%2,%3}], [%4];"
                 :: "r"(dst), "l"(tm), "r"(mgroup * 64), "r"(kstep * 16), "r"(mb) : "memory");
}
__device__ __forceinline__ void ldsm4(uint32_t* r, uint32_t a) {
    asm volatile("ldmatrix.sync.aligned.m8n8.x4.shared.b16 {%0,%1,%2,%3}, [%4];"
                 : "=r"(r[0]), "=r"(r[1]), "=r"(r[2]), "=r"(r[3]) : "r"(a) : "memory");
}
__device__ __forceinline__ void ldsm4t(uint32_t* r, uint32_t a) {
    asm volatile("ldmatrix.sync.aligned.m8n8.x4.trans.shared.b16 {%0,%1,%2,%3}, [%4];"
                 : "=r"(r[0]), "=r"(r[1]), "=r"(r[2]), "=r"(r[3]) : "r"(a) : "memory");
}
__device__ __forceinline__ void stsm4(uint32_t a, uint32_t r0, uint32_t r1, uint32_t r2, uint32_t r3) {
    asm volatile("stmatrix.sync.aligned.m8n8.x4.shared.b16 [%0], {%1,%2,%3,%4};" :: "r"(a), "r"(r0), "r"(r1), "r"(r2), "r"(r3) : "memory");
}
__device__ __forceinline__ void stsm4t(uint32_t a, uint32_t r0, uint32_t r1, uint32_t r2, uint32_t r3) {
    asm volatile("stmatrix.sync.aligned.m8n8.x4.trans.shared.b16 [%0], {%1,%2,%3,%4};" :: "r"(a), "r"(r0), "r"(r1), "r"(r2), "r"(r3) : "memory");
}
__device__ __forceinline__ uint32_t pack2(float lo, float hi) {
    uint32_t d; asm("cvt.rn.bf16x2.f32 %0, %1, %2;" : "=r"(d) : "f"(hi), "f"(lo)); return d;
}
__device__ __forceinline__ float bf_lo(uint32_t w) { return __uint_as_float(w << 16); }
__device__ __forceinline__ float bf_hi(uint32_t w) { return __uint_as_float(w & 0xffff0000u); }
__device__ __forceinline__ float ex2(float x) { float y; asm("ex2.approx.ftz.f32 %0, %1;" : "=f"(y) : "f"(x)); return y; }
__device__ __forceinline__ float rcp(float x) { float y; asm("rcp.approx.ftz.f32 %0, %1;" : "=f"(y) : "f"(x)); return y; }
__device__ __forceinline__ uint32_t fu(float x) { return __float_as_uint(x); }
__device__ __forceinline__ float uf(uint32_t x) { return __uint_as_float(x); }
__device__ __forceinline__ void mma16816(float* d, const uint32_t* a, uint32_t b0, uint32_t b1) {
    asm volatile("mma.sync.aligned.m16n8k16.row.col.f32.bf16.bf16.f32 {%0,%1,%2,%3}, {%4,%5,%6,%7}, {%8,%9}, {%0,%1,%2,%3};"
                 : "+f"(d[0]), "+f"(d[1]), "+f"(d[2]), "+f"(d[3]) : "r"(a[0]), "r"(a[1]), "r"(a[2]), "r"(a[3]), "r"(b0), "r"(b1));
}
__device__ __forceinline__ void mma1688(float* d, uint32_t a0, uint32_t a1, uint32_t b0) {
    asm volatile("mma.sync.aligned.m16n8k8.row.col.f32.bf16.bf16.f32 {%0,%1,%2,%3}, {%4,%5}, {%6}, {%0,%1,%2,%3};"
                 : "+f"(d[0]), "+f"(d[1]), "+f"(d[2]), "+f"(d[3]) : "r"(a0), "r"(a1), "r"(b0));
}
template <int N> __device__ __forceinline__ void reg_inc() { asm volatile("setmaxnreg.inc.sync.aligned.u32 %0;" :: "n"(N)); }
template <int N> __device__ __forceinline__ void reg_dec() { asm volatile("setmaxnreg.dec.sync.aligned.u32 %0;" :: "n"(N)); }

__device__ __forceinline__ uint64_t mkdesc(uint32_t addr, uint32_t lbo, uint32_t sbo, uint32_t swz) {
    return (uint64_t)((addr + SM_ORG) >> 4) | ((uint64_t)(lbo >> 4) << 16) | ((uint64_t)(sbo >> 4) << 32) | ((uint64_t)swz << 62);
}
__device__ __forceinline__ void wg_fence() { asm volatile("wgmma.fence.sync.aligned;" ::: "memory"); }
__device__ __forceinline__ void wg_commit() { asm volatile("wgmma.commit_group.sync.aligned;" ::: "memory"); }
template <int N> __device__ __forceinline__ void wg_wait() { asm volatile("wgmma.wait_group.sync.aligned %0;" :: "n"(N) : "memory"); }
template <int M> __device__ __forceinline__ void acc_ready(float* d) {
#pragma unroll
    for (int j = 0; j < M; j++) asm volatile("" : "+f"(d[j]) :: "memory");
}
template <int N, int M> __device__ __forceinline__ void wg_wait_acc(float* d) { wg_wait<N>(); acc_ready<M>(d); }

#define F8(c, d, o) c(d[o]), c(d[o + 1]), c(d[o + 2]), c(d[o + 3]), c(d[o + 4]), c(d[o + 5]), c(d[o + 6]), c(d[o + 7])
#define R8L "%0,%1,%2,%3,%4,%5,%6,%7"
#define R16L R8L ",%8,%9,%10,%11,%12,%13,%14,%15"
#define R32L R16L ",%16,%17,%18,%19,%20,%21,%22,%23,%24,%25,%26,%27,%28,%29,%30,%31"
#define R40L R32L ",%32,%33,%34,%35,%36,%37,%38,%39"
#define WG_BOTH(TXT_PRE, TXT_POST, OUTS, ...)                                                   \
    if (acc) asm volatile(TXT_PRE "1" TXT_POST : OUTS("+f") : __VA_ARGS__);                     \
    else asm volatile(TXT_PRE "0" TXT_POST : OUTS("=f") : __VA_ARGS__)
#define O8(c) F8(c, d, 0)
#define O16(c) F8(c, d, 0), F8(c, d, 8)
#define O32(c) O16(c), F8(c, d, 16), F8(c, d, 24)
#define O40(c) O32(c), F8(c, d, 32)
#define WGM(n) "wgmma.mma_async.sync.aligned.m64n" #n "k16.f32.bf16.bf16 "
__device__ __forceinline__ void wg_rs16(float* d, const uint32_t* a, uint64_t db, bool acc) {
    WG_BOTH(WGM(16) "{" R8L "}, {%8,%9,%10,%11}, %12, ", ", 1, 1, 1;", O8, "r"(a[0]), "r"(a[1]), "r"(a[2]), "r"(a[3]), "l"(db));
}
__device__ __forceinline__ void wg_ss16(float* d, uint64_t da, uint64_t db, bool acc) {
    WG_BOTH(WGM(16) "{" R8L "}, %8, %9, ", ", 1, 1, 1, 1;", O8, "l"(da), "l"(db));
}
__device__ __forceinline__ void wg_rs32(float* d, const uint32_t* a, uint64_t db, bool acc) {
    WG_BOTH(WGM(32) "{" R16L "}, {%16,%17,%18,%19}, %20, ", ", 1, 1, 0;", O16, "r"(a[0]), "r"(a[1]), "r"(a[2]), "r"(a[3]), "l"(db));
}
template <int TB> __device__ __forceinline__ void wg_rs64(float* d, const uint32_t* a, uint64_t db, bool acc) {
    WG_BOTH(WGM(64) "{" R32L "}, {%32,%33,%34,%35}, %36, ", ", 1, 1, %37;", O32, "r"(a[0]), "r"(a[1]), "r"(a[2]), "r"(a[3]), "l"(db), "n"(TB));
}
template <int TB> __device__ __forceinline__ void wg_ss64(float* d, uint64_t da, uint64_t db, bool acc) {
    WG_BOTH(WGM(64) "{" R32L "}, %32, %33, ", ", 1, 1, 1, %34;", O32, "l"(da), "l"(db), "n"(TB));
}
__device__ __forceinline__ void wg_ss80(float* d, uint64_t da, uint64_t db, bool acc) {
    WG_BOTH(WGM(80) "{" R40L "}, %40, %41, ", ", 1, 1, 1, 1;", O40, "l"(da), "l"(db));
}

constexpr float SM_SCALE = 0.08838834764831845f;
constexpr float LOG2E = 1.4426950408889634f;

__device__ __forceinline__ uint32_t* flag_ptr(int stage, int b) { return &g_flag[stage][b][0]; }
__device__ __forceinline__ uint32_t this_launch() { return ld_rlx(&g_epoch[fresh_bid()][0]) + 1; }
__device__ __forceinline__ bool flag_up(int stage, int b, uint32_t target) { return (int)(ld_rlx(flag_ptr(stage, b)) - target) >= 0; }
__device__ __forceinline__ void flag_wait(int stage, int b, uint32_t target) {
    [[maybe_unused]] int n = 0;
    while (!flag_up(stage, b, target)) {
        __nanosleep(20);
        SPIN_CHECK(n, 10 + stage);
    }
    fence_acq_gpu();
    fence_async_glb();
}
__device__ __forceinline__ void publish(int stage, int b) {
    fence_async_glb();
    fence_rel_gpu();
    red_add_u32(flag_ptr(stage, b), 1);
}
__device__ __forceinline__ uint32_t unit_frag_addr(int tid) {
    const int lane = tid & 31, w = (tid >> 5) & 3, i = lane & 7, j = lane >> 3;
    return ((j >> 1) * 8 + i) * 128 + ((((w << 1) + (j & 1)) ^ i) << 4);
}

#define V_BURST2 2
#define V_LEAD 9
static_assert(V_LEAD > 2 + V_BURST2, "q and k rely on v for the arrival of the blocks");
#define V_EARLY 0
#define SX_EARLY 1
__host__ __device__ constexpr int x_order(int mat, int j) {
    return mat == 2 ? j : j < 2 ? j + 2 : j == 2 ? 6 : j < 5 ? j + 1 : j == 5 ? 8 : j == 6 ? 1 : j == 7 ? 7 : 0;
}
#define SS0Q 0
#define SS0K 0
#define SS0V 22
#define SSLQ 36
#define SSLK 36
#define SSLV 14
__host__ __device__ constexpr uint64_t ss_mask(int mat) {
    const int ns = 36 - (mat == 0 ? NRQ : mat == 1 ? NRK : NRV);
    const int j0 = mat == 0 ? SS0Q : mat == 1 ? SS0K : SS0V, len = mat == 0 ? SSLQ : mat == 1 ? SSLK : SSLV;
    uint64_t m = 0;
    for (int j = j0; j < j0 + len; j++)
        if ((j - j0) * ns / len != (j - j0 + 1) * ns / len) m |= 1ull << (x_order(mat, j >> 2) * 4 + (j & 3));
    return m;
}
__device__ __forceinline__ int popc_below(uint64_t m, int k) { return __popcll(m & ((1ull << k) - 1)); }
__host__ __device__ constexpr int x_slot(int f) {
    return f == 0 || f == 6 || f == 9 ? E_R0 : f == 1 || f == 7 ? E_R2 : f < 4 ? E_MEM + (f - 2) * 8192 : f == 4 ? E_QT : f == 5 ? E_KT : f == 8 ? E_VP : E_R1;
}
__host__ __device__ constexpr int x_empty(int blk) { return blk == 3 ? 0 : blk == 6 ? 1 : blk == 5 ? 2 : blk == 1 ? 3 : -1; }
__host__ __device__ constexpr int sx_off(int u) { return u == 0 ? 0 : u == 1 ? 1536 : u == 2 ? 2560 : u == 3 ? 3072 : 5120; }

template <int MAT, int NR, int K0, int K1>
__device__ __forceinline__ void proj_mem(float* d, const uint32_t (&w)[NR][4]) {
    constexpr uint64_t M = ss_mask(MAT);
    const uint64_t db = mkdesc(E_MEM, 128, 9216, 0);
    const uint64_t da = mkdesc((MAT == 0 ? E_WQ : MAT == 1 ? E_WK : E_WV), 1024, 1024, 1);
#pragma unroll
    for (int ks = K0; ks < K1; ks++) {
        const int s = popc_below(M, ks);
        if ((M >> ks) & 1) wg_ss16(d, da + s * 128, db + ks * 16, ks > 0);
        else wg_rs16(d, w[ks - s], db + ks * 16, ks > 0);
    }
}
__device__ __forceinline__ uint32_t tl_lane(int tid, int group_bytes) {
    return ((tid >> 4) & 1) * group_bytes + (((tid >> 5) & 3) * 16 + (tid & 15)) * 16;
}
__device__ __forceinline__ void ar_red(uint8_t* p, uint8_t* q, const float* y) {
    asm volatile("red.relaxed.gpu.global.add.noftz.v4.bf16x2 [%0], {%1,%2,%3,%4};"
                 :: "l"(p), "r"(pack2(y[0], y[1])), "r"(pack2(y[2], y[3])), "r"(pack2(y[4], y[5])), "r"(pack2(y[6], 1.f)) : "memory");
    asm volatile("red.relaxed.gpu.global.add.noftz.bf16x2 [%0], %1;" :: "l"(q), "r"(pack2(y[7], 1.f)) : "memory");
}
__device__ __forceinline__ uint32_t ar_main(int tid) { return ((tid & 127) >> 3) * AR_STR + (tid & 7) * 16; }
__device__ __forceinline__ uint32_t ar_side(int tid) { return ((tid & 127) >> 5) * (4 * AR_STR) + AR_STR / 2 + (tid & 31) * 4; }

__device__ __forceinline__ void attn_mem(float* d, uint32_t par, int i) {
    const int tid = fresh_tid(), lane = tid & 31, warp = tid >> 5, c = warp >> 1, hf = warp & 1;
    const int rank = fresh_bid() & 1;
    const uint32_t peer = mapa(sb, rank ^ 1);
    const uint32_t l4 = (lane >> 4) * 1024 + (lane & 15) * 16;
    uint32_t kb[4][4];
    nbar_sync(NB_KT, 256);
    {
        const uint32_t aK = sb + E_KT + (c * 6 + hf * 2) * 1024 + l4;
#pragma unroll
        for (int ks = 0; ks < 4; ks++) ldsm4t(kb[ks], aK + ks * 256);
    }
    const uint32_t aQs = pin(sb + E_QM + tl_lane(tid, 1024));
    const uint32_t aQ = pin(sb + E_QM + c * 1024 + (((lane >> 3) & 1) * 16 + (lane >> 4) * 8 + (lane & 7)) * 16);
    const uint32_t aM = pin(sb + E_KT + (4 + c) * 1024 + lane * 16);
    const uint32_t oS = pin(tid * 16);
    const uint32_t aV = pin(sb + (hf == rank ? E_VT + c * 6144 : E_VP + c * 4096) + l4);
    wg_wait_acc<0, 8>(d);
    stsm4(aQs, pack2(d[0], d[1]), pack2(d[2], d[3]), pack2(d[4], d[5]), pack2(d[6], d[7]));
    nbar_sync(NB_QK, 256);
    TS(0, i, 1);
    float s[6];
    {
        uint32_t q[2][4], km[2][4];
        ldsm4t(q[0], aQ); ldsm4t(km[0], aM); ldsm4t(q[1], aQ + 512); ldsm4t(km[1], aM + 512);
        float a[6][4];
#pragma unroll
        for (int m = 0; m < 6; m++) a[m][0] = a[m][1] = a[m][2] = a[m][3] = 0.f;
#pragma unroll
        for (int j = 0; j < 2; j++) {
#pragma unroll
            for (int o = 0; o < 2; o++) {
                mma16816(a[o * 3], q[j], kb[2 * j + o][0], kb[2 * j + o][1]);
                mma16816(a[o * 3 + 1], q[j], kb[2 * j + o][2], kb[2 * j + o][3]);
            }
            mma16816(a[2], q[j], km[j][0], km[j][1]);
            mma16816(a[5], q[j], km[j][2], km[j][3]);
        }
        nbar_arrive(NB_S, 256);
        nbar_arrive(NB_S2, 256);
        mbar_wait_cl(bars + EB_VX * 8, par);
#pragma unroll
        for (int m = 0; m < 3; m++) { s[2 * m] = a[m][0] + a[3 + m][2]; s[2 * m + 1] = a[m][1] + a[3 + m][3]; }
    }
    st_async128(peer + E_SR + oS, fu(s[0]), fu(s[1]), fu(s[2]), fu(s[3]), peer + SM_BAR + EB_SM * 8);
    const uint32_t oM = E_SR + 2048 + c * 256 + lane * 8;
    asm volatile("st.async.shared::cluster.mbarrier::complete_tx::bytes.b32 [%0], %1, [%2];"
                 :: "r"(peer + oM + hf * 4), "r"(fu(hf ? s[5] : s[4])), "r"(peer + SM_BAR + EB_SM * 8) : "memory");
    sts128(sb + E_SL + oS, fu(s[0]), fu(s[1]), fu(s[2]), fu(s[3]));
    mbar_arrive_warp(bars + EB_KF * 8);
    TS(0, i, 2);
#pragma unroll
    for (int T = 0; T < 4; T++) ldsm4(kb[T], aV + hf * 2048 + T * 256);
    nbar_sync(NB_G, 128);
    const uint4 l1 = lds128(sb + E_SL + (oS ^ 512));
    mbar_wait_cl(bars + EB_VM * 8, par);
    uint2 vm[4];
#pragma unroll
    for (int T = 0; T < 4; T++) vm[T] = lds64(sb + E_VF + hf * 2048 + lane * 16 + c * 8 + T * 512);
    const uint32_t aO = keep(sb + E_OM + c * OM_STR + (hf * 64 + lane) * 16);
    const uint32_t aR = keep(sb + E_SR + oS), aR1 = keep(sb + E_SR + (oS ^ 512)), aRm = keep(sb + oM), aV1 = keep(aV + (hf ^ 1) * 2048);
    mbar_wait_cl(bars + EB_SM * 8, par);
    TS(0, i, 3);
    float p[10];
    {
        const uint4 r0 = lds128(aR), r1 = lds128(aR1);
        const uint2 rm = lds64(aRm);
        p[0] = s[0] + uf(r0.x); p[1] = s[1] + uf(r0.y); p[2] = s[2] + uf(r0.z); p[3] = s[3] + uf(r0.w);
        p[4] = uf(l1.x) + uf(r1.x); p[5] = uf(l1.y) + uf(r1.y); p[6] = uf(l1.z) + uf(r1.z); p[7] = uf(l1.w) + uf(r1.w);
        p[8] = s[4] + uf(rm.x); p[9] = s[5] + uf(rm.y);
    }
    float mx = fmaxf(fmaxf(fmaxf(p[0], p[1]), fmaxf(p[2], p[3])), fmaxf(fmaxf(fmaxf(p[4], p[5]), fmaxf(p[6], p[7])), fmaxf(p[8], p[9])));
    mx = fmaxf(mx, __shfl_xor_sync(~0u, mx, 1));
    mx = fmaxf(mx, __shfl_xor_sync(~0u, mx, 2));
    const float mo = mx * (SM_SCALE * LOG2E);
    uint32_t pb[5];
    float o[5][4];
    const uint32_t ones[4] = {0x3f803f80u, 0x3f803f80u, 0x3f803f80u, 0x3f803f80u};
    pb[4] = pack2(ex2(fmaf(p[8], SM_SCALE * LOG2E, -mo)), ex2(fmaf(p[9], SM_SCALE * LOG2E, -mo)));
#pragma unroll
    for (int T = 0; T < 5; T++) { o[T][0] = o[T][1] = o[T][2] = o[T][3] = 0.f; mma1688(o[T], T < 4 ? vm[T & 3].x : ones[0], T < 4 ? vm[T & 3].y : ones[1], pb[4]); }
#pragma unroll
    for (int m = 0; m < 2; m++) pb[m] = pack2(ex2(fmaf(p[2 * m], SM_SCALE * LOG2E, -mo)), ex2(fmaf(p[2 * m + 1], SM_SCALE * LOG2E, -mo)));
    mma16816(o[4], ones, pb[0], pb[1]);
#pragma unroll
    for (int T = 0; T < 4; T++) { mma16816(o[T], kb[T], pb[0], pb[1]); ldsm4(kb[T], aV1 + T * 256); }
#pragma unroll
    for (int m = 2; m < 4; m++) pb[m] = pack2(ex2(fmaf(p[2 * m], SM_SCALE * LOG2E, -mo)), ex2(fmaf(p[2 * m + 1], SM_SCALE * LOG2E, -mo)));
    mma16816(o[4], ones, pb[2], pb[3]);
#pragma unroll
    for (int T = 0; T < 4; T++) mma16816(o[T], kb[T], pb[2], pb[3]);
    nbar_arrive(NB_PV, 256);
    mbar_arrive_warp(bars + EB_CONS * 8);
    const float i0 = rcp(o[4][0]), i1 = rcp(o[4][1]);
#pragma unroll
    for (int j = 0; j < 2; j++)
        stsm4(aO + j * 512, pack2(o[2 * j][0] * i0, o[2 * j][1] * i1), pack2(o[2 * j][2] * i0, o[2 * j][3] * i1),
              pack2(o[2 * j + 1][0] * i0, o[2 * j + 1][1] * i1), pack2(o[2 * j + 1][2] * i0, o[2 * j + 1][3] * i1));
}

__device__ __forceinline__ void attn_x_scores(float (&p)[2][10], uint32_t par, int i) {
    {
        float s[40];
        const uint64_t da = mkdesc(E_QT, 128, 1024, 0), db = mkdesc(E_KT, 128, 1024, 0);
        wg_fence();
#pragma unroll
        for (int ks = 0; ks < 4; ks++) wg_ss80(s, da + ks * 16, db + ks * 16, ks > 0);
        wg_commit();
        mbar_wait_cl(bars + EB_PRDY * 8, par);
        wg_wait_acc<0, 40>(s);
#pragma unroll
        for (int u = 0; u < 5; u++) {
            const int v = u < 4 ? 6 + u : 5;
            constexpr float C = SM_SCALE * LOG2E;
            p[0][2 * u] = s[4 * u] * C; p[0][2 * u + 1] = s[4 * u + 1] * C; p[1][2 * u] = s[4 * v + 2] * C; p[1][2 * u + 1] = s[4 * v + 3] * C;
        }
    }
    mbar_arrive_warp(bars + EB_QF * 8);
    const int tid = fresh_tid() & 127, w = tid >> 5;
    {
        const uint32_t peer = mapa(sb, (fresh_bid() & 1) ^ 1);
        if (!SX_EARLY) nbar_sync(NB_OM, 256);
#pragma unroll
        for (int u = 0; u < 5; u++)
            if (u <= w || u == 4) st_async128(peer + E_SX + sx_off(u) + tid * 16, fu(p[0][2 * u]), fu(p[0][2 * u + 1]), fu(p[1][2 * u]), fu(p[1][2 * u + 1]), peer + SM_BAR + EB_SX * 8);
    }
    TS(128, i, 10);
}
__device__ __forceinline__ void attn_x_finish(float (&p)[2][10], uint32_t par, int i) {
    const int tid = fresh_tid() & 127, lane = tid & 31, w = tid >> 5;
    const int dq = w * 8 + (lane >> 2) - 2 * (lane & 3);
#pragma unroll
    for (int j = 0; j < 8; j++)
        if ((j >> 1) * 8 + (j & 1) > dq) p[0][j] = p[1][j] = -1e9f * LOG2E;
    nbar_sync(NB_V, 256);
    fence_async_smem();
    mbar_wait_cl(bars + EB_SX * 8, par);
    TS(128, i, 11);
#pragma unroll
    for (int u = 0; u < 5; u++) {
        const uint4 r = lds128(sb + E_SX + (u <= w ? sx_off(u) : sx_off(4)) + tid * 16);
        p[0][2 * u] += uf(r.x); p[0][2 * u + 1] += uf(r.y); p[1][2 * u] += uf(r.z); p[1][2 * u + 1] += uf(r.w);
    }
    uint32_t pa[5][4];
    float mx[2], inv[2];
#pragma unroll
    for (int h = 0; h < 2; h++) {
        const float* q = p[h];
        mx[h] = fmaxf(fmaxf(fmaxf(q[0], q[1]), fmaxf(q[2], q[3])), fmaxf(fmaxf(fmaxf(q[4], q[5]), fmaxf(q[6], q[7])), fmaxf(q[8], q[9])));
    }
#pragma unroll
    for (int o = 1; o < 4; o <<= 1) { mx[0] = fmaxf(mx[0], __shfl_xor_sync(~0u, mx[0], o)); mx[1] = fmaxf(mx[1], __shfl_xor_sync(~0u, mx[1], o)); }
#pragma unroll
    for (int h = 0; h < 2; h++) {
        float* q = p[h];
#pragma unroll
        for (int j = 0; j < 10; j++) q[j] = ex2(q[j] - mx[h]);
#pragma unroll
        for (int u = 0; u < 4; u++) {
            pa[h * 3 + (u >> 1)][(u & 1) * 2 + h] = pack2(q[2 * u], q[2 * u + 1]);
            pa[h * 3 + (u >> 1)][(u & 1) * 2 + (h ^ 1)] = pin(0);
        }
        pa[2][h * 3] = pack2(q[8], q[9]);
        pa[2][1 + h] = pin(0);
        inv[h] = ((q[0] + q[1]) + (q[2] + q[3])) + ((q[4] + q[5]) + (q[6] + q[7])) + (q[8] + q[9]);
    }
    const uint32_t aO = sb + E_R1 + ((lane >> 4) * 8 + (lane & 7)) * 128 + (((((lane >> 3) & 1) * 4 + w) ^ (lane & 7)) << 4);
    if (SX_EARLY) nbar_sync(NB_OM, 256); else nbar_sync(NB_W, 128);
    TS(128, i, 12);
#pragma unroll
    for (int nh = 0; nh < 2; nh++) {
        float o[16];
        const uint64_t db = mkdesc(E_VT + nh * 512, 1024, 128, 0);
        wg_fence();
#pragma unroll
        for (int kk = 0; kk < 5; kk++) wg_rs32(o, pa[kk], db + kk * 128, kk > 0);
        wg_commit();
        if (nh == 0) {
#pragma unroll
            for (int o = 1; o < 4; o <<= 1) { inv[0] += __shfl_xor_sync(~0u, inv[0], o); inv[1] += __shfl_xor_sync(~0u, inv[1], o); }
            inv[0] = rcp(inv[0]); inv[1] = rcp(inv[1]);
        }
        wg_wait_acc<0, 16>(o);
        if (nh) nbar_arrive(NB_VT, 256);
#pragma unroll
        for (int j = 0; j < 2; j++) {
            const float* y = &o[8 * j];
            stsm4t(aO + nh * 4096 + j * 2048, pack2(y[0] * inv[0], y[1] * inv[0]), pack2(y[2] * inv[1], y[3] * inv[1]), pack2(y[4] * inv[0], y[5] * inv[0]), pack2(y[6] * inv[1], y[7] * inv[1]));
        }
    }
    mbar_arrive_warp(bars + EB_OST * 8);
    TS(128, i, 13);
}

template <int MAT>
__device__ __forceinline__ void engine_main(const Params& P) {
    constexpr int NR = MAT == 0 ? NRQ : MAT == 1 ? NRK : NRV;
    constexpr uint64_t M = ss_mask(MAT);
    uint32_t w[NR][4];
    {
        const uint32_t a = sb + E_WO + (MAT == 0 ? 0 : MAT == 1 ? NRQ : NRQ + NRK) * 2048 + unit_frag_addr(threadIdx.x);
        mbar_wait(bars + EB_WL * 8, 0);
#pragma unroll
        for (int u = 0; u < NR; u++) ldsm4t(w[u], a + u * 2048);
    }
    cluster_sync_all();
#pragma unroll 1
    for (int i = -1; i < NSTEP; i++) {
        const uint32_t par = i & 1;
        if (i >= 0) {
            float d[8];
            mbar_wait(bars + EB_MEM * 8, par);
            fence_async_smem();
            TS(MAT * 128, i, MAT == 2 ? 26 : 14 + MAT);
            wg_fence();
            proj_mem<MAT, NR, 0, 36>(d, w);
            wg_commit();
            if (MAT == 0) {
                attn_mem(d, par, i);
            } else if (MAT == 1) {
                const uint32_t a = pin(sb + E_KT + 4096 + tl_lane(fresh_tid(), 1024));
                wg_wait_acc<0, 8>(d);
                stsm4(a, pack2(d[0], d[1]), pack2(d[2], d[3]), pack2(d[4], d[5]), pack2(d[6], d[7]));
                nbar_arrive(NB_QK, 256);
                TS(128, i, 18);
                nbar_sync(NB_T, 256);
                fence_async_smem();
                nbar_sync(NB_S2, 256);
                float p[2][10];
                attn_x_scores(p, par, i);
                attn_x_finish(p, par, i);
            } else {
                const int tid = fresh_tid(), rank = fresh_bid() & 1;
                const uint32_t a = pin(sb + E_VT + 4096 + tl_lane(tid, 1024)), of = pin(E_VF + rank * 2048 + (tid & 127) * 16);
                const uint32_t peer = pin(mapa(sb, rank ^ 1));
                wg_wait_acc<0, 8>(d);
                const uint32_t v0 = pack2(d[0], d[1]), v1 = pack2(d[2], d[3]), v2 = pack2(d[4], d[5]), v3 = pack2(d[6], d[7]);
                st_async128(peer + of, v0, v1, v2, v3, peer + SM_BAR + EB_VM * 8);
                sts128(sb + of, v0, v1, v2, v3);
                stsm4(a, v0, v1, v2, v3);
                mbar_arrive_warp(bars + EB_VM * 8);
                mbar_arrive_warp(bars + EB_KF * 8);
                nbar_arrive(NB_V, 256);
                TS(256, i, 16);
                if (i == NSTEP - 1) { nbar_sync(NB_S, 256); nbar_sync(NB_PV, 256); nbar_sync(NB_VT, 256); }
            }
            if (MAT == 0) {
                const int tid = fresh_tid(), rank = fresh_bid() & 1;
                uint8_t* const ar = g_ar + (i & 3) * AR_SLOT;
                uint8_t* const pm = ar + pin(ar_main(tid) + rank * (64 * AR_STR));
                uint8_t* const ps = ar + pin(ar_side(tid) + rank * (64 * AR_STR));
                const uint32_t o8 = (128 - rank * 64) * AR_STR;
                const uint64_t db = mkdesc(E_OM, 128, OM_STR, 0), da = mkdesc(E_WO, 1024, 1024, 1);
                nbar_arrive(NB_OM, 256);
                nbar_sync(NB_G, 128);
                fence_async_smem();
                TS(0, i, 6);
                if (i == NSTEP - 1) break;
                float y[4][8];
                wg_fence();
#pragma unroll
                for (int ks = 0; ks < 8; ks++) {
                    if (ks < 4) wg_ss16(y[3], da + (32 + ks) * 128, db + (rank * 4 + ks) * 16, ks > 0);
                    wg_ss16(y[0], da + ks * 128, db + ks * 16, ks > 0);
                }
                wg_commit();
#pragma unroll
                for (int ks = 0; ks < 8; ks++) wg_ss16(y[2], da + (16 + ks) * 128, db + ks * 16, ks > 0);
                wg_commit();
#pragma unroll
                for (int ks = 0; ks < 8; ks++) wg_ss16(y[1], da + (8 + ks) * 128, db + ks * 16, ks > 0);
                wg_commit();
                wg_wait_acc<2, 8>(y[3]); acc_ready<8>(y[0]);
                ar_red(pm + o8, ps + o8, y[3]);
                mbar_wait(bars + EB_WO * 8, 0);
                wg_fence();
#pragma unroll
                for (int ks = 0; ks < 8; ks++) wg_ss16(y[3], da + (24 + ks) * 128, db + ks * 16, ks > 0);
                wg_commit();
                if (V_EARLY) nbar_arrive(NB_WO, 256);
                ar_red(pm, ps, y[0]);
                wg_wait_acc<2, 8>(y[2]);
                ar_red(pm + 32 * AR_STR, ps + 32 * AR_STR, y[2]);
                wg_wait_acc<1, 8>(y[1]);
                ar_red(pm + 16 * AR_STR, ps + 16 * AR_STR, y[1]);
                wg_wait_acc<0, 8>(y[3]);
                ar_red(pm + 48 * AR_STR, ps + 48 * AR_STR, y[3]);
                if (!V_EARLY) nbar_arrive(NB_WO, 256);
                TS(0, i, 7);
            }
            if (i == NSTEP - 1) break;
        }
        uint32_t t[16], aT, arm, ars;
        {
            float d[32];
            const uint64_t da = mkdesc((MAT == 0 ? E_WQ : MAT == 1 ? E_WK : E_WV), 1024, 1024, 1);
#pragma unroll
            for (int n = 0; n < 9; n++) {
                const int blk = x_order(MAT, n), prev = n ? x_order(MAT, n - 1) : 0, f = MAT != 2 && blk < 2 ? 9 + blk : blk;
                if (MAT == 2) {
                    if (n == 2) { wg_wait<0>(); mbar_arrive_warp(bars + EB_V0 * 8); }
                    if (n == 0 || n == 2 || n == 2 + V_BURST2) {
#pragma unroll
                        for (int j = n; j < (n == 0 ? 2 : n < 2 + V_BURST2 ? 2 + V_BURST2 : 8); j++) mbar_wait(bars + (EB_FULL + j) * 8, par ^ 1);
                    }
                    if (n == 2 + V_BURST2) {
                        const int tid = fresh_tid();
                        aT = keep(sb + E_VT + tl_lane(tid, 1024));
                        arm = keep((i & 3) * AR_SLOT + ar_main(tid)); ars = keep((i & 3) * AR_SLOT + ar_side(tid));
                    }
                    if (i >= 0) {
                        if (n == 0) nbar_sync(NB_S, 256);
                        if (n == 2) nbar_sync(NB_PV, 256);
                        if (n == 2 + V_BURST2) nbar_sync(NB_WO, 256);
                    }
                } else {
                    if (n == 0) {
                        aT = keep(sb + (MAT == 0 ? E_QT : E_KT) + tl_lane(fresh_tid(), MAT == 0 ? 2048 : 1024));
                        nbar_sync(MAT ? NB_VL : NB_VL2, 256);
                    }
                }
                if (f >= 8) mbar_wait(bars + (EB_FULL + f) * 8, par ^ 1);
                TX(MAT * 128, 1 + MAT * 9 + n);
                if (n == 0) { wg_fence(); TS(MAT * 128, i + 1, 20 + MAT); }
                const uint64_t db = mkdesc(x_slot(f), 16, 1024, 1);
#pragma unroll
                for (int j = 0; j < 4; j++) {
                    const int ks = blk * 4 + j, s = popc_below(M, ks);
                    if ((M >> ks) & 1) wg_ss64<0>(d, da + s * 128, db + j * 2, n + j > 0);
                    else wg_rs64<0>(d, w[ks - s], db + j * 2, n + j > 0);
                }
                wg_commit();
                if (MAT == 2 && n + 1 == V_LEAD) { nbar_arrive(NB_VL, 256); nbar_arrive(NB_VL2, 256); }
                if (MAT != 2 && x_empty(prev) >= 0) { wg_wait<1>(); mbar_arrive_warp(bars + (EB_EMPTY + x_empty(prev)) * 8); }
            }
            if (MAT != 2) mbar_wait(bars + (EB_EMPTY + 2) * 8, par ^ 1);
            else if (i >= 0) nbar_sync(NB_VT, 256);
            wg_wait_acc<0, 32>(d);
            if (MAT != 2) mbar_arrive_warp(bars + EB_STEP * 8);
            TS(MAT * 128, i + 1, 23 + MAT);
#pragma unroll
            for (int j = 0; j < 16; j++) t[j] = pack2(d[2 * j], d[2 * j + 1]);
        }
        if (MAT == 2) {
            const int lane = (ars >> 2) & 31;
            if (lane < 4) mbar_arrive(bars + (EB_EMPTY + lane) * 8);
        }
        {
#pragma unroll
            for (int j = 0; j < 8; j += 2) {
                const int grp = MAT == 0 ? 2 * (j & 3) + (j >> 2) : j < 4 ? j : j + 2;
                stsm4(aT + grp * 1024, t[2 * j], t[2 * j + 1], t[2 * j + 2], t[2 * j + 3]);
            }
        }
        if (MAT == 2) {
            if (i >= 0) {
                [[maybe_unused]] int n = 0;
                while (true) {
                    uint4 av[9];
                    uint32_t as[9];
#pragma unroll
                    for (int j = 0; j < 9; j++) {
                        const int T = j == 0 ? 8 : j < 5 ? ((j - 1) & 1) * 4 + ((j - 1) & 2) : ((j - 1) & 1) * 4 + ((j - 1) & 2) + 1;
                        av[j] = ld_rlx128(g_ar + arm + T * (16 * AR_STR)); as[j] = ld_rlx(g_ar + ars + T * (16 * AR_STR));
                    }
                    mbar_wait(bars + EB_EMPTY * 8, par ^ 1);
                    const uint32_t a = sb + E_MEM + tl_lane(fresh_tid(), 9216);
                    bool ok = true;
#pragma unroll
                    for (int j = 0; j < 9; j++) {
                        const int T = j == 0 ? 8 : j < 5 ? ((j - 1) & 1) * 4 + ((j - 1) & 2) : ((j - 1) & 1) * 4 + ((j - 1) & 2) + 1;
                        ok &= __byte_perm(av[j].w, as[j], 0x7632) == (T == 8 ? 0x42804280u : 0x42004200u);
                        stsm4(a + T * 1024, av[j].x, av[j].y, av[j].z, __byte_perm(av[j].w, as[j], 0x5410));
                    }
                    if (__all_sync(~0u, ok)) break;
                    SPIN_CHECK(n, 2);
                }
                TS(256, i, 19);
            }
            if (i < 0 || i + 1 == LAG) {
                mbar_wait(bars + EB_WO * 8, 0);
                const int tid = fresh_tid();
                mbar_wait(bars + EB_EMPTY * 8, par ^ 1);
                const uint16_t* m = (const uint16_t*)P.mem0 + (tid & 3) * (2 * DM) + ((tid >> 5) & 3) * 16 + ((tid & 31) >> 2);
                const uint32_t a2 = sb + E_MEM + ((tid >> 5) & 3) * 256 + (tid & 31) * 4;
                __syncwarp();
#pragma unroll 6
                for (int T = 0; T < 18; T++) {
                    const int f = (T >> 1) * 64 + (T & 1) * 8;
                    const uint32_t v = (uint32_t)__ldg(m + f) | ((uint32_t)__ldg(m + f + DM) << 16);
                    sts32(a2 + 9216 + f * 16, v);
                    if (i < 0) sts32(a2 + f * 16, v);
                }
            }
        }
        if (MAT == 0) nbar_arrive(NB_T, 256);
        if (MAT == 1) nbar_arrive(NB_KT, 256);
        if (MAT == 2) { mbar_arrive_warp(bars + EB_MEM * 8); TS(256, i + 1, 8); }
    }
}

__device__ __forceinline__ void engine_helper(const Params& P) {
    const int lane = threadIdx.x & 31, hw = (threadIdx.x >> 5) & 3, e = blockIdx.x, rank = e & 1;
    if (hw < 3) {
        constexpr uint64_t M0 = ss_mask(0), M1 = ss_mask(1), M2 = ss_mask(2);
        const uint64_t m = hw == 0 ? M0 : hw == 1 ? M1 : M2;
        const uint32_t ws = sb + (hw == 0 ? E_WQ : hw == 1 ? E_WK : E_WV), wr = sb + E_WO + (hw == 0 ? 0 : hw == 1 ? NRQ : NRQ + NRK) * 2048;
        if (lane == 0) mbar_expect(bars + EB_WL * 8, 36 * 2048);
        __syncwarp();
        for (int ks = lane; ks < 36; ks += 32) {
            const int s = __popcll(m & ((1ull << ks) - 1));
            tma_unit(((m >> ks) & 1) ? ws + s * 2048 : wr + (ks - s) * 2048, hw == 0 ? &P.tmWq : hw == 1 ? &P.tmWk : &P.tmWv, ks, e, bars + EB_WL * 8);
        }
    }
    __syncwarp();
    cluster_sync_all();
    if (hw == 0) {
        if (lane == 0) {
            const uint32_t peer = mapa(sb, rank ^ 1), ep = this_launch();
#pragma unroll 1
            for (int n = 0; n < NSTEP; n++) {
                const uint32_t par = (n & 1) ^ 1;
                if (n < NSEG) flag_wait(F_X0, n, 16 * ep);
                if (n >= LAG) flag_wait(F_X1, n - LAG, 16 * ep);
                TG(n, 30);
                const uint8_t* s0 = g_x0 + min(n, NSEG - 1) * XIMG;
                const uint8_t* s1 = n >= LAG ? g_x1 + (n - LAG) * XIMG : s0;
#pragma unroll
                for (int j = 0; j < 11; j++) {
                    const int f = j < 9 ? j : 19 - j, blk = f < 9 ? f : f - 9;
                    if (n > 0 && (f == 0 || f == 2 || f == 4 || f == 8 || f == 10))
                        mbar_wait(bars + (f == 0 ? EB_STEP : f == 2 ? EB_KF : f == 4 ? EB_QF : f == 8 ? EB_CONS : EB_OFREE) * 8, par);
                    if (f == 6 || f == 9) mbar_wait(bars + (f == 6 ? EB_V0 : EB_EMPTY + 1) * 8, par ^ 1);
                    const uint32_t fb = bars + (EB_FULL + f) * 8;
                    mbar_expect(fb, 8192);
                    bulk_g2s(sb + x_slot(f), s0 + blk * 4096, 4096, fb);
                    bulk_g2s(sb + x_slot(f) + 4096, s1 + blk * 4096, 4096, fb);
                }
                mbar_wait(bars + (EB_EMPTY + 3) * 8, par ^ 1);
                mbar_arrive_remote(peer + SM_BAR + EB_PRDY * 8);
            }
        }
    } else if (hw == 1) {
        if (lane == 0) {
#pragma unroll 1
            for (int i = 0; i < NSTEP; i++) {
                mbar_wait(bars + EB_OST * 8, i & 1);
                fence_async_smem();
                bulk_s2g(g_o + (i & (RING - 1)) * O_BYTES + e * 8192, sb + E_R1, 8192);
                asm volatile("cp.async.bulk.commit_group;" ::: "memory");
                asm volatile("cp.async.bulk.wait_group.read 0;" ::: "memory");
                mbar_arrive(bars + EB_OFREE * 8);
                asm volatile("cp.async.bulk.wait_group 0;" ::: "memory");
                publish(F_O, i);
                TG(i, 31);
            }
        }
    } else if (hw == 2) {
        const uint32_t peer = mapa(sb, rank ^ 1);
        const int idx = e * 23 + lane, line = idx >> 3;
        uint8_t* z = g_ar + (line < 144 ? line * AR_STR : (line - 144) * (4 * AR_STR) + AR_STR / 2) + (idx & 7) * 16;
#pragma unroll 1
        for (int i = 0; i < NSTEP; i++) {
            mbar_wait(bars + EB_MEM * 8, i & 1);
            if (lane == 0) {
                mbar_wait_cl(bars + EB_PRDY * 8, i & 1);
                fence_async_smem();
                bulk_s2peer(peer + E_VP, sb + E_VT, 4096, peer + SM_BAR + EB_VX * 8);
                bulk_s2peer(peer + E_VP + 4096, sb + E_VT + 6144, 4096, peer + SM_BAR + EB_VX * 8);
                mbar_expect(bars + EB_VX * 8, 8192);
                mbar_expect(bars + EB_SX * 8, 7168);
                mbar_expect(bars + EB_SM * 8, 2560);
                mbar_expect(bars + EB_VM * 8, 2048);
            }
            __syncwarp();
            if (i >= 2 && lane < 23 && idx < 1440) stg128(z + ((i + 2) & 3) * AR_SLOT, make_uint4(0, 0, 0, 0));
            __syncwarp();
            if (lane == 0) { fence_gpu(); mbar_arrive(bars + EB_VM * 8); }
            __syncwarp();
        }
        flag_wait(F_O, NSTEP - 1, NENG * this_launch());
        if (lane < 23 && idx < 1440) stg128(z + ((NSTEP - 2) & 3) * AR_SLOT, make_uint4(0, 0, 0, 0));
    } else {
        if (lane == 0) mbar_expect(bars + EB_WO * 8, 36 * 2048);
        __syncwarp();
        for (int u = lane; u < 36; u += 32)
            tma_unit(sb + E_WO + u * 2048, &P.tmWo, (e >> 1) * 8 + (u < 32 ? u & 7 : rank * 4 + (u & 3)), u < 32 ? rank * 4 + (u >> 3) : 8, bars + EB_WO * 8);
    }
    __syncwarp();
}

__device__ __forceinline__ void f1_fetch(const Params& P, uint32_t dst, int f0, int ks0, int n) {
    const int tid = threadIdx.x & 127, r = tid >> 3, c = tid & 7;
    const bf16* src = ((c & 1) ? P.w3 : P.w1) + (size_t)(ks0 * 16 + r) * FF + f0 + (c >> 1) * 8;
    dst += r * 128 + ((c ^ (r & 7)) << 4);
#pragma unroll 1
    for (int u = 0; u < n; u++)
        asm volatile("cp.async.cg.shared.global [%0], [%1], 16;" :: "r"(dst + u * 2048), "l"(src + (size_t)u * 16 * FF) : "memory");
}
template <bool RF, bool second>
__device__ __forceinline__ void f1_tile(const uint32_t (&w)[NRF][4], uint32_t ws, int b, int fo) {
    const uint32_t par = b & 1;
    float d[32];
    const uint64_t da = mkdesc(ws, 1024, 1024, 1), db = mkdesc(F_X, 16, 1024, 1);
#pragma unroll
    for (int blk = 0; blk < 9; blk++) {
        if (!second || blk == 0) mbar_wait(bars + (FB_FULL + blk) * 8, par);
        if (blk == 0) wg_fence();
#pragma unroll
        for (int j = 0; j < 4; j++) {
            const int ks = blk * 4 + j;
            if (RF && ks < NRF) wg_rs64<0>(d, w[ks < NRF ? ks : 0], db + blk * 512 + j * 2, ks > 0);
            else wg_ss64<0>(d, da + (RF ? ks - NRF : 36 - NRF + ks) * 128, db + blk * 512 + j * 2, ks > 0);
        }
        wg_commit();
        if (blk > 0 && second) { wg_wait<1>(); mbar_arrive_warp(bars + (FB_EMPTY + blk - 1) * 8); }
    }
    const int tid = fresh_tid(), g = (tid & 31) >> 2;
    uint8_t* dst = g_h + (b & (RING - 1)) * H_BYTES + ((fresh_bid() - NENG) * 128 + fo + ((tid >> 5) & 3) * 8 + g) * 128;
    wg_wait_acc<0, 32>(d);
    if (second) mbar_arrive_warp(bars + (FB_EMPTY + 8) * 8);
    uint32_t h[8];
#pragma unroll
    for (int j = 0; j < 8; j++) {
        const float g0 = d[4 * j], g1 = d[4 * j + 1];
        const float e0 = 1.f + ex2(fminf(-LOG2E * g0, 60.f)), e1 = 1.f + ex2(fminf(-LOG2E * g1, 60.f));
        const float r = rcp(e0 * e1);
        h[j] = pack2(g0 * d[4 * j + 2] * (e1 * r), g1 * d[4 * j + 3] * (e0 * r));
    }
    stg128(dst + (((tid & 3) ^ g) << 4), make_uint4(h[0], h[1], h[2], h[3]));
    stg128(dst + ((((tid & 3) + 4) ^ g) << 4), make_uint4(h[4], h[5], h[6], h[7]));
}
template <int a>
__device__ __forceinline__ void f1_main(const Params& P) {
    constexpr uint32_t ws = F_W + a * (72 - NRF) * 2048;
    const int f0 = (blockIdx.x - NENG) * 128 + a * 64;
    uint32_t w[NRF][4];
    f1_fetch(P, sb + ws, f0, 0, NRF);
    asm volatile("cp.async.wait_all;" ::: "memory");
    nbar_sync(NB_G + a, 128);
    {
        const uint32_t fa = sb + ws + unit_frag_addr(threadIdx.x);
#pragma unroll
        for (int u = 0; u < NRF; u++) ldsm4t(w[u], fa + u * 2048);
    }
    nbar_sync(NB_G + a, 128);
    f1_fetch(P, sb + ws, f0, NRF, 36 - NRF);
    f1_fetch(P, sb + ws + (36 - NRF) * 2048, f0 + 32, 0, 36);
    asm volatile("cp.async.wait_all;" ::: "memory");
    fence_async_smem();
    nbar_sync(NB_G + a, 128);
#pragma unroll 1
    for (int b = 0; b < NSTEP; b++) {
        f1_tile<a == 0, false>(w, ws, b, a * 96);
        f1_tile<a == 1, true>(w, ws, b, 32 + a * 32);
        mbar_wait(bars + FB_RACK * 8, (b & 1) ^ 1);
        mbar_arrive_warp(bars + FB_H * 8);
    }
}
__device__ __forceinline__ uint32_t n_pairs(int b) { return (b < NSEG ? 16 : 0) + (b >= LAG ? 16 : 0); }
__device__ __forceinline__ void publisher(uint32_t done, uint32_t ack, int stage) {
#pragma unroll 1
    for (int b = 0; b < NSTEP; b++) {
        mbar_wait(done, b & 1);
        mbar_arrive(ack);
        TG(b, 30);
        publish(stage, b);
        TG(b, 31);
    }
}
__device__ __forceinline__ void f1_helper() {
    const int hw = (threadIdx.x >> 5) & 3;
    if ((threadIdx.x & 31) == 0) {
        if (hw == 0) {
            const uint32_t ep = this_launch();
#pragma unroll 1
            for (int b = 0; b < NSTEP; b++) {
                flag_wait(F_XF, b, n_pairs(b) * ep);
                TG(b, 29);
                const uint8_t* src = g_xf + (b & (RING - 1)) * (9 * 8192);
#pragma unroll 1
                for (int blk = 0; blk < 9; blk++) {
                    mbar_wait(bars + (FB_EMPTY + blk) * 8, (b & 1) ^ 1);
                    mbar_expect(bars + (FB_FULL + blk) * 8, 8192);
                    bulk_g2s(sb + F_X + blk * 8192, src + blk * 8192, 8192, bars + (FB_FULL + blk) * 8);
                }
            }
        } else if (hw == 1) {
            publisher(bars + FB_H * 8, bars + FB_RACK * 8, F_H);
        } else if (hw == 2 && blockIdx.x < NENG + 32) {
            const uint32_t ep = this_launch();
            int b1 = blockIdx.x < NENG + 16 ? 0 : LAG, b2 = b1;
            const int bend = b1 + NSEG;
#pragma unroll 1
            for (int j = 0; j < 2 * NSEG; j++) {
                [[maybe_unused]] int n = 0;
                bool second;
                while (true) {
                    const bool r1 = flag_up(F_P1, b1, 15 * ep) && b1 < bend && b1 < b2 + RING;
                    second = flag_up(F_P2, b2, 17 * ep);
                    if (r1 || second) break;
                    __nanosleep(20);
                    SPIN_CHECK(n, 20);
                }
                fence_acq_gpu();
                TG(second ? b2 : b1, 25 + 2 * second);
                if (j) mbar_wait(bars + FB_RDONE * 8, (j & 1) ^ 1);
                sts32(sb + F_RED + 64 + (j & 1) * 4, second ? b2 + 256 : b1);
                mbar_arrive(bars + FB_JOB * 8);
                if (second) b2++; else b1++;
            }
        }
    }
    __syncwarp();
}

__device__ __forceinline__ void add8(float* f, uint4 a) {
    f[0] += bf_lo(a.x); f[1] += bf_hi(a.x); f[2] += bf_lo(a.y); f[3] += bf_hi(a.y);
    f[4] += bf_lo(a.z); f[5] += bf_hi(a.z); f[6] += bf_lo(a.w); f[7] += bf_hi(a.w);
}
__device__ __forceinline__ void set8(float* f, uint4 a) {
    f[0] = bf_lo(a.x); f[1] = bf_hi(a.x); f[2] = bf_lo(a.y); f[3] = bf_hi(a.y);
    f[4] = bf_lo(a.z); f[5] = bf_hi(a.z); f[6] = bf_lo(a.w); f[7] = bf_hi(a.w);
}
__device__ __forceinline__ void ln0_rows(const Params& P, int r) {
    const int lane = threadIdx.x & 31, l = lane < 24 ? lane : 0;
    const uint4* xrow = (const uint4*)(P.x + r * DM) + l;
    uint4 xw[2][3];
#pragma unroll
    for (int k = 0; k < 6; k++) xw[k / 3][k % 3] = __ldg(xrow + (k / 3) * (16 * DM / 8) + 24 * (k % 3));
#pragma unroll 1
    for (int seg = 0; seg < NSEG; seg++) {
#pragma unroll
        for (int h = 0; h < 2; h++) {
            float f[24];
#pragma unroll
            for (int k = 0; k < 3; k++) set8(&f[k * 8], xw[h][k]);
            if (seg + 1 < NSEG) {
#pragma unroll
                for (int k = 0; k < 3; k++) xw[h][k] = __ldg(xrow + (2 * seg + 2 + h) * (16 * DM / 8) + 24 * k);
            }
            float s = 0.f, q = 0.f;
#pragma unroll
            for (int j = 0; j < 24; j++) s += f[j];
            if (lane >= 24) s = 0.f;
#pragma unroll
            for (int o = 16; o; o >>= 1) s += __shfl_xor_sync(~0u, s, o);
            const float mean = s * (1.f / DM);
#pragma unroll
            for (int j = 0; j < 24; j++) { f[j] -= mean; q += f[j] * f[j]; }
            if (lane >= 24) q = 0.f;
#pragma unroll
            for (int o = 16; o; o >>= 1) q += __shfl_xor_sync(~0u, q, o);
            const float rstd = rsqrtf(q * (1.f / DM) + 1e-5f);
            if (lane < 24) {
                uint8_t* d = g_x0 + seg * XIMG + (l >> 3) * 4096 + (r + 16 * h) * 128 + (((l & 7) ^ (r & 7)) << 4);
#pragma unroll
                for (int k = 0; k < 3; k++) {
                    const float* y = &f[8 * k];
                    stg128(d + k * 12288, make_uint4(pack2(y[0] * rstd, y[1] * rstd), pack2(y[2] * rstd, y[3] * rstd), pack2(y[4] * rstd, y[5] * rstd), pack2(y[6] * rstd, y[7] * rstd)));
                }
            }
        }
        __syncwarp();
        if (lane == 0) publish(F_X0, seg);
        __syncwarp();
    }
}

template <bool SECOND, bool CHAIN>
__device__ __forceinline__ void reduce_job(const Params& P, int b) {
    constexpr int NP = SECOND ? NP2 : NP1;
    const int tid = fresh_tid() & 127, lane = tid & 31, p = fresh_bid() - NENG, seg = CHAIN ? b - LAG : b;
    const bool act = lane < 24;
    const int i = (tid >> 5) * 24 + (act ? lane : 0);
    const uint32_t ro = (b & (RING - 1)), po = p * (DM * 4) + i * 32;
    const int fa = (i >> 1) * 16 + (i & 1) * 4;
    const uint32_t row = (seg * 32 + (p & 15) * 2) * DM + fa;
    uint8_t* const r1 = g_r1 + ro * PART + po;
    uint8_t* const r2 = g_r2 + seg * (PART / 2) + po - (CHAIN ? PART / 2 : 0);
    float f[16];
    uint4 x0, x1;
    {
        const uint8_t* src = (SECOND ? g_p2 : g_p1) + ro * (NP * PART) + po;
        uint4 a[NP][2];
#pragma unroll
        for (int k = 0; k < NP; k++) { a[k][0] = ld_rlx128(src + k * PART); a[k][1] = ld_rlx128(src + k * PART + 16); }
        if (SECOND || CHAIN) {
            x0 = ld_rlx128(SECOND ? r1 : r2); x1 = ld_rlx128((SECOND ? r1 : r2) + 16);
        } else {
            const uint2 a0 = ld_rlx64(P.x + row), b0 = ld_rlx64(P.x + row + 8), a1 = ld_rlx64(P.x + row + DM), c1 = ld_rlx64(P.x + row + DM + 8);
            x0 = make_uint4(__byte_perm(a0.x, a1.x, 0x5410), __byte_perm(b0.x, c1.x, 0x5410), __byte_perm(a0.x, a1.x, 0x7632), __byte_perm(b0.x, c1.x, 0x7632));
            x1 = make_uint4(__byte_perm(a0.y, a1.y, 0x5410), __byte_perm(b0.y, c1.y, 0x5410), __byte_perm(a0.y, a1.y, 0x7632), __byte_perm(b0.y, c1.y, 0x7632));
        }
        set8(f, a[0][0]);
#pragma unroll
        for (int k = 1; k < NP; k++) add8(f, a[k][0]);
        set8(f + 8, a[0][1]);
#pragma unroll
        for (int k = 1; k < NP; k++) add8(f + 8, a[k][1]);
    }
    add8(f, x0); add8(f + 8, x1);
    x0 = make_uint4(pack2(f[0], f[1]), pack2(f[2], f[3]), pack2(f[4], f[5]), pack2(f[6], f[7]));
    x1 = make_uint4(pack2(f[8], f[9]), pack2(f[10], f[11]), pack2(f[12], f[13]), pack2(f[14], f[15]));
    if (SECOND && CHAIN) {
        if (act) {
            stg64(P.out + row, __byte_perm(x0.x, x0.z, 0x5410), __byte_perm(x1.x, x1.z, 0x5410));
            stg64(P.out + row + 8, __byte_perm(x0.y, x0.w, 0x5410), __byte_perm(x1.y, x1.w, 0x5410));
            stg64(P.out + row + DM, __byte_perm(x0.x, x0.z, 0x7632), __byte_perm(x1.x, x1.z, 0x7632));
            stg64(P.out + row + DM + 8, __byte_perm(x0.y, x0.w, 0x7632), __byte_perm(x1.y, x1.w, 0x7632));
        }
        return;
    }
    set8(f, x0); set8(f + 8, x1);
    float st[4] = {0.f, 0.f, 0.f, 0.f};
#pragma unroll
    for (int j = 0; j < 16; j++) { st[j & 1] += f[j]; st[2 + (j & 1)] += f[j] * f[j]; }
    {
        const bool u = lane & 1, v = lane & 2;
        st[0] = (u ? st[1] : st[0]) + __shfl_xor_sync(~0u, u ? st[0] : st[1], 1);
        st[2] = (u ? st[3] : st[2]) + __shfl_xor_sync(~0u, u ? st[2] : st[3], 1);
        st[0] = (v ? st[2] : st[0]) + __shfl_xor_sync(~0u, v ? st[0] : st[2], 2);
        st[0] += __shfl_xor_sync(~0u, st[0], 4);
        if (act && !(lane & 4)) sts32(sb + F_RED + 128 + (i >> 3) * 16 + (lane & 3) * 4, fu(st[0]));
    }
    if (act) { stg128(SECOND ? r2 : r1, x0); stg128((SECOND ? r2 : r1) + 16, x1); }
    nbar_sync(NB_R, 96);
#pragma unroll
    for (int k = 0; k < 9; k++) {
        const uint4 t = lds128(sb + F_RED + 128 + k * 16);
        if (k == 0) { st[0] = uf(t.x); st[1] = uf(t.y); st[2] = uf(t.z); st[3] = uf(t.w); }
        else { st[0] += uf(t.x); st[1] += uf(t.y); st[2] += uf(t.z); st[3] += uf(t.w); }
    }
    const float m0 = st[0] * (1.f / DM), m1 = st[1] * (1.f / DM);
    const float q0 = rsqrtf(fmaxf(st[2] * (1.f / DM) - m0 * m0, 0.f) + 1e-5f), q1 = rsqrtf(fmaxf(st[3] * (1.f / DM) - m1 * m1, 0.f) + 1e-5f);
    if (act) {
        uint8_t* d = (SECOND ? g_x1 + seg * XIMG + (fa >> 6) * 4096 : g_xf + ro * (9 * 8192) + (fa >> 6) * 8192) + p * 256 + (i & 1) * 8;
#pragma unroll
        for (int e = 0; e < 2; e++) {
            const float m = e ? m1 : m0, q = e ? q1 : q0;
#pragma unroll
            for (int h = 0; h < 2; h++) {
                const float* y = &f[2 * h + e];
                stg64(d + e * 128 + (((((fa >> 3) & 6) + h) ^ ((2 * p + e) & 7)) << 4), pack2((y[0] - m) * q, (y[4] - m) * q), pack2((y[8] - m) * q, (y[12] - m) * q));
            }
        }
    }
}
__device__ __forceinline__ void reducer(const Params& P) {
    const bool chain = blockIdx.x >= NENG + 16;
    if (threadIdx.x < 352) {
#pragma unroll 1
        for (int j = 0; j < 2 * NSEG; j++) {
            mbar_wait(bars + FB_JOB * 8, j & 1);
            const int job = lds32(sb + F_RED + 64 + (j & 1) * 4);
            if (job >= 256) { if (chain) reduce_job<true, true>(P, job - 256); else reduce_job<true, false>(P, job - 256); }
            else { if (chain) reduce_job<false, true>(P, job); else reduce_job<false, false>(P, job); }
            mbar_arrive_warp(bars + FB_RDONE * 8);
        }
    } else if (threadIdx.x == 352) {
        mbar_arrive(bars + FB_JOB * 8);
#pragma unroll 1
        for (int j = 0; j < 2 * NSEG; j++) {
            mbar_wait(bars + FB_RDONE * 8, j & 1);
            const int job = lds32(sb + F_RED + 64 + (j & 1) * 4);
            mbar_arrive(bars + FB_JOB * 8);
            TG(job & 255, 23 + (job >> 8));
            if (job < 256 || !chain) publish(job < 256 ? F_XF : F_X1, job & 255);
            TG(job & 255, 26 + 2 * (job >> 8));
        }
    }
    __syncwarp();
}

__host__ __device__ constexpr int d_rf(int u) { return u < 48 ? ((u & 3) < 2 ? (u >> 2) * 2 + (u & 1) : -1) : u == 48 ? 24 : -1; }
__host__ __device__ constexpr int d_ss(int u) { return u < 48 ? (u >> 2) * 2 + (u & 1) : u - 25; }
template <bool WIDE, int wg>
__device__ __forceinline__ void d_main() {
    constexpr int NR = WIDE ? 24 : NRD;
    uint32_t w[NR][4];
    {
        const uint32_t fa = sb + wg * (NRD * 2048) + unit_frag_addr(threadIdx.x);
        mbar_wait(bars + DB_WL * 8, 0);
#pragma unroll
        for (int u = 0; u < NR; u++) ldsm4t(w[u], fa + u * 2048);
        nbar_arrive(NB_W, 416);
        mbar_wait(bars + DB_WL * 8, 1);
    }
    const uint64_t da = mkdesc(wg * ((52 - NRD) * 2048), 1024, 1024, 1);
#pragma unroll 1
    for (int b = 0; b < NSTEP; b++) {
#pragma unroll
        for (int T = 0; T < (WIDE ? 3 : 1); T++) {
            float d[32];
            constexpr int NB = WIDE ? 4 : 13;
#pragma unroll
            for (int blk = 0; blk < NB; blk++) {
                const int c = blk;
                if (T == 0 || blk == 0) mbar_wait(bars + (DB_FULL + (c & 7)) * 8, WIDE || (c & 7) >= 5 ? b & 1 : c >> 3);
                if (blk == 0) wg_fence();
                const uint64_t db = mkdesc(D_B + (c & 7) * 8192, 8192, 1024, 1);
#pragma unroll
                for (int j = 0; j < 4; j++) {
                    const int u = T * 16 + blk * 4 + j;
                    if (d_rf(u) >= 0) wg_rs64<1>(d, w[d_rf(u) >= 0 ? d_rf(u) : 0], db + j * 128, blk + j > 0);
                    else wg_ss64<1>(d, da + d_ss(u) * 128, db + j * 128, blk + j > 0);
                }
                wg_commit();
                if (!WIDE && blk > 0) { wg_wait<1>(); mbar_arrive_warp(bars + (DB_EMPTY + ((c - 1) & 7)) * 8); }
            }
            const int tid = fresh_tid(), t = tid & 3, ds = fresh_bid() - NENG - NF1;
            const bool w2 = ds >= 15;
            const int tile = WIDE ? wg * 3 + T : (ds % 3) * 3 + wg;
            uint8_t* dst = (w2 ? g_p2 + ((b & (RING - 1)) * NP2 + (WIDE ? ds - 25 : (ds - 15) / 3)) * PART : g_p1 + ((b & (RING - 1)) * NP1 + ds / 3) * PART)
                         + (tile * 64 + ((tid >> 5) & 3) * 16 + ((tid & 31) >> 2) * 2) * 4 + (w2 ? 4 * t : t) * (DM * 4);
            const uint32_t js = w2 ? DM * 4 : DM * 16;
            wg_wait_acc<0, 32>(d);
            if (!WIDE) mbar_arrive_warp(bars + (DB_EMPTY + ((NB - 1) & 7)) * 8);
            else if (T == 2) {
#pragma unroll
                for (int blk = 0; blk < 4; blk++) mbar_arrive_warp(bars + (DB_EMPTY + blk) * 8);
            }
#pragma unroll
            for (int j = 0; j < 8; j++) stg64(dst + (j >> 2) * (DM * 64) + (j & 3) * js, pack2(d[4 * j], d[4 * j + 1]), pack2(d[4 * j + 2], d[4 * j + 3]));
        }
        mbar_wait(bars + (DB_P + 1) * 8, (b & 1) ^ 1);
        mbar_arrive_warp(bars + DB_P * 8);
    }
}
__device__ __forceinline__ void d_helper(const Params& P, int ds) {
    const int lane = threadIdx.x & 31, hw = (threadIdx.x >> 5) & 3;
    const bool w2 = ds >= 15, wide = ds >= 30;
    const int blk0 = wide ? 65 + (ds - 30) * 4 : ((w2 ? ds - 15 : ds) / 3) * 13, nb = wide ? 4 : 13;
    if (hw == 0) {
        const int nu = wide ? 48 : 52;
#pragma unroll 1
        for (int ph = 0; ph < 2; ph++) {
            if (ph) nbar_sync(NB_W, 416);
            if (lane == 0) mbar_expect(bars + DB_WL * 8, (wide ? 72 : ph ? 3 * (52 - NRD) : 3 * NRD) * 2048);
            __syncwarp();
#pragma unroll 1
            for (int x = lane; x < 3 * nu; x += 32) {
                const int wg = x / nu, u = x - wg * nu;
                if ((d_rf(u) < 0) == (ph != 0))
                    tma_unit(sb + (ph ? wg * (52 - NRD) + d_ss(u) : wg * NRD + d_rf(u)) * 2048, w2 ? &P.tmW2 : &P.tmWo,
                             blk0 * 4 + (wide ? u & 15 : u), wide ? wg * 3 + (u >> 4) : (ds % 3) * 3 + wg, bars + DB_WL * 8);
            }
        }
        __syncwarp();
        if (lane == 0) {
            const uint32_t target = (w2 ? NF1 : NENG) * this_launch();
#pragma unroll 1
            for (int b = 0; b < NSTEP; b++) {
                flag_wait(w2 ? F_H : F_O, b, target);
                TG(b, 29);
                const uint8_t* src = (w2 ? g_h + (b & (RING - 1)) * H_BYTES : g_o + (b & (RING - 1)) * O_BYTES) + blk0 * 8192;
#pragma unroll 1
                for (int blk = 0; blk < nb; blk++) {
                    const int c = blk;
                    mbar_wait(bars + (DB_EMPTY + (c & 7)) * 8, (wide || (c & 7) >= 5 ? b & 1 : c >> 3) ^ 1);
                    mbar_expect(bars + (DB_FULL + (c & 7)) * 8, 8192);
                    bulk_g2s(sb + D_B + (c & 7) * 8192, src + blk * 8192, 8192, bars + (DB_FULL + (c & 7)) * 8);
                }
            }
        }
    } else if (hw == 1 && lane == 0) {
        publisher(bars + DB_P * 8, bars + (DB_P + 1) * 8, w2 ? F_P2 : F_P1);
    }
    __syncwarp();
}

__device__ __forceinline__ void sign_off() { mbar_arrive_warp(sb + SM_DONE); }
__device__ __forceinline__ void sign_off_helper() {
    if (fresh_tid() < NTHREADS - 32) { sign_off(); return; }
    uint32_t ok, t0, t1;
    asm volatile("mov.u32 %0, %%globaltimer_lo;" : "=r"(t0));
    while (true) {
        asm volatile("{.reg .pred p; mbarrier.try_wait.parity.shared::cta.b64 p, [%1], 0, 0x100000; selp.u32 %0, 1, 0, p;}" : "=r"(ok) : "r"(sb + SM_DONE) : "memory");
        if (ok) break;
        asm volatile("mov.u32 %0, %%globaltimer_lo;" : "=r"(t1));
        if (t1 - t0 > 2000000000u) __trap();
    }
    if (fresh_tid() == NTHREADS - 32) { g_epoch[fresh_bid()][0] = this_launch(); TG(79, 1); }
    __syncwarp();
}

__global__ void __cluster_dims__(2, 1, 1) __launch_bounds__(NTHREADS, 1) fused_kernel(const __grid_constant__ Params P) {
    const int wg = __shfl_sync(~0u, threadIdx.x >> 7, 0);
    const int bid = blockIdx.x;
    if (threadIdx.x == 0) {
        if ((sb & 0x3ffff) != SM_ORG) __trap();
        TG(79, 0);
        mbar_init(sb + SM_DONE, 15);
        if (bid < NENG) {
            for (int i = 0; i < 11; i++) mbar_init(bars + (EB_FULL + i) * 8, 1);
            mbar_init(bars + EB_V0 * 8, 4);
            for (int i = 0; i < 4; i++) mbar_init(bars + (EB_EMPTY + i) * 8, 12);
            mbar_init(bars + EB_WL * 8, 3); mbar_init(bars + EB_WO * 8, 1); mbar_init(bars + EB_STEP * 8, 8);
            mbar_init(bars + EB_VX * 8, 1); mbar_init(bars + EB_SM * 8, 1); mbar_init(bars + EB_SX * 8, 1); mbar_init(bars + EB_VM * 8, 6);
            mbar_init(bars + EB_QF * 8, 4); mbar_init(bars + EB_KF * 8, 8); mbar_init(bars + EB_MEM * 8, 4); mbar_init(bars + EB_PRDY * 8, 1);
            mbar_init(bars + EB_CONS * 8, 4); mbar_init(bars + EB_OST * 8, 4); mbar_init(bars + EB_OFREE * 8, 1);
        } else if (bid < NENG + NF1) {
            for (int i = 0; i < 9; i++) { mbar_init(bars + (FB_FULL + i) * 8, 1); mbar_init(bars + (FB_EMPTY + i) * 8, 8); }
            mbar_init(bars + FB_H * 8, 8); mbar_init(bars + FB_RACK * 8, 1); mbar_init(bars + FB_JOB * 8, 2); mbar_init(bars + FB_RDONE * 8, 3);
        } else {
            for (int i = 0; i < 8; i++) { mbar_init(bars + (DB_FULL + i) * 8, 1); mbar_init(bars + (DB_EMPTY + i) * 8, 12); }
            mbar_init(bars + DB_WL * 8, 1); mbar_init(bars + DB_P * 8, 12); mbar_init(bars + (DB_P + 1) * 8, 1);
        }
        asm volatile("fence.mbarrier_init.release.cluster;" ::: "memory");
    }
    __syncthreads();
    if (bid < NENG) {
        if (wg == 0) { reg_inc<REGQ>(); engine_main<0>(P); sign_off(); cluster_sync_all(); }
        else if (wg == 1) { reg_inc<REGK>(); engine_main<1>(P); sign_off(); cluster_sync_all(); }
        else if (wg == 2) { reg_inc<REGV>(); engine_main<2>(P); sign_off(); cluster_sync_all(); }
        else { reg_dec<24>(); engine_helper(P); sign_off_helper(); cluster_sync_all(); }
    } else if (bid < NENG + NF1) {
        if (wg < 2) {
            reg_inc<200>();
            if (wg == 0) f1_main<0>(P); else f1_main<1>(P);
            sign_off();
        } else if (wg == 2) {
            reg_dec<88>();
            if (bid >= NENG + 32) ln0_rows(P, (bid - NENG - 32) * 4 + ((threadIdx.x >> 5) & 3));
            else reducer(P);
            sign_off();
        } else {
            reg_dec<24>();
            f1_helper();
            sign_off_helper();
        }
    } else {
        const int ds = bid - NENG - NF1;
        if (wg < 3) {
            reg_inc<160>();
            if (ds < 30) { if (wg == 0) d_main<false, 0>(); else if (wg == 1) d_main<false, 1>(); else d_main<false, 2>(); }
            else { if (wg == 0) d_main<true, 0>(); else if (wg == 1) d_main<true, 1>(); else d_main<true, 2>(); }
            sign_off();
        } else {
            reg_dec<32>();
            d_helper(P, ds);
            sign_off_helper();
        }
    }
}

typedef CUresult (*EncodeFn)(CUtensorMap*, CUtensorMapDataType, cuuint32_t, void*, const cuuint64_t*, const cuuint64_t*,
                             const cuuint32_t*, const cuuint32_t*, CUtensorMapInterleave, CUtensorMapSwizzle,
                             CUtensorMapL2promotion, CUtensorMapFloatOOBfill);

void make_map(EncodeFn enc, CUtensorMap* m, const void* p, int rows, int cols) {
    cuuint64_t dims[2] = {(cuuint64_t)cols, (cuuint64_t)rows};
    cuuint64_t strides[1] = {(cuuint64_t)cols * 2};
    cuuint32_t box[2] = {64, 16};
    cuuint32_t es[2] = {1, 1};
    enc(m, CU_TENSOR_MAP_DATA_TYPE_BFLOAT16, 2, (void*)p, dims, strides, box, es, CU_TENSOR_MAP_INTERLEAVE_NONE,
        CU_TENSOR_MAP_SWIZZLE_128B, CU_TENSOR_MAP_L2_PROMOTION_L2_128B, CU_TENSOR_MAP_FLOAT_OOB_FILL_NONE);
}

}

extern "C" void kernel_launch(void* const* d_in, const int* in_sizes, int n_in, void* d_out, int out_size) {
    (void)in_sizes; (void)n_in; (void)out_size;
    static EncodeFn enc = nullptr;
    if (!enc) {
        void* fn = nullptr;
        cudaDriverEntryPointQueryResult qr;
        cudaGetDriverEntryPoint("cuTensorMapEncodeTiled", &fn, cudaEnableDefault, &qr);
        enc = (EncodeFn)fn;
        cudaFuncSetAttribute(fused_kernel, cudaFuncAttributeMaxDynamicSharedMemorySize, SM_TOTAL);
    }
    Params P;
    make_map(enc, &P.tmWq, d_in[2], DM, 4096);
    make_map(enc, &P.tmWk, d_in[3], DM, 4096);
    make_map(enc, &P.tmWv, d_in[4], DM, 4096);
    make_map(enc, &P.tmWo, d_in[5], 4096, DM);
    make_map(enc, &P.tmW2, d_in[10], FF, DM);
    P.x = (const bf16*)d_in[0];
    P.mem0 = (const bf16*)d_in[1];
    P.w1 = (const bf16*)d_in[8];
    P.w3 = (const bf16*)d_in[9];
    P.out = (bf16*)d_out;
    fused_kernel<<<NCTA, NTHREADS, SM_TOTAL>>>(P);
}
```

```cpp
#include <cuda_runtime.h>
#include <cuda_bf16.h>
#include <cuda.h>
#include <stdint.h>

typedef __nv_bfloat16 bf16;

namespace {

constexpr int DM = 576, FF = 4608, NSEG = 64;
constexpr int NENG = 64, NF1 = 36, ND = 32, NCTA = NENG + NF1 + ND;
constexpr int NTHREADS = 512;
#define LAG 7
#define RING 8
static_assert(RING > LAG, "ring too short");
constexpr int NSTEP = NSEG + LAG;

enum { F_X0 = 0, F_X1, F_O, F_P1, F_XF, F_H, F_P2, F_COUNT };
__device__ uint32_t g_flag[F_COUNT][96][8];
__device__ uint32_t g_epoch[NCTA][8];
constexpr int XIMG = 9 * 4096;
constexpr int O_BYTES = 65 * 8192;
constexpr int H_BYTES = 73 * 8192;
constexpr int PART = 32 * DM * 4;
constexpr int NP1 = 5, NP2 = 7;
__device__ __align__(1024) uint8_t g_x0[NSEG * XIMG];
__device__ __align__(1024) uint8_t g_x1[NSEG * XIMG];
__device__ __align__(1024) uint8_t g_xf[RING * 9 * 8192];
__device__ __align__(1024) uint8_t g_o[RING * O_BYTES];
__device__ __align__(1024) uint8_t g_h[RING * H_BYTES];
__device__ __align__(1024) uint8_t g_p1[RING * NP1 * PART];
__device__ __align__(1024) uint8_t g_p2[RING * NP2 * PART];
__device__ __align__(1024) uint8_t g_r1[RING * PART];
__device__ __align__(1024) uint8_t g_r2[NSEG * PART / 2];
#define AR_STR 4352
constexpr int AR_SLOT = 144 * AR_STR;
__device__ __align__(1024) uint8_t g_ar[4 * AR_SLOT];

struct Params {
    CUtensorMap tmWq, tmWk, tmWv, tmWo, tmW2;
    const bf16 *x, *mem0, *w1, *w3;
    bf16* out;
    uint32_t zero;
};

constexpr uint32_t SM_ORG = 1024;
extern __shared__ __align__(1024) uint8_t smem_raw[];
#define sb ((uint32_t)__cvta_generic_to_shared(smem_raw))
#define bars (sb + SM_BAR)
constexpr int SM_BAR = 231936;
constexpr int SM_TOTAL = SM_BAR + 512;
#define NRQ 27
#define NRK 23
#define NRV 25
#define REGQ 168
#define REGK 160
#define REGV 160
constexpr int E_WQ = 0;
constexpr int E_WK = E_WQ + (36 - NRQ) * 2048;
constexpr int E_WV = E_WK + (36 - NRK) * 2048;
constexpr int E_WO = E_WV + (36 - NRV) * 2048;
constexpr int E_MEM = E_WO + 36 * 2048;
constexpr int E_R0 = E_MEM + 18432;
constexpr int E_R1 = E_R0 + 8192, E_R2 = E_R1 + 8192;
constexpr int E_SX = E_R1;
constexpr int E_QT = E_R2 + 8192;
constexpr int E_KT = E_QT + 8192;
constexpr int E_VT = E_KT + 10240;
constexpr int E_VP = E_VT + 10240;
constexpr int E_VF = E_VP + 8192;
constexpr int E_QM = E_VF + 4096;
constexpr int E_SR = E_QM + 2048;
constexpr int E_SL = E_SR + 2560;
constexpr int E_END = E_SL + 2048;
constexpr int E_OM = E_MEM + 16384, OM_STR = E_QM - E_OM;
static_assert(E_END <= SM_BAR, "engine smem overflow");
static_assert(E_WO + (NRQ + NRK + NRV) * 2048 <= SM_BAR, "weight staging overflow");
enum {
    EB_FULL = 0, EB_EMPTY = 11  , EB_V0 = 15, EB_WL, EB_WO, EB_STEP, EB_VX, EB_SM, EB_SX, EB_VM, EB_QF, EB_KF, EB_CONS, EB_OST, EB_OFREE,
    EB_MEM, EB_PRDY
};
enum { NB_G = 1, NB_LEAD, NB_QK, NB_S, NB_OM, NB_W, NB_R, NB_T, NB_PV, NB_WO, NB_V, NB_KT, NB_S2, NB_VL };
constexpr int NB_VL2 = NB_LEAD;
constexpr int NRF = 35;
constexpr int F_W = 0;
constexpr int F_X = 2 * (72 - NRF) * 2048;
constexpr int F_RED = F_X + 9 * 8192;
static_assert(F_RED + 512 <= SM_BAR, "F1 smem overflow");
enum { FB_FULL = 0, FB_EMPTY = 9, FB_H = 18, FB_RACK, FB_JOB, FB_RDONE };
constexpr int NRD = 25;
constexpr int D_B = 3 * (52 - NRD) * 2048;
static_assert(D_B + 8 * 8192 <= SM_BAR, "D smem overflow");
enum { DB_FULL = 0, DB_EMPTY = 8, DB_WL = 16, DB_P };
constexpr int SM_DONE = SM_BAR + 240, SM_XRDY = SM_BAR + 248, SM_ONES = SM_BAR + 384;
constexpr uint32_t TIME_LIMIT = 2000000000u;

#define SPIN_CHECK(n, code)

#define TS(thr, step, k)
#define TX(thr, k)
#define TG(step, k)
#define PROF_INC(n, k)

__device__ __forceinline__ uint32_t mapa(uint32_t a, uint32_t r) {
    uint32_t o; asm("mapa.shared::cluster.u32 %0, %1, %2;" : "=r"(o) : "r"(a), "r"(r)); return o;
}
__device__ __forceinline__ void mbar_init(uint32_t b, uint32_t cnt) {
    asm volatile("mbarrier.init.shared::cta.b64 [%0], %1;" :: "r"(b), "r"(cnt) : "memory");
}
__device__ __forceinline__ void mbar_arrive(uint32_t b) {
    asm volatile("mbarrier.arrive.shared::cta.b64 _, [%0];" :: "r"(b) : "memory");
}
__device__ __forceinline__ void mbar_arrive_warp(uint32_t b) {
    asm volatile("{.reg .pred p; bar.warp.sync -1; elect.sync _|p, -1; @p mbarrier.arrive.shared::cta.b64 _, [%0];}" :: "r"(b) : "memory");
}
__device__ __forceinline__ void mbar_arrive_remote(uint32_t b) {
    asm volatile("fence.release.sync_restrict::shared::cta.cluster; mbarrier.arrive.relaxed.cluster.shared::cluster.b64 _, [%0];" :: "r"(b) : "memory");
}
__device__ __forceinline__ void mbar_expect(uint32_t b, uint32_t bytes) {
    asm volatile("mbarrier.arrive.expect_tx.shared::cta.b64 _, [%0], %1;" :: "r"(b), "r"(bytes) : "memory");
}
__device__ __forceinline__ void mbar_wait(uint32_t b, uint32_t par) {
    uint32_t ok; [[maybe_unused]] int n = 0;
    while (true) {
        asm volatile("{.reg .pred p; mbarrier.try_wait.parity.shared::cta.b64 p, [%1], %2; selp.u32 %0, 1, 0, p;}"
                     : "=r"(ok) : "r"(b), "r"(par) : "memory");
        if (ok) break;
        SPIN_CHECK(n, 1000 + ((b & 511) >> 3));
    }
}
__device__ __forceinline__ void mbar_wait_cl(uint32_t b, uint32_t par) {
    uint32_t ok; [[maybe_unused]] int n = 0;
    while (true) {
        asm volatile("{.reg .pred p; mbarrier.try_wait.parity.relaxed.cluster.shared::cta.b64 p, [%1], %2; selp.u32 %0, 1, 0, p;}"
                     : "=r"(ok) : "r"(b), "r"(par) : "memory");
        if (ok) break;
        SPIN_CHECK(n, 1000 + ((b & 511) >> 3));
    }
    asm volatile("fence.acquire.sync_restrict::shared::cluster.cluster;" ::: "memory");
}
__device__ __forceinline__ void nbar_sync(int id, int n) { asm volatile("bar.sync %0, %1;" :: "r"(id), "r"(n) : "memory"); }
__device__ __forceinline__ void nbar_arrive(int id, int n) { asm volatile("bar.arrive %0, %1;" :: "r"(id), "r"(n) : "memory"); }
__device__ __forceinline__ void cluster_sync_all() {
    asm volatile("barrier.cluster.arrive.release.aligned; barrier.cluster.wait.acquire.aligned;" ::: "memory");
}
__device__ __forceinline__ void fence_async_smem() { asm volatile("fence.proxy.async.shared::cta;" ::: "memory"); }
__device__ __forceinline__ void fence_async_glb() { asm volatile("fence.proxy.async.global;" ::: "memory"); }
__device__ __forceinline__ void fence_rel_gpu() { asm volatile("fence.release.gpu;" ::: "memory"); }
__device__ __forceinline__ void fence_acq_gpu() { asm volatile("fence.acquire.gpu;" ::: "memory"); }
__device__ __forceinline__ void fence_gpu() { asm volatile("fence.acq_rel.gpu;" ::: "memory"); }
__device__ __forceinline__ int fresh_tid() { int t; asm volatile("mov.u32 %0, %%tid.x;" : "=r"(t)); return t; }
__device__ __forceinline__ int fresh_bid() { int t; asm volatile("mov.u32 %0, %%ctaid.x;" : "=r"(t)); return t; }
__device__ __forceinline__ uint32_t pin(uint32_t v) { asm volatile("" : "+r"(v)); return v; }
__device__ __forceinline__ int warp_in_group() { return __shfl_sync(~0u, (fresh_tid() >> 5) & 3, 0); }
__device__ __forceinline__ int cta_rank() { int t; asm volatile("mov.u32 %0, %%cluster_ctarank;" : "=r"(t)); return t; }
__device__ __forceinline__ uint32_t timer_lo() { uint32_t t; asm volatile("mov.u32 %0, %%globaltimer_lo;" : "=r"(t)); return t; }
__device__ __forceinline__ uint32_t keep(uint32_t v) { return __shfl_xor_sync(~0u, v, 0); }
__device__ __forceinline__ void red_add_u32(uint32_t* p, uint32_t v) {
    asm volatile("red.relaxed.gpu.global.add.u32 [%0], %1;" :: "l"(p), "r"(v) : "memory");
}
__device__ __forceinline__ uint32_t ld_rlx(const void* p) {
    uint32_t v; asm volatile("ld.relaxed.gpu.global.u32 %0, [%1];" : "=r"(v) : "l"(p) : "memory"); return v;
}
__device__ __forceinline__ uint2 ld_rlx64(const void* p) {
    uint2 v; asm volatile("ld.relaxed.gpu.global.v2.u32 {%0,%1}, [%2];" : "=r"(v.x), "=r"(v.y) : "l"(p) : "memory"); return v;
}
__device__ __forceinline__ uint4 ld_rlx128(const void* p) {
    uint4 v;
    asm volatile("ld.relaxed.gpu.global.v4.u32 {%0,%1,%2,%3}, [%4];" : "=r"(v.x), "=r"(v.y), "=r"(v.z), "=r"(v.w) : "l"(p) : "memory");
    return v;
}
__device__ __forceinline__ void stg128(void* p, uint4 v) {
    asm volatile("st.global.v4.b32 [%0], {%1,%2,%3,%4};" :: "l"(p), "r"(v.x), "r"(v.y), "r"(v.z), "r"(v.w) : "memory");
}
__device__ __forceinline__ void stg64(void* p, uint32_t a, uint32_t b) {
    asm volatile("st.global.v2.b32 [%0], {%1,%2};" :: "l"(p), "r"(a), "r"(b) : "memory");
}
__device__ __forceinline__ void st_async128(uint32_t a, uint32_t x, uint32_t y, uint32_t z, uint32_t w, uint32_t mb) {
    asm volatile("st.async.shared::cluster.mbarrier::complete_tx::bytes.v4.b32 [%0], {%1,%2,%3,%4}, [%5];"
                 :: "r"(a), "r"(x), "r"(y), "r"(z), "r"(w), "r"(mb) : "memory");
}
__device__ __forceinline__ void st_async64(uint32_t a, uint32_t x, uint32_t y, uint32_t mb) {
    asm volatile("st.async.shared::cluster.mbarrier::complete_tx::bytes.v2.b32 [%0], {%1,%2}, [%3];"
                 :: "r"(a), "r"(x), "r"(y), "r"(mb) : "memory");
}
__device__ __forceinline__ void sts128(uint32_t a, uint32_t x, uint32_t y, uint32_t z, uint32_t w) {
    asm volatile("st.shared.v4.b32 [%0], {%1,%2,%3,%4};" :: "r"(a), "r"(x), "r"(y), "r"(z), "r"(w) : "memory");
}
__device__ __forceinline__ void sts32(uint32_t a, uint32_t v) { asm volatile("st.shared.b32 [%0], %1;" :: "r"(a), "r"(v) : "memory"); }
__device__ __forceinline__ uint4 lds128(uint32_t a) {
    uint4 v; asm volatile("ld.shared.v4.b32 {%0,%1,%2,%3}, [%4];" : "=r"(v.x), "=r"(v.y), "=r"(v.z), "=r"(v.w) : "r"(a) : "memory"); return v;
}
__device__ __forceinline__ uint2 lds64(uint32_t a) {
    uint2 v; asm volatile("ld.shared.v2.b32 {%0,%1}, [%2];" : "=r"(v.x), "=r"(v.y) : "r"(a) : "memory"); return v;
}
__device__ __forceinline__ uint32_t lds32(uint32_t a) {
    uint32_t v; asm volatile("ld.shared.b32 %0, [%1];" : "=r"(v) : "r"(a) : "memory"); return v;
}
__device__ __forceinline__ void bulk_g2s(uint32_t dst, const void* src, uint32_t bytes, uint32_t mb) {
    asm volatile("cp.async.bulk.shared::cluster.global.mbarrier::complete_tx::bytes [%0], [%1], %2, [%3];"
                 :: "r"(dst), "l"(src), "r"(bytes), "r"(mb) : "memory");
}
__device__ __forceinline__ void bulk_s2g(void* dst, uint32_t src, uint32_t bytes) {
    asm volatile("cp.async.bulk.global.shared::cta.bulk_group [%0], [%1], %2;" :: "l"(dst), "r"(src), "r"(bytes) : "memory");
}
__device__ __forceinline__ void bulk_s2peer(uint32_t dst, uint32_t src, uint32_t bytes, uint32_t mb) {
    asm volatile("cp.async.bulk.shared::cluster.shared::cta.mbarrier::complete_tx::bytes [%0], [%1], %2, [%3];"
                 :: "r"(dst), "r"(src), "r"(bytes), "r"(mb) : "memory");
}
__device__ __forceinline__ void tma_unit(uint32_t dst, const CUtensorMap* tm, int kstep, int mgroup, uint32_t mb) {
    asm volatile("cp.async.bulk.tensor.2d.shared::cluster.global.mbarrier::complete_tx::bytes [%0], [%1, {%2,%3}], [%4];"
                 :: "r"(dst), "l"(tm), "r"(mgroup * 64), "r"(kstep * 16), "r"(mb) : "memory");
}
__device__ __forceinline__ void ldsm4(uint32_t* r, uint32_t a) {
    asm volatile("ldmatrix.sync.aligned.m8n8.x4.shared.b16 {%0,%1,%2,%3}, [%4];"
                 : "=r"(r[0]), "=r"(r[1]), "=r"(r[2]), "=r"(r[3]) : "r"(a) : "memory");
}
__device__ __forceinline__ void ldsm4t(uint32_t* r, uint32_t a) {
    asm volatile("ldmatrix.sync.aligned.m8n8.x4.trans.shared.b16 {%0,%1,%2,%3}, [%4];"
                 : "=r"(r[0]), "=r"(r[1]), "=r"(r[2]), "=r"(r[3]) : "r"(a) : "memory");
}
__device__ __forceinline__ void stsm4(uint32_t a, uint32_t r0, uint32_t r1, uint32_t r2, uint32_t r3) {
    asm volatile("stmatrix.sync.aligned.m8n8.x4.shared.b16 [%0], {%1,%2,%3,%4};" :: "r"(a), "r"(r0), "r"(r1), "r"(r2), "r"(r3) : "memory");
}
__device__ __forceinline__ void stsm4t(uint32_t a, uint32_t r0, uint32_t r1, uint32_t r2, uint32_t r3) {
    asm volatile("stmatrix.sync.aligned.m8n8.x4.trans.shared.b16 [%0], {%1,%2,%3,%4};" :: "r"(a), "r"(r0), "r"(r1), "r"(r2), "r"(r3) : "memory");
}
__device__ __forceinline__ uint32_t pack2(float lo, float hi) {
    uint32_t d; asm("cvt.rn.bf16x2.f32 %0, %1, %2;" : "=r"(d) : "f"(hi), "f"(lo)); return d;
}
__device__ __forceinline__ float bf_lo(uint32_t w) { return __uint_as_float(w << 16); }
__device__ __forceinline__ float bf_hi(uint32_t w) { return __uint_as_float(w & 0xffff0000u); }
__device__ __forceinline__ float ex2(float x) { float y; asm("ex2.approx.ftz.f32 %0, %1;" : "=f"(y) : "f"(x)); return y; }
__device__ __forceinline__ float rcp(float x) { float y; asm("rcp.approx.ftz.f32 %0, %1;" : "=f"(y) : "f"(x)); return y; }
__device__ __forceinline__ uint32_t fu(float x) { return __float_as_uint(x); }
__device__ __forceinline__ float uf(uint32_t x) { return __uint_as_float(x); }
__device__ __forceinline__ void mma16816(float* d, const uint32_t* a, uint32_t b0, uint32_t b1) {
    asm volatile("mma.sync.aligned.m16n8k16.row.col.f32.bf16.bf16.f32 {%0,%1,%2,%3}, {%4,%5,%6,%7}, {%8,%9}, {%0,%1,%2,%3};"
                 : "+f"(d[0]), "+f"(d[1]), "+f"(d[2]), "+f"(d[3]) : "r"(a[0]), "r"(a[1]), "r"(a[2]), "r"(a[3]), "r"(b0), "r"(b1));
}
__device__ __forceinline__ void mma1688(float* d, uint32_t a0, uint32_t a1, uint32_t b0) {
    asm volatile("mma.sync.aligned.m16n8k8.row.col.f32.bf16.bf16.f32 {%0,%1,%2,%3}, {%4,%5}, {%6}, {%0,%1,%2,%3};"
                 : "+f"(d[0]), "+f"(d[1]), "+f"(d[2]), "+f"(d[3]) : "r"(a0), "r"(a1), "r"(b0));
}
template <int N> __device__ __forceinline__ void reg_inc() { asm volatile("setmaxnreg.inc.sync.aligned.u32 %0;" :: "n"(N)); }
template <int N> __device__ __forceinline__ void reg_dec() { asm volatile("setmaxnreg.dec.sync.aligned.u32 %0;" :: "n"(N)); }

__device__ __forceinline__ uint64_t mkdesc(uint32_t addr, uint32_t lbo, uint32_t sbo, uint32_t swz) {
    return (uint64_t)((addr + SM_ORG) >> 4) | ((uint64_t)(lbo >> 4) << 16) | ((uint64_t)(sbo >> 4) << 32) | ((uint64_t)swz << 62);
}
__device__ __forceinline__ void wg_fence() { asm volatile("wgmma.fence.sync.aligned;" ::: "memory"); }
__device__ __forceinline__ void wg_commit() { asm volatile("wgmma.commit_group.sync.aligned;" ::: "memory"); }
template <int N> __device__ __forceinline__ void wg_wait() { asm volatile("wgmma.wait_group.sync.aligned %0;" :: "n"(N) : "memory"); }
template <int M> __device__ __forceinline__ void acc_ready(float* d) {
#pragma unroll
    for (int j = 0; j < M; j++) asm volatile("" : "+f"(d[j]) :: "memory");
}
template <int N, int M> __device__ __forceinline__ void wg_wait_acc(float* d) { wg_wait<N>(); acc_ready<M>(d); }

#define F8(c, d, o) c(d[o]), c(d[o + 1]), c(d[o + 2]), c(d[o + 3]), c(d[o + 4]), c(d[o + 5]), c(d[o + 6]), c(d[o + 7])
#define R8L "%0,%1,%2,%3,%4,%5,%6,%7"
#define R16L R8L ",%8,%9,%10,%11,%12,%13,%14,%15"
#define R32L R16L ",%16,%17,%18,%19,%20,%21,%22,%23,%24,%25,%26,%27,%28,%29,%30,%31"
#define R40L R32L ",%32,%33,%34,%35,%36,%37,%38,%39"
#define WG_BOTH(TXT_PRE, TXT_POST, OUTS, ...)                                                   \
    if (acc) asm volatile(TXT_PRE "1" TXT_POST : OUTS("+f") : __VA_ARGS__);                     \
    else asm volatile(TXT_PRE "0" TXT_POST : OUTS("=f") : __VA_ARGS__)
#define O8(c) F8(c, d, 0)
#define O16(c) F8(c, d, 0), F8(c, d, 8)
#define O32(c) O16(c), F8(c, d, 16), F8(c, d, 24)
#define O40(c) O32(c), F8(c, d, 32)
#define WGM(n) "wgmma.mma_async.sync.aligned.m64n" #n "k16.f32.bf16.bf16 "
__device__ __forceinline__ void wg_rs16(float* d, const uint32_t* a, uint64_t db, bool acc) {
    WG_BOTH(WGM(16) "{" R8L "}, {%8,%9,%10,%11}, %12, ", ", 1, 1, 1;", O8, "r"(a[0]), "r"(a[1]), "r"(a[2]), "r"(a[3]), "l"(db));
}
__device__ __forceinline__ void wg_ss16(float* d, uint64_t da, uint64_t db, bool acc) {
    WG_BOTH(WGM(16) "{" R8L "}, %8, %9, ", ", 1, 1, 1, 1;", O8, "l"(da), "l"(db));
}
__device__ __forceinline__ void wg_rs8(float* d, const uint32_t* a, uint64_t db, bool acc) {
#define O4(c) c(d[0]), c(d[1]), c(d[2]), c(d[3])
    WG_BOTH(WGM(8) "{%0,%1,%2,%3}, {%4,%5,%6,%7}, %8, ", ", 1, 1, 0;", O4, "r"(a[0]), "r"(a[1]), "r"(a[2]), "r"(a[3]), "l"(db));
}
__device__ __forceinline__ void wg_rs32(float* d, const uint32_t* a, uint64_t db, bool acc) {
    WG_BOTH(WGM(32) "{" R16L "}, {%16,%17,%18,%19}, %20, ", ", 1, 1, 0;", O16, "r"(a[0]), "r"(a[1]), "r"(a[2]), "r"(a[3]), "l"(db));
}
template <int TB> __device__ __forceinline__ void wg_rs64(float* d, const uint32_t* a, uint64_t db, bool acc) {
    WG_BOTH(WGM(64) "{" R32L "}, {%32,%33,%34,%35}, %36, ", ", 1, 1, %37;", O32, "r"(a[0]), "r"(a[1]), "r"(a[2]), "r"(a[3]), "l"(db), "n"(TB));
}
template <int TB> __device__ __forceinline__ void wg_ss64(float* d, uint64_t da, uint64_t db, bool acc) {
    WG_BOTH(WGM(64) "{" R32L "}, %32, %33, ", ", 1, 1, 1, %34;", O32, "l"(da), "l"(db), "n"(TB));
}
__device__ __forceinline__ void wg_ss80(float* d, uint64_t da, uint64_t db, bool acc) {
    WG_BOTH(WGM(80) "{" R40L "}, %40, %41, ", ", 1, 1, 1, 1;", O40, "l"(da), "l"(db));
}

constexpr float SM_SCALE = 0.08838834764831845f;
constexpr float LOG2E = 1.4426950408889634f;

__device__ __forceinline__ uint32_t* flag_ptr(int stage, int b) { return &g_flag[stage][b][0]; }
__device__ __forceinline__ uint32_t this_launch() { return ld_rlx(&g_epoch[fresh_bid()][0]) + 1; }
__device__ __forceinline__ bool flag_up(int stage, int b, uint32_t target) { return (int)(ld_rlx(flag_ptr(stage, b)) - target) >= 0; }
__device__ __forceinline__ void flag_wait(int stage, int b, uint32_t target) {
    [[maybe_unused]] int n = 0;
    while (!flag_up(stage, b, target)) {
        __nanosleep(20);
        SPIN_CHECK(n, 10 + stage);
    }
    fence_acq_gpu();
    fence_async_glb();
}
__device__ __forceinline__ void publish(int stage, int b) {
    fence_async_glb();
    fence_rel_gpu();
    red_add_u32(flag_ptr(stage, b), 1);
}
__device__ __forceinline__ uint32_t unit_frag_addr(int tid) {
    const int lane = tid & 31, w = (tid >> 5) & 3, i = lane & 7, j = lane >> 3;
    return ((j >> 1) * 8 + i) * 128 + ((((w << 1) + (j & 1)) ^ i) << 4);
}

#define V_BURST2 1
#define V_LEAD 9
static_assert(V_LEAD > 2 + V_BURST2, "q and k rely on v for the arrival of the blocks");
#define K_LEAD 0
#define Q_LEAD 36
#define V_FIRST 12
#define SX_GATE 1
#define PVX_LATE 1
#define V_EARLY 0
#define VM_EARLY 0
__host__ __device__ constexpr int x_order(int mat, int j) {
    return mat == 2 ? j : j < 2 ? j + 2 : j == 2 ? 6 : j < 5 ? j + 1 : j == 5 ? 8 : j == 6 ? 1 : j == 7 ? 7 : 0;
}
#define SS0Q 0
#define SS0K 0
#define SS0V 22
#define SSLQ 36
#define SSLK 36
#define SSLV 14
__host__ __device__ constexpr uint64_t ss_mask(int mat) {
    const int ns = 36 - (mat == 0 ? NRQ : mat == 1 ? NRK : NRV);
    const int j0 = mat == 0 ? SS0Q : mat == 1 ? SS0K : SS0V, len = mat == 0 ? SSLQ : mat == 1 ? SSLK : SSLV;
    uint64_t m = 0;
    for (int j = j0; j < j0 + len; j++)
        if ((j - j0) * ns / len != (j - j0 + 1) * ns / len) m |= 1ull << (x_order(mat, j >> 2) * 4 + (j & 3));
    return m;
}
__device__ __forceinline__ int popc_below(uint64_t m, int k) { return __popcll(m & ((1ull << k) - 1)); }
__host__ __device__ constexpr int x_slot(int f) {
    return f == 0 || f == 6 || f == 9 ? E_R0 : f == 1 || f == 7 ? E_R2 : f < 4 ? E_MEM + (f - 2) * 8192 : f == 4 ? E_QT : f == 5 ? E_KT : f == 8 ? E_VP : E_R1;
}
__host__ __device__ constexpr int x_empty(int blk) { return blk == 3 ? 0 : blk == 6 ? 1 : blk == 5 ? 2 : blk == 1 ? 3 : -1; }
__host__ __device__ constexpr int ar_tile(int j) { return j == 0 ? 8 : ((j - 1) & 1) * 4 + ((j - 1) & 2) + (j > 4); }
__host__ __device__ constexpr int sx_off(int u) { return u == 0 ? 0 : u == 1 ? 1536 : u == 2 ? 2560 : u == 3 ? 3072 : 5120; }

template <int MAT, int NR, int K0, int K1>
__device__ __forceinline__ void proj_mem(float* d, const uint32_t (&w)[NR][4]) {
    constexpr uint64_t M = ss_mask(MAT);
    const uint64_t db = mkdesc(E_MEM, 128, 9216, 0);
    const uint64_t da = mkdesc((MAT == 0 ? E_WQ : MAT == 1 ? E_WK : E_WV), 1024, 1024, 1);
#pragma unroll
    for (int ks = K0; ks < K1; ks++) {
        const int s = popc_below(M, ks);
        if ((M >> ks) & 1) wg_ss16(d, da + s * 128, db + ks * 16, ks > 0);
        else wg_rs16(d, w[ks - s], db + ks * 16, ks > 0);
    }
}
__device__ __forceinline__ uint32_t tl_lane(int tid, int group_bytes) {
    return ((tid >> 4) & 1) * group_bytes + (((tid >> 5) & 3) * 16 + (tid & 15)) * 16;
}
__device__ __forceinline__ void ar_red(uint8_t* p, uint8_t* q, const float* y) {
    asm volatile("red.relaxed.gpu.global.add.noftz.v4.bf16x2 [%0], {%1,%2,%3,%4};"
                 :: "l"(p), "r"(pack2(y[0], y[1])), "r"(pack2(y[2], y[3])), "r"(pack2(y[4], y[5])), "r"(pack2(y[6], 1.f)) : "memory");
    asm volatile("red.relaxed.gpu.global.add.noftz.bf16x2 [%0], %1;" :: "l"(q), "r"(pack2(y[7], 1.f)) : "memory");
}
__device__ __forceinline__ uint32_t ar_main(int tid) { return ((tid & 127) >> 3) * AR_STR + (tid & 7) * 16; }
__device__ __forceinline__ uint32_t ar_side(int tid) { return ((tid & 127) >> 5) * (4 * AR_STR) + AR_STR / 2 + (tid & 31) * 4; }

#define AR_LDQ 2
#define AR_LDK 2
#define AR_STQ 6
#define AR_STK 7
#define AR_VWAIT 1
#define AR_J1 3
#define AR_J2 5
template <int MAT> struct ArPart {
    static constexpr int J0 = MAT == 0 ? 0 : MAT == 1 ? AR_J1 : AR_J2, J1 = MAT == 0 ? AR_J1 : MAT == 1 ? AR_J2 : 9;
    uint4 av[J1 - J0];
    uint32_t as[J1 - J0];
    __device__ __forceinline__ void load(int i, int tid) {
        const uint8_t* pm = g_ar + ((i & 3) * AR_SLOT + ar_main(tid));
        const uint8_t* ps = g_ar + ((i & 3) * AR_SLOT + ar_side(tid));
#pragma unroll
        for (int j = J0; j < J1; j++) { av[j - J0] = ld_rlx128(pm + ar_tile(j) * (16 * AR_STR)); as[j - J0] = ld_rlx(ps + ar_tile(j) * (16 * AR_STR)); }
    }
    __device__ __forceinline__ void first_load(int i, int tid) {
        if (i >= 0) load(i, tid);
        else {
#pragma unroll
            for (int j = 0; j < J1 - J0; j++) { av[j] = make_uint4(pin(0), pin(0), pin(0), pin(0)); as[j] = pin(0); }
        }
    }
    __device__ __forceinline__ bool complete() {
        bool ok = true;
#pragma unroll
        for (int j = J0; j < J1; j++) {
            ok &= __byte_perm(av[j - J0].w, as[j - J0], 0x7632) == (j == 0 ? 0x42804280u : 0x42004200u);
            av[j - J0].w = __byte_perm(av[j - J0].w, as[j - J0], 0x5410);
        }
        return __all_sync(~0u, ok);
    }
    __device__ __forceinline__ void store(const Params& P, int i, int tid) {
        [[maybe_unused]] int n = 0;
        while (!complete() && i >= 0) { load(i, tid); SPIN_CHECK(n, 2); PROF_INC(n, 1); }
        mbar_wait(bars + EB_EMPTY * 8, (i & 1) ^ 1);
        if (i < 0 || i + 1 == LAG) {
            mbar_wait(bars + EB_WO * 8, 0);
            const uint16_t* m = (const uint16_t*)P.mem0 + (tid & 3) * (2 * DM) + ((tid >> 5) & 3) * 16 + ((tid & 31) >> 2);
#pragma unroll
            for (int j = J0; j < J1; j++) {
                const int f = ar_tile(j) * 64;
                av[j - J0].z = (uint32_t)__ldg(m + f) | ((uint32_t)__ldg(m + f + DM) << 16);
                av[j - J0].w = (uint32_t)__ldg(m + f + 8) | ((uint32_t)__ldg(m + f + DM + 8) << 16);
                if (i < 0) { av[j - J0].x = av[j - J0].z; av[j - J0].y = av[j - J0].w; }
            }
        }
        const uint32_t a = sb + E_MEM + tl_lane(tid, 9216);
#pragma unroll
        for (int j = J0; j < J1; j++) stsm4(a + ar_tile(j) * 1024, av[j - J0].x, av[j - J0].y, av[j - J0].z, av[j - J0].w);
        mbar_arrive_warp(bars + EB_MEM * 8);
    }
};

__device__ __forceinline__ void attn_mem(float* d, uint32_t par, int i, int tid) {
    const int lane = tid & 31, warp = tid >> 5, c = warp >> 1, hf = warp & 1;
    const int rank = cta_rank();
    const uint32_t peer = mapa(sb, rank ^ 1);
    const uint32_t l4 = (lane >> 4) * 1024 + (lane & 15) * 16;
    uint32_t kb[4][4];
    mbar_wait_cl(bars + EB_VX * 8, par);
    if (VM_EARLY) mbar_wait_cl(bars + EB_VM * 8, par);
    nbar_sync(NB_KT, 256);
    {
        const uint32_t aK = sb + E_KT + (c * 6 + hf * 2) * 1024 + l4;
#pragma unroll
        for (int ks = 0; ks < 4; ks++) ldsm4t(kb[ks], aK + ks * 256);
    }
    const uint32_t aQs = pin(sb + E_QM + tl_lane(tid, 1024));
    const uint32_t aQ = pin(sb + E_QM + c * 1024 + (((lane >> 3) & 1) * 16 + (lane >> 4) * 8 + (lane & 7)) * 16);
    const uint32_t aM = pin(sb + E_KT + (4 + c) * 1024 + lane * 16);
    const uint32_t oS = pin(tid * 16);
    const uint32_t aV = pin(sb + (hf == rank ? E_VT + c * 6144 : E_VP + c * 4096) + l4);
    wg_wait_acc<0, 8>(d);
    stsm4(aQs, pack2(d[0], d[1]), pack2(d[2], d[3]), pack2(d[4], d[5]), pack2(d[6], d[7]));
    nbar_sync(NB_QK, 256);
    TS(0, i, 1);
    float s[6];
    {
        uint32_t q[2][4], km[2][4];
        ldsm4t(q[0], aQ); ldsm4t(km[0], aM); ldsm4t(q[1], aQ + 512); ldsm4t(km[1], aM + 512);
        float a[6][4];
#pragma unroll
        for (int m = 0; m < 6; m++) a[m][0] = a[m][1] = a[m][2] = a[m][3] = 0.f;
#pragma unroll
        for (int j = 0; j < 2; j++) {
#pragma unroll
            for (int o = 0; o < 2; o++) {
                mma16816(a[o * 3], q[j], kb[2 * j + o][0], kb[2 * j + o][1]);
                mma16816(a[o * 3 + 1], q[j], kb[2 * j + o][2], kb[2 * j + o][3]);
            }
            mma16816(a[2], q[j], km[j][0], km[j][1]);
            mma16816(a[5], q[j], km[j][2], km[j][3]);
        }
        nbar_arrive(NB_S, 256);
        if (SX_GATE) nbar_arrive(NB_S2, 256);
#pragma unroll
        for (int m = 0; m < 3; m++) { s[2 * m] = a[m][0] + a[3 + m][2]; s[2 * m + 1] = a[m][1] + a[3 + m][3]; }
    }
    st_async128(peer + E_SR + oS, fu(s[0]), fu(s[1]), fu(s[2]), fu(s[3]), peer + SM_BAR + EB_SM * 8);
    const uint32_t oM = E_SR + 2048 + c * 256 + lane * 8;
    asm volatile("st.async.shared::cluster.mbarrier::complete_tx::bytes.b32 [%0], %1, [%2];"
                 :: "r"(peer + oM + hf * 4), "r"(fu(hf ? s[5] : s[4])), "r"(peer + SM_BAR + EB_SM * 8) : "memory");
    sts128(sb + E_SL + oS, fu(s[0]), fu(s[1]), fu(s[2]), fu(s[3]));
    mbar_arrive_warp(bars + EB_KF * 8);
    TS(0, i, 2);
#pragma unroll
    for (int T = 0; T < 4; T++) ldsm4(kb[T], aV + hf * 2048 + T * 256);
    nbar_sync(NB_G, 128);
    const uint32_t aO = sb + E_OM + c * OM_STR + (hf * 64 + lane) * 16;
    const uint32_t aR = sb + E_SR + oS, aR1 = sb + E_SR + (oS ^ 512), aRm = sb + oM, aV1 = aV + (hf ^ 1) * 2048;
    const uint4 l1 = lds128(aR1 + (E_SL - E_SR));
    mbar_wait_cl(bars + EB_SM * 8, par);
    TS(0, i, 3);
    float p[10];
    {
        const uint4 r0 = lds128(aR), r1 = lds128(aR1);
        const uint2 rm = lds64(aRm);
        p[0] = s[0] + uf(r0.x); p[1] = s[1] + uf(r0.y); p[2] = s[2] + uf(r0.z); p[3] = s[3] + uf(r0.w);
        p[4] = uf(l1.x) + uf(r1.x); p[5] = uf(l1.y) + uf(r1.y); p[6] = uf(l1.z) + uf(r1.z); p[7] = uf(l1.w) + uf(r1.w);
        p[8] = s[4] + uf(rm.x); p[9] = s[5] + uf(rm.y);
    }
    float mx = fmaxf(fmaxf(fmaxf(p[0], p[1]), fmaxf(p[2], p[3])), fmaxf(fmaxf(fmaxf(p[4], p[5]), fmaxf(p[6], p[7])), fmaxf(p[8], p[9])));
    mx = fmaxf(mx, __shfl_xor_sync(~0u, mx, 1));
    mx = fmaxf(mx, __shfl_xor_sync(~0u, mx, 2));
    const float mo = mx * (SM_SCALE * LOG2E);
    uint32_t pb[5];
    float o[5][4];
    const uint32_t ones[4] = {0x3f803f80u, 0x3f803f80u, 0x3f803f80u, 0x3f803f80u};
#pragma unroll
    for (int m = 0; m < 2; m++) pb[m] = pack2(ex2(fmaf(p[2 * m], SM_SCALE * LOG2E, -mo)), ex2(fmaf(p[2 * m + 1], SM_SCALE * LOG2E, -mo)));
#pragma unroll
    for (int T = 0; T < 5; T++) o[T][0] = o[T][1] = o[T][2] = o[T][3] = 0.f;
    mma16816(o[4], ones, pb[0], pb[1]);
#pragma unroll
    for (int T = 0; T < 4; T++) { mma16816(o[T], kb[T], pb[0], pb[1]); ldsm4(kb[T], aV1 + T * 256); }
#pragma unroll
    for (int m = 2; m < 5; m++) pb[m] = pack2(ex2(fmaf(p[2 * m], SM_SCALE * LOG2E, -mo)), ex2(fmaf(p[2 * m + 1], SM_SCALE * LOG2E, -mo)));
    if (!VM_EARLY) mbar_wait_cl(bars + EB_VM * 8, par);
    uint2 vm[4];
#pragma unroll
    for (int T = 0; T < 4; T++) vm[T] = lds64(sb + E_VF + hf * 2048 + lane * 16 + c * 8 + T * 512);
    mma16816(o[4], ones, pb[2], pb[3]);
#pragma unroll
    for (int T = 0; T < 4; T++) mma16816(o[T], kb[T], pb[2], pb[3]);
    mma1688(o[4], ones[0], ones[1], pb[4]);
#pragma unroll
    for (int T = 0; T < 4; T++) mma1688(o[T], vm[T].x, vm[T].y, pb[4]);
    nbar_arrive(NB_PV, 256);
    mbar_arrive_warp(bars + EB_CONS * 8);
    const float i0 = rcp(o[4][0]), i1 = rcp(o[4][1]);
#pragma unroll
    for (int j = 0; j < 2; j++)
        stsm4(aO + j * 512, pack2(o[2 * j][0] * i0, o[2 * j][1] * i1), pack2(o[2 * j][2] * i0, o[2 * j][3] * i1),
              pack2(o[2 * j + 1][0] * i0, o[2 * j + 1][1] * i1), pack2(o[2 * j + 1][2] * i0, o[2 * j + 1][3] * i1));
}

__device__ __forceinline__ void attn_x_scores(float (&p)[2][10], uint32_t par, int i, int tid) {
    {
        float s[40];
        const uint64_t da = mkdesc(E_QT, 128, 1024, 0), db = mkdesc(E_KT, 128, 1024, 0);
        wg_fence();
#pragma unroll
        for (int ks = 0; ks < 4; ks++) wg_ss80(s, da + ks * 16, db + ks * 16, ks > 0);
        wg_commit();
        const int dq = (tid >> 2) - 2 * (tid & 3);
        float mask[8];
#pragma unroll
        for (int j = 0; j < 8; j++) mask[j] = (j >> 1) * 8 + (j & 1) > dq ? -1e9f * LOG2E : 0.f;
        mbar_wait_cl(bars + EB_PRDY * 8, par);
        wg_wait_acc<0, 40>(s);
#pragma unroll
        for (int u = 0; u < 5; u++) {
            const int v = u < 4 ? 6 + u : 5;
            constexpr float C = SM_SCALE * LOG2E;
            const float m0 = u < 4 ? mask[2 * u & 7] : 0.f, m1 = u < 4 ? mask[(2 * u + 1) & 7] : 0.f;
            p[0][2 * u] = fmaf(s[4 * u], C, m0); p[0][2 * u + 1] = fmaf(s[4 * u + 1], C, m1); p[1][2 * u] = fmaf(s[4 * v + 2], C, m0); p[1][2 * u + 1] = fmaf(s[4 * v + 3], C, m1);
        }
    }
    mbar_arrive_warp(bars + EB_QF * 8);
    const int w = tid >> 5;
    {
        const uint32_t peer = mapa(sb, cta_rank() ^ 1);
#pragma unroll
        for (int u = 0; u < 5; u++)
            if (u == 0 || u <= w || u == 4) st_async128(peer + E_SX + sx_off(u) + tid * 16, fu(p[0][2 * u]), fu(p[0][2 * u + 1]), fu(p[1][2 * u]), fu(p[1][2 * u + 1]), peer + SM_BAR + EB_SX * 8);
    }
    TS(128, i, 10);
}
__device__ __forceinline__ void attn_x_finish(float (&p)[2][10], uint32_t par, int i, int& tid, uint32_t zero) {
    const int w = tid >> 5;
    mbar_wait_cl(bars + EB_SX * 8, par);
    TS(128, i, 11);
#pragma unroll
    for (int u = 0; u < 5; u++) {
        const uint4 r = lds128(pin(sb + tid * 16 + (u == 0 || u <= w ? sx_off(u) : sx_off(4))) + E_SX);
        p[0][2 * u] += uf(r.x); p[0][2 * u + 1] += uf(r.y); p[1][2 * u] += uf(r.z); p[1][2 * u + 1] += uf(r.w);
    }
    nbar_sync(NB_W, 128);
    uint32_t pa[5][4];
    float mx[2], inv[2];
#pragma unroll
    for (int h = 0; h < 2; h++) {
        const float* q = p[h];
        mx[h] = fmaxf(fmaxf(fmaxf(q[0], q[1]), fmaxf(q[2], q[3])), fmaxf(fmaxf(fmaxf(q[4], q[5]), fmaxf(q[6], q[7])), fmaxf(q[8], q[9])));
    }
#pragma unroll
    for (int o = 1; o < 4; o <<= 1) { mx[0] = fmaxf(mx[0], __shfl_xor_sync(~0u, mx[0], o)); mx[1] = fmaxf(mx[1], __shfl_xor_sync(~0u, mx[1], o)); }
#pragma unroll
    for (int h = 0; h < 2; h++) {
        float* q = p[h];
#pragma unroll
        for (int j = 0; j < 10; j++) q[j] = ex2(q[j] - mx[h]);
#pragma unroll
        for (int u = 0; u < 4; u++) {
            pa[h * 3 + (u >> 1)][(u & 1) * 2 + h] = pack2(q[2 * u], q[2 * u + 1]);
            pa[h * 3 + (u >> 1)][(u & 1) * 2 + (h ^ 1)] = zero << (h * 5 + u + 1);
        }
        pa[2][h * 3] = pack2(q[8], q[9]);
        pa[2][1 + h] = zero << (h * 5 + 5);
    }
    mbar_wait(bars + (PVX_LATE ? EB_CONS : EB_KF) * 8, par);
    fence_async_smem();
    tid = pin(tid << zero);
    const uint32_t aO = pin(sb + (((tid >> 4) & 1) * 8 + (tid & 7)) * 128 + (((((tid >> 3) & 1) * 4 + (tid >> 5)) ^ (tid & 7)) << 4)) + E_R1;
    TS(128, i, 12);
#pragma unroll
    for (int nh = 0; nh < 2; nh++) {
        float o[16], sum[4];
        const uint64_t db = mkdesc(E_VT + nh * 512, 1024, 128, 0);
        wg_fence();
#pragma unroll
        for (int kk = 0; kk < 5; kk++) {
            if (nh == 0) wg_rs8(sum, pa[kk], mkdesc(SM_ONES, 0, 0, 0), kk > 0);
            wg_rs32(o, pa[kk], db + kk * 128, kk > 0);
        }
        wg_commit();
        wg_wait_acc<0, 16>(o);
        if (nh == 0) { acc_ready<4>(sum); inv[0] = rcp(sum[0]); inv[1] = rcp(sum[2]); }
#pragma unroll
        for (int j = 0; j < 2; j++) {
            const float* y = &o[8 * j];
            stsm4t(aO + nh * 4096 + j * 2048, pack2(y[0] * inv[0], y[1] * inv[0]), pack2(y[2] * inv[1], y[3] * inv[1]), pack2(y[4] * inv[0], y[5] * inv[0]), pack2(y[6] * inv[1], y[7] * inv[1]));
        }
    }
    mbar_arrive_warp(bars + EB_OST * 8);
    TS(128, i, 13);
}

template <int MAT>
__device__ __forceinline__ void engine_main(const Params& P) {
    constexpr int NR = MAT == 0 ? NRQ : MAT == 1 ? NRK : NRV;
    constexpr uint64_t M = ss_mask(MAT);
    uint32_t w[NR][4];
    {
        const uint32_t a = sb + E_WO + (MAT == 0 ? 0 : MAT == 1 ? NRQ : NRQ + NRK) * 2048 + unit_frag_addr(fresh_tid());
        mbar_wait(bars + EB_WL * 8, 0);
#pragma unroll
        for (int u = 0; u < NR; u++) ldsm4t(w[u], a + u * 2048);
    }
    cluster_sync_all();
    int tid = fresh_tid() - MAT * 128;
#define TID (tid = pin(tid << P.zero))
#pragma unroll 1
    for (int i = -1; i < NSTEP; i++) {
        const uint32_t par = i & 1;
        if (i >= 0) {
            float d[8];
            mbar_wait(bars + EB_MEM * 8, par);
            fence_async_smem();
            TS(MAT * 128, i, MAT == 2 ? 26 : 14 + MAT);
            if (MAT == 2 && Q_LEAD) nbar_sync(NB_OM, 256);
            wg_fence();
            constexpr int MID = MAT == 0 ? Q_LEAD : MAT == 2 ? V_FIRST : 0;
            proj_mem<MAT, NR, 0, MID>(d, w);
            if (MAT == 0 && Q_LEAD) nbar_arrive(NB_OM, 256);
            if (MAT == 2 && V_FIRST < 36) nbar_sync(NB_S, 256);
            proj_mem<MAT, NR, MID, 36>(d, w);
            wg_commit();
            if (MAT == 0) {
                attn_mem(d, par, i, TID);
            } else if (MAT == 1) {
                const uint32_t a = pin(sb + E_KT + 4096 + tl_lane(TID, 1024));
                wg_wait_acc<0, 8>(d);
                stsm4(a, pack2(d[0], d[1]), pack2(d[2], d[3]), pack2(d[4], d[5]), pack2(d[6], d[7]));
                nbar_arrive(NB_QK, 256);
                TS(128, i, 18);
                nbar_sync(NB_T, 256);
                fence_async_smem();
                if (SX_GATE) nbar_sync(NB_S2, 256);
                float p[2][10];
                attn_x_scores(p, par, i, TID);
                attn_x_finish(p, par, i, TID, pin(P.zero));
            } else {
                const int rank = cta_rank();
                const uint32_t a = pin(sb + E_VT + 4096 + tl_lane(TID, 1024)), of = pin(E_VF + rank * 2048 + (tid & 127) * 16);
                const uint32_t peer = pin(mapa(sb, rank ^ 1));
                wg_wait_acc<0, 8>(d);
                const uint32_t v0 = pack2(d[0], d[1]), v1 = pack2(d[2], d[3]), v2 = pack2(d[4], d[5]), v3 = pack2(d[6], d[7]);
                st_async128(peer + of, v0, v1, v2, v3, peer + SM_BAR + EB_VM * 8);
                sts128(sb + of, v0, v1, v2, v3);
                stsm4(a, v0, v1, v2, v3);
                mbar_arrive_warp(bars + EB_VM * 8);
                mbar_arrive_warp(bars + EB_KF * 8);
                TS(256, i, 16);
                if (i == NSTEP - 1) { if (V_FIRST == 36) nbar_sync(NB_S, 256); nbar_sync(NB_PV, 256); }
            }
            if (MAT == 0) {
                const int rank = cta_rank();
                uint8_t* const ar = g_ar + (i & 3) * AR_SLOT;
                uint8_t* const pm = ar + pin(ar_main(TID) + rank * (64 * AR_STR));
                uint8_t* const ps = ar + pin(ar_side(tid) + rank * (64 * AR_STR));
                const uint32_t o8 = (128 - rank * 64) * AR_STR;
                const uint64_t db = mkdesc(E_OM, 128, OM_STR, 0), da = mkdesc(E_WO, 1024, 1024, 1);
                nbar_sync(NB_G, 128);
                fence_async_smem();
                TS(0, i, 6);
                if (i == NSTEP - 1) break;
                float y[4][8];
                wg_fence();
#pragma unroll
                for (int ks = 0; ks < 8; ks++) {
                    if (ks < 4) wg_ss16(y[3], da + (32 + ks) * 128, db + (rank * 4 + ks) * 16, ks > 0);
                    wg_ss16(y[0], da + ks * 128, db + ks * 16, ks > 0);
                }
                wg_commit();
#pragma unroll
                for (int ks = 0; ks < 8; ks++) wg_ss16(y[2], da + (16 + ks) * 128, db + ks * 16, ks > 0);
                wg_commit();
#pragma unroll
                for (int ks = 0; ks < 8; ks++) wg_ss16(y[1], da + (8 + ks) * 128, db + ks * 16, ks > 0);
                wg_commit();
                wg_wait_acc<2, 8>(y[3]); acc_ready<8>(y[0]);
                ar_red(pm + o8, ps + o8, y[3]);
                mbar_wait(bars + EB_WO * 8, 0);
                wg_fence();
#pragma unroll
                for (int ks = 0; ks < 8; ks++) wg_ss16(y[3], da + (24 + ks) * 128, db + ks * 16, ks > 0);
                wg_commit();
                if (V_EARLY) nbar_arrive(NB_WO, 256);
                ar_red(pm, ps, y[0]);
                wg_wait_acc<2, 8>(y[2]);
                ar_red(pm + 32 * AR_STR, ps + 32 * AR_STR, y[2]);
                wg_wait_acc<1, 8>(y[1]);
                ar_red(pm + 16 * AR_STR, ps + 16 * AR_STR, y[1]);
                wg_wait_acc<0, 8>(y[3]);
                ar_red(pm + 48 * AR_STR, ps + 48 * AR_STR, y[3]);
                if (!V_EARLY) nbar_arrive(NB_WO, 256);
                TS(0, i, 7);
            }
            if (i == NSTEP - 1) break;
        }
        uint32_t t[16];
        ArPart<MAT> ar;
        {
            float d[32];
            const uint64_t da = mkdesc((MAT == 0 ? E_WQ : MAT == 1 ? E_WK : E_WV), 1024, 1024, 1);
#pragma unroll
            for (int n = 0; n < 9; n++) {
                const int blk = x_order(MAT, n), prev = n ? x_order(MAT, n - 1) : -1, f = MAT != 2 && blk < 2 ? 9 + blk : blk;
                if (MAT == 2) {
                    if (n == 2) { wg_wait<0>(); mbar_arrive_warp(bars + EB_V0 * 8); }
                    if (n == 0 || n == 2 || n == 2 + V_BURST2) {
#pragma unroll
                        for (int j = n; j < (n == 0 ? 2 : n < 2 + V_BURST2 ? 2 + V_BURST2 : 8); j++) mbar_wait(bars + (EB_FULL + j) * 8, par ^ 1);
                    }
                    if (i >= 0) {
                        if (n == 0 && V_FIRST == 36) nbar_sync(NB_S, 256);
                        if (n == 2) nbar_sync(NB_PV, 256);
                        if (n == 2 + V_BURST2) nbar_sync(NB_WO, 256);
                    }
                } else {
                    if (n == 0) nbar_sync(MAT ? NB_VL : NB_VL2, 256);
                }
                if (f >= 8) mbar_wait(bars + (EB_FULL + f) * 8, par ^ 1);
                TX(MAT * 128, 1 + MAT * 9 + n);
                wg_fence();
                if (n == 0) TS(MAT * 128, i + 1, 20 + MAT);
                const uint64_t db = mkdesc(x_slot(f), 16, 1024, 1);
#pragma unroll
                for (int j = 0; j < 4; j++) {
                    const int ks = blk * 4 + j, s = popc_below(M, ks);
                    if ((M >> ks) & 1) wg_ss64<0>(d, da + s * 128, db + j * 2, n + j > 0);
                    else wg_rs64<0>(d, w[ks - s], db + j * 2, n + j > 0);
                }
                wg_commit();
                if (MAT == 2 && n + 1 == V_LEAD) { nbar_arrive(NB_VL, 256); if (!K_LEAD) nbar_arrive(NB_VL2, 256); }
                if (MAT == 1 && n + 1 == K_LEAD) nbar_arrive(NB_VL2, 256);
                if (MAT != 2 && n == (MAT ? AR_LDK : AR_LDQ)) { ar.first_load(i, TID); }
                if (MAT != 2 && n == (MAT ? AR_STK : AR_STQ)) ar.store(P, i, TID);
                if (MAT != 2 && x_empty(prev) >= 0) { wg_wait<1>(); mbar_arrive_warp(bars + (EB_EMPTY + x_empty(prev)) * 8); }
            }
            if (MAT != 2) mbar_wait(bars + (EB_EMPTY + 2) * 8, par ^ 1);
            else mbar_wait(bars + EB_OST * 8, par);
            wg_wait_acc<0, 32>(d);
            if (MAT != 2) mbar_arrive_warp(bars + EB_STEP * 8);
            TS(MAT * 128, i + 1, 23 + MAT);
#pragma unroll
            for (int j = 0; j < 16; j++) t[j] = pack2(d[2 * j], d[2 * j + 1]);
        }
        if (MAT == 2) {
            if ((TID & 31) < 4) mbar_arrive(bars + (EB_EMPTY + (tid & 31)) * 8);
        }
        {
            const uint32_t a = sb + (MAT == 0 ? E_QT : MAT == 1 ? E_KT : E_VT) + tl_lane(TID, MAT == 0 ? 2048 : 1024);
#pragma unroll
            for (int j = 0; j < 8; j += 2) {
                const int grp = MAT == 0 ? 2 * (j & 3) + (j >> 2) : j < 4 ? j : j + 2;
                stsm4(a + grp * 1024, t[2 * j], t[2 * j + 1], t[2 * j + 2], t[2 * j + 3]);
            }
        }
        if (MAT == 2) {
            if (AR_VWAIT) mbar_wait(bars + EB_EMPTY * 8, par ^ 1);
            ar.first_load(i, TID);
            ar.store(P, i, tid);
            TS(256, i, 19);
        }
        if (MAT == 0) nbar_arrive(NB_T, 256);
        if (MAT == 1) nbar_arrive(NB_KT, 256);
    }
}

__device__ __forceinline__ void engine_helper(const Params& P) {
    const int lane = threadIdx.x & 31, hw = warp_in_group(), e = blockIdx.x, rank = e & 1;
    if (hw < 3) {
        constexpr uint64_t M0 = ss_mask(0), M1 = ss_mask(1), M2 = ss_mask(2);
        const uint64_t m = hw == 0 ? M0 : hw == 1 ? M1 : M2;
        const uint32_t ws = sb + (hw == 0 ? E_WQ : hw == 1 ? E_WK : E_WV), wr = sb + E_WO + (hw == 0 ? 0 : hw == 1 ? NRQ : NRQ + NRK) * 2048;
        if (lane == 0) mbar_expect(bars + EB_WL * 8, 36 * 2048);
        __syncwarp();
        for (int ks = lane; ks < 36; ks += 32) {
            const int s = __popcll(m & ((1ull << ks) - 1));
            tma_unit(((m >> ks) & 1) ? ws + s * 2048 : wr + (ks - s) * 2048, hw == 0 ? &P.tmWq : hw == 1 ? &P.tmWk : &P.tmWv, ks, e, bars + EB_WL * 8);
        }
    }
    __syncwarp();
    cluster_sync_all();
    if (hw == 0) {
        if (lane == 0) {
            const uint32_t peer = mapa(sb, rank ^ 1);
#pragma unroll 1
            for (int n = 0; n < NSTEP; n++) {
                const uint32_t par = (n & 1) ^ 1;
                uint32_t rdy;
                do { asm volatile("ld.acquire.cta.shared.u32 %0, [%1];" : "=r"(rdy) : "r"(sb + SM_XRDY) : "memory"); } while (rdy <= n && (__nanosleep(20), true));
                fence_async_glb();
                TG(n, 30);
                const uint8_t* s0 = g_x0 + min(n, NSEG - 1) * XIMG;
                const uint8_t* s1 = n >= LAG ? g_x1 + (n - LAG) * XIMG : s0;
#pragma unroll
                for (int j = 0; j < 11; j++) {
                    const int f = j < 9 ? j : 19 - j, blk = f < 9 ? f : f - 9;
                    if (n > 0 && (f == 0 || f == 2 || f == 4 || f == 8 || f == 10))
                        mbar_wait(bars + (f == 0 ? EB_STEP : f == 2 ? EB_KF : f == 4 ? EB_QF : f == 8 ? EB_CONS : EB_OFREE) * 8, par);
                    if (f == 6 || f == 9) mbar_wait(bars + (f == 6 ? EB_V0 : EB_EMPTY + 1) * 8, par ^ 1);
                    const uint32_t fb = bars + (EB_FULL + f) * 8;
                    mbar_expect(fb, 8192);
                    bulk_g2s(sb + x_slot(f), s0 + blk * 4096, 4096, fb);
                    bulk_g2s(sb + x_slot(f) + 4096, s1 + blk * 4096, 4096, fb);
                }
                mbar_wait(bars + (EB_EMPTY + 3) * 8, par ^ 1);
                mbar_arrive_remote(peer + SM_BAR + EB_PRDY * 8);
            }
        }
    } else if (hw == 1) {
        if (lane == 0) {
#pragma unroll 1
            for (int i = 0; i < NSTEP; i++) {
                mbar_wait(bars + EB_OST * 8, i & 1);
                fence_async_smem();
                bulk_s2g(g_o + (i & (RING - 1)) * O_BYTES + e * 8192, sb + E_R1, 8192);
                asm volatile("cp.async.bulk.commit_group;" ::: "memory");
                asm volatile("cp.async.bulk.wait_group.read 0;" ::: "memory");
                mbar_arrive(bars + EB_OFREE * 8);
                asm volatile("cp.async.bulk.wait_group 0;" ::: "memory");
                publish(F_O, i);
                TG(i, 31);
            }
        }
    } else if (hw == 2) {
        const uint32_t peer = mapa(sb, rank ^ 1);
        const int idx = e * 23 + lane, line = idx >> 3;
        uint8_t* z = g_ar + (line < 144 ? line * AR_STR : (line - 144) * (4 * AR_STR) + AR_STR / 2) + (idx & 7) * 16;
        if (lane == 0) mbar_arrive(bars + EB_MEM * 8);
#pragma unroll 1
        for (int i = 0; i < NSTEP; i++) {
            mbar_wait(bars + EB_MEM * 8, i & 1);
            if (lane == 0) {
                mbar_wait_cl(bars + EB_PRDY * 8, i & 1);
                fence_async_smem();
                bulk_s2peer(peer + E_VP, sb + E_VT, 4096, peer + SM_BAR + EB_VX * 8);
                bulk_s2peer(peer + E_VP + 4096, sb + E_VT + 6144, 4096, peer + SM_BAR + EB_VX * 8);
                mbar_expect(bars + EB_VX * 8, 8192);
                mbar_expect(bars + EB_SX * 8, 7168);
                mbar_expect(bars + EB_SM * 8, 2560);
                mbar_expect(bars + EB_VM * 8, 2048);
            }
            __syncwarp();
            if (i >= 2 && lane < 23 && idx < 1440) stg128(z + ((i + 2) & 3) * AR_SLOT, make_uint4(0, 0, 0, 0));
            __syncwarp();
            if (lane == 0) { fence_gpu(); mbar_arrive(bars + EB_MEM * 8); }
            __syncwarp();
        }
        flag_wait(F_O, NSTEP - 1, NENG * this_launch());
        if (lane < 23 && idx < 1440) stg128(z + ((NSTEP - 2) & 3) * AR_SLOT, make_uint4(0, 0, 0, 0));
    } else {
        if (lane == 0) mbar_expect(bars + EB_WO * 8, 36 * 2048);
        __syncwarp();
        for (int u = lane; u < 36; u += 32)
            tma_unit(sb + E_WO + u * 2048, &P.tmWo, (e >> 1) * 8 + (u < 32 ? u & 7 : rank * 4 + (u & 3)), u < 32 ? rank * 4 + (u >> 3) : 8, bars + EB_WO * 8);
        if (lane == 0) {
            const uint32_t ep = this_launch(), t0 = timer_lo();
#pragma unroll 1
            for (int n = 0; n < NSTEP; n++) {
                while ((n < NSEG && !flag_up(F_X0, n, 16 * ep)) || (n >= LAG && !flag_up(F_X1, n - LAG, 16 * ep))) {
                    __nanosleep(20);
                    if (timer_lo() - t0 > TIME_LIMIT) break;
                }
                fence_acq_gpu();
                asm volatile("st.release.cta.shared.u32 [%0], %1;" :: "r"(sb + SM_XRDY), "r"(n + 1) : "memory");
            }
        }
    }
    __syncwarp();
}

__device__ __forceinline__ void f1_fetch(const Params& P, uint32_t dst, int f0, int ks0, int n) {
    const int tid = threadIdx.x & 127, r = tid >> 3, c = tid & 7;
    const bf16* src = ((c & 1) ? P.w3 : P.w1) + (size_t)(ks0 * 16 + r) * FF + f0 + (c >> 1) * 8;
    dst += r * 128 + ((c ^ (r & 7)) << 4);
#pragma unroll 1
    for (int u = 0; u < n; u++)
        asm volatile("cp.async.cg.shared.global [%0], [%1], 16;" :: "r"(dst + u * 2048), "l"(src + (size_t)u * 16 * FF) : "memory");
}
template <bool RF, bool second>
__device__ __forceinline__ void f1_tile(const uint32_t (&w)[NRF][4], uint32_t ws, int b, int fo) {
    const uint32_t par = b & 1;
    float d[32];
    const uint64_t da = mkdesc(ws, 1024, 1024, 1), db = mkdesc(F_X, 16, 1024, 1);
#pragma unroll
    for (int blk = 0; blk < 9; blk++) {
        if (!second || blk == 0) mbar_wait(bars + (FB_FULL + blk) * 8, par);
        wg_fence();
#pragma unroll
        for (int j = 0; j < 4; j++) {
            const int ks = blk * 4 + j;
            if (RF && ks < NRF) wg_rs64<0>(d, w[ks < NRF ? ks : 0], db + blk * 512 + j * 2, ks > 0);
            else wg_ss64<0>(d, da + (RF ? ks - NRF : 36 - NRF + ks) * 128, db + blk * 512 + j * 2, ks > 0);
        }
        wg_commit();
        if (blk > 0 && second) { wg_wait<1>(); mbar_arrive_warp(bars + (FB_EMPTY + blk - 1) * 8); }
    }
    const int tid = fresh_tid(), g = (tid & 31) >> 2;
    uint8_t* dst = g_h + (b & (RING - 1)) * H_BYTES + ((fresh_bid() - NENG) * 128 + fo + ((tid >> 5) & 3) * 8 + g) * 128;
    wg_wait_acc<0, 32>(d);
    if (second) mbar_arrive_warp(bars + (FB_EMPTY + 8) * 8);
    uint32_t h[8];
#pragma unroll
    for (int j = 0; j < 8; j++) {
        const float g0 = d[4 * j], g1 = d[4 * j + 1];
        const float e0 = 1.f + ex2(fminf(-LOG2E * g0, 60.f)), e1 = 1.f + ex2(fminf(-LOG2E * g1, 60.f));
        const float r = rcp(e0 * e1);
        h[j] = pack2(g0 * d[4 * j + 2] * (e1 * r), g1 * d[4 * j + 3] * (e0 * r));
    }
    stg128(dst + (((tid & 3) ^ g) << 4), make_uint4(h[0], h[1], h[2], h[3]));
    stg128(dst + ((((tid & 3) + 4) ^ g) << 4), make_uint4(h[4], h[5], h[6], h[7]));
}
template <int a>
__device__ __forceinline__ void f1_main(const Params& P) {
    constexpr uint32_t ws = F_W + a * (72 - NRF) * 2048;
    const int f0 = (blockIdx.x - NENG) * 128 + a * 64;
    uint32_t w[NRF][4];
    f1_fetch(P, sb + ws, f0, 0, NRF);
    asm volatile("cp.async.wait_all;" ::: "memory");
    nbar_sync(NB_G + a, 128);
    {
        const uint32_t fa = sb + ws + unit_frag_addr(threadIdx.x);
#pragma unroll
        for (int u = 0; u < NRF; u++) ldsm4t(w[u], fa + u * 2048);
    }
    nbar_sync(NB_G + a, 128);
    f1_fetch(P, sb + ws, f0, NRF, 36 - NRF);
    f1_fetch(P, sb + ws + (36 - NRF) * 2048, f0 + 32, 0, 36);
    asm volatile("cp.async.wait_all;" ::: "memory");
    fence_async_smem();
    nbar_sync(NB_G + a, 128);
#pragma unroll 1
    for (int b = 0; b < NSTEP; b++) {
        f1_tile<a == 0, false>(w, ws, b, a * 96);
        f1_tile<a == 1, true>(w, ws, b, 32 + a * 32);
        mbar_wait(bars + FB_RACK * 8, (b & 1) ^ 1);
        mbar_arrive_warp(bars + FB_H * 8);
    }
}
__device__ __forceinline__ uint32_t n_pairs(int b) { return (b < NSEG ? 16 : 0) + (b >= LAG ? 16 : 0); }
__device__ __forceinline__ void publisher(uint32_t done, uint32_t ack, int stage) {
#pragma unroll 1
    for (int b = 0; b < NSTEP; b++) {
        mbar_wait(done, b & 1);
        mbar_arrive(ack);
        TG(b, 30);
        publish(stage, b);
        TG(b, 31);
    }
}
__device__ __forceinline__ void f1_helper() {
    const int hw = warp_in_group();
    if ((threadIdx.x & 31) == 0) {
        if (hw == 0) {
            const uint32_t ep = this_launch();
#pragma unroll 1
            for (int b = 0; b < NSTEP; b++) {
                flag_wait(F_XF, b, n_pairs(b) * ep);
                TG(b, 29);
                const uint8_t* src = g_xf + (b & (RING - 1)) * (9 * 8192);
#pragma unroll 1
                for (int blk = 0; blk < 9; blk++) {
                    mbar_wait(bars + (FB_EMPTY + blk) * 8, (b & 1) ^ 1);
                    mbar_expect(bars + (FB_FULL + blk) * 8, 8192);
                    bulk_g2s(sb + F_X + blk * 8192, src + blk * 8192, 8192, bars + (FB_FULL + blk) * 8);
                }
            }
        } else if (hw == 1) {
            publisher(bars + FB_H * 8, bars + FB_RACK * 8, F_H);
        } else if (hw == 2 && blockIdx.x < NENG + 32) {
            const uint32_t ep = this_launch();
            int b1 = blockIdx.x < NENG + 16 ? 0 : LAG, b2 = b1;
            const int bend = b1 + NSEG;
#pragma unroll 1
            for (int j = 0; j < 2 * NSEG; j++) {
                [[maybe_unused]] int n = 0;
                bool second, any;
                const bool may1 = b1 < bend && b1 < b2 + RING;
                do {
                    const bool r1 = flag_up(F_P1, b1, 15 * ep);
                    second = flag_up(F_P2, b2, 17 * ep);
                    any = (r1 & may1) | second;
                    if (!any) __nanosleep(20);
                    SPIN_CHECK(n, 20);
                } while (!any);
                fence_acq_gpu();
                TG(second ? b2 : b1, 25 + 2 * second);
                if (j) mbar_wait(bars + FB_RDONE * 8, (j & 1) ^ 1);
                sts32(sb + F_RED + 64 + (j & 1) * 4, second ? b2 + 256 : b1);
                mbar_arrive(bars + FB_JOB * 8);
                if (second) b2++; else b1++;
            }
        }
    }
    __syncwarp();
}

__device__ __forceinline__ void add8(float* f, uint4 a) {
    f[0] += bf_lo(a.x); f[1] += bf_hi(a.x); f[2] += bf_lo(a.y); f[3] += bf_hi(a.y);
    f[4] += bf_lo(a.z); f[5] += bf_hi(a.z); f[6] += bf_lo(a.w); f[7] += bf_hi(a.w);
}
__device__ __forceinline__ void set8(float* f, uint4 a) {
    f[0] = bf_lo(a.x); f[1] = bf_hi(a.x); f[2] = bf_lo(a.y); f[3] = bf_hi(a.y);
    f[4] = bf_lo(a.z); f[5] = bf_hi(a.z); f[6] = bf_lo(a.w); f[7] = bf_hi(a.w);
}
__device__ __forceinline__ void ln0_rows(const Params& P, int r) {
    const int lane = threadIdx.x & 31, l = lane < 24 ? lane : 0;
    const uint4* xrow = (const uint4*)(P.x + r * DM) + l;
    uint4 xw[2][3];
#pragma unroll
    for (int k = 0; k < 6; k++) xw[k / 3][k % 3] = __ldg(xrow + (k / 3) * (16 * DM / 8) + 24 * (k % 3));
#pragma unroll 1
    for (int seg = 0; seg < NSEG; seg++) {
#pragma unroll
        for (int h = 0; h < 2; h++) {
            float f[24];
#pragma unroll
            for (int k = 0; k < 3; k++) set8(&f[k * 8], xw[h][k]);
            if (seg + 1 < NSEG) {
#pragma unroll
                for (int k = 0; k < 3; k++) xw[h][k] = __ldg(xrow + (2 * seg + 2 + h) * (16 * DM / 8) + 24 * k);
            }
            float s = 0.f, q = 0.f;
#pragma unroll
            for (int j = 0; j < 24; j++) s += f[j];
            if (lane >= 24) s = 0.f;
#pragma unroll
            for (int o = 16; o; o >>= 1) s += __shfl_xor_sync(~0u, s, o);
            const float mean = s * (1.f / DM);
#pragma unroll
            for (int j = 0; j < 24; j++) { f[j] -= mean; q += f[j] * f[j]; }
            if (lane >= 24) q = 0.f;
#pragma unroll
            for (int o = 16; o; o >>= 1) q += __shfl_xor_sync(~0u, q, o);
            const float rstd = rsqrtf(q * (1.f / DM) + 1e-5f);
            if (lane < 24) {
                uint8_t* d = g_x0 + seg * XIMG + (l >> 3) * 4096 + (r + 16 * h) * 128 + (((l & 7) ^ (r & 7)) << 4);
#pragma unroll
                for (int k = 0; k < 3; k++) {
                    const float* y = &f[8 * k];
                    stg128(d + k * 12288, make_uint4(pack2(y[0] * rstd, y[1] * rstd), pack2(y[2] * rstd, y[3] * rstd), pack2(y[4] * rstd, y[5] * rstd), pack2(y[6] * rstd, y[7] * rstd)));
                }
            }
        }
        __syncwarp();
        if (lane == 0) publish(F_X0, seg);
        __syncwarp();
    }
}

template <bool SECOND, bool CHAIN>
__device__ __forceinline__ void reduce_job(const Params& P, int b) {
    constexpr int NP = SECOND ? NP2 : NP1;
    const int tid = fresh_tid() & 127, lane = tid & 31, p = fresh_bid() - NENG, seg = CHAIN ? b - LAG : b;
    const bool act = lane < 24;
    const int i = (tid >> 5) * 24 + (act ? lane : 0);
    const uint32_t ro = (b & (RING - 1)), po = p * (DM * 4) + i * 32;
    const int fa = (i >> 1) * 16 + (i & 1) * 4;
    const uint32_t row = (seg * 32 + (p & 15) * 2) * DM + fa;
    uint8_t* const r1 = g_r1 + ro * PART + po;
    uint8_t* const r2 = g_r2 + seg * (PART / 2) + po - (CHAIN ? PART / 2 : 0);
    float f[16];
    uint4 x0, x1;
    {
        const uint8_t* src = (SECOND ? g_p2 : g_p1) + ro * (NP * PART) + po;
        uint4 a[NP][2];
#pragma unroll
        for (int k = 0; k < NP; k++) { a[k][0] = ld_rlx128(src + k * PART); a[k][1] = ld_rlx128(src + k * PART + 16); }
        if (SECOND || CHAIN) {
            x0 = ld_rlx128(SECOND ? r1 : r2); x1 = ld_rlx128((SECOND ? r1 : r2) + 16);
        } else {
            const uint2 a0 = ld_rlx64(P.x + row), b0 = ld_rlx64(P.x + row + 8), a1 = ld_rlx64(P.x + row + DM), c1 = ld_rlx64(P.x + row + DM + 8);
            x0 = make_uint4(__byte_perm(a0.x, a1.x, 0x5410), __byte_perm(b0.x, c1.x, 0x5410), __byte_perm(a0.x, a1.x, 0x7632), __byte_perm(b0.x, c1.x, 0x7632));
            x1 = make_uint4(__byte_perm(a0.y, a1.y, 0x5410), __byte_perm(b0.y, c1.y, 0x5410), __byte_perm(a0.y, a1.y, 0x7632), __byte_perm(b0.y, c1.y, 0x7632));
        }
        set8(f, a[0][0]);
#pragma unroll
        for (int k = 1; k < NP; k++) add8(f, a[k][0]);
        set8(f + 8, a[0][1]);
#pragma unroll
        for (int k = 1; k < NP; k++) add8(f + 8, a[k][1]);
    }
    add8(f, x0); add8(f + 8, x1);
    x0 = make_uint4(pack2(f[0], f[1]), pack2(f[2], f[3]), pack2(f[4], f[5]), pack2(f[6], f[7]));
    x1 = make_uint4(pack2(f[8], f[9]), pack2(f[10], f[11]), pack2(f[12], f[13]), pack2(f[14], f[15]));
    if (SECOND && CHAIN) {
        if (act) {
            stg64(P.out + row, __byte_perm(x0.x, x0.z, 0x5410), __byte_perm(x1.x, x1.z, 0x5410));
            stg64(P.out + row + 8, __byte_perm(x0.y, x0.w, 0x5410), __byte_perm(x1.y, x1.w, 0x5410));
            stg64(P.out + row + DM, __byte_perm(x0.x, x0.z, 0x7632), __byte_perm(x1.x, x1.z, 0x7632));
            stg64(P.out + row + DM + 8, __byte_perm(x0.y, x0.w, 0x7632), __byte_perm(x1.y, x1.w, 0x7632));
        }
        return;
    }
    set8(f, x0); set8(f + 8, x1);
    float st[4] = {0.f, 0.f, 0.f, 0.f};
#pragma unroll
    for (int j = 0; j < 16; j++) { st[j & 1] += f[j]; st[2 + (j & 1)] += f[j] * f[j]; }
    {
        const bool u = lane & 1, v = lane & 2;
        st[0] = (u ? st[1] : st[0]) + __shfl_xor_sync(~0u, u ? st[0] : st[1], 1);
        st[2] = (u ? st[3] : st[2]) + __shfl_xor_sync(~0u, u ? st[2] : st[3], 1);
        st[0] = (v ? st[2] : st[0]) + __shfl_xor_sync(~0u, v ? st[0] : st[2], 2);
        st[0] += __shfl_xor_sync(~0u, st[0], 4);
        if (act && !(lane & 4)) sts32(sb + F_RED + 128 + (i >> 3) * 16 + (lane & 3) * 4, fu(st[0]));
    }
    if (act) { stg128(SECOND ? r2 : r1, x0); stg128((SECOND ? r2 : r1) + 16, x1); }
    nbar_sync(NB_R, 96);
#pragma unroll
    for (int k = 0; k < 9; k++) {
        const uint4 t = lds128(sb + F_RED + 128 + k * 16);
        if (k == 0) { st[0] = uf(t.x); st[1] = uf(t.y); st[2] = uf(t.z); st[3] = uf(t.w); }
        else { st[0] += uf(t.x); st[1] += uf(t.y); st[2] += uf(t.z); st[3] += uf(t.w); }
    }
    const float m0 = st[0] * (1.f / DM), m1 = st[1] * (1.f / DM);
    const float q0 = rsqrtf(fmaxf(st[2] * (1.f / DM) - m0 * m0, 0.f) + 1e-5f), q1 = rsqrtf(fmaxf(st[3] * (1.f / DM) - m1 * m1, 0.f) + 1e-5f);
    if (act) {
        uint8_t* d = (SECOND ? g_x1 + seg * XIMG + (fa >> 6) * 4096 : g_xf + ro * (9 * 8192) + (fa >> 6) * 8192) + p * 256 + (i & 1) * 8;
#pragma unroll
        for (int e = 0; e < 2; e++) {
            const float m = e ? m1 : m0, q = e ? q1 : q0;
#pragma unroll
            for (int h = 0; h < 2; h++) {
                const float* y = &f[2 * h + e];
                stg64(d + e * 128 + (((((fa >> 3) & 6) + h) ^ ((2 * p + e) & 7)) << 4), pack2((y[0] - m) * q, (y[4] - m) * q), pack2((y[8] - m) * q, (y[12] - m) * q));
            }
        }
    }
}
__device__ __forceinline__ void reducer(const Params& P) {
    const bool chain = blockIdx.x >= NENG + 16;
    if (warp_in_group() < 3) {
#pragma unroll 1
        for (int j = 0; j < 2 * NSEG; j++) {
            mbar_wait(bars + FB_JOB * 8, j & 1);
            const int job = lds32(sb + F_RED + 64 + (j & 1) * 4);
            if (job >= 256) { if (chain) reduce_job<true, true>(P, job - 256); else reduce_job<true, false>(P, job - 256); }
            else { if (chain) reduce_job<false, true>(P, job); else reduce_job<false, false>(P, job); }
            mbar_arrive_warp(bars + FB_RDONE * 8);
        }
    } else if (threadIdx.x == 352) {
        mbar_arrive(bars + FB_JOB * 8);
#pragma unroll 1
        for (int j = 0; j < 2 * NSEG; j++) {
            mbar_wait(bars + FB_RDONE * 8, j & 1);
            const int job = lds32(sb + F_RED + 64 + (j & 1) * 4);
            mbar_arrive(bars + FB_JOB * 8);
            TG(job & 255, 23 + (job >> 8));
            if (job < 256 || !chain) publish(job < 256 ? F_XF : F_X1, job & 255);
            TG(job & 255, 26 + 2 * (job >> 8));
        }
    }
    __syncwarp();
}

__host__ __device__ constexpr int d_rf(int u) { return u < 48 ? ((u & 3) < 2 ? (u >> 2) * 2 + (u & 1) : -1) : u == 48 ? 24 : -1; }
__host__ __device__ constexpr int d_ss(int u) { return u < 48 ? (u >> 2) * 2 + (u & 1) : u - 25; }
template <bool WIDE, int wg>
__device__ __forceinline__ void d_main() {
    constexpr int NR = WIDE ? 24 : NRD;
    uint32_t w[NR][4];
    {
        const uint32_t fa = sb + wg * (NRD * 2048) + unit_frag_addr(threadIdx.x);
        mbar_wait(bars + DB_WL * 8, 0);
#pragma unroll
        for (int u = 0; u < NR; u++) ldsm4t(w[u], fa + u * 2048);
        nbar_arrive(NB_W, 416);
        mbar_wait(bars + DB_WL * 8, 1);
    }
    const uint64_t da = mkdesc(wg * ((52 - NRD) * 2048), 1024, 1024, 1);
#pragma unroll 1
    for (int b = 0; b < NSTEP; b++) {
#pragma unroll
        for (int T = 0; T < (WIDE ? 3 : 1); T++) {
            float d[32];
            constexpr int NB = WIDE ? 4 : 13;
#pragma unroll
            for (int blk = 0; blk < NB; blk++) {
                const int c = blk;
                if (T == 0 || blk == 0) mbar_wait(bars + (DB_FULL + (c & 7)) * 8, WIDE || (c & 7) >= 5 ? b & 1 : c >> 3);
                wg_fence();
                const uint64_t db = mkdesc(D_B + (c & 7) * 8192, 8192, 1024, 1);
#pragma unroll
                for (int j = 0; j < 4; j++) {
                    const int u = T * 16 + blk * 4 + j;
                    if (d_rf(u) >= 0) wg_rs64<1>(d, w[d_rf(u) >= 0 ? d_rf(u) : 0], db + j * 128, blk + j > 0);
                    else wg_ss64<1>(d, da + d_ss(u) * 128, db + j * 128, blk + j > 0);
                }
                wg_commit();
                if (!WIDE && blk > 0) { wg_wait<1>(); mbar_arrive_warp(bars + (DB_EMPTY + ((c - 1) & 7)) * 8); }
            }
            const int tid = fresh_tid(), t = tid & 3, ds = fresh_bid() - NENG - NF1;
            const bool w2 = ds >= 15;
            const int tile = WIDE ? wg * 3 + T : (ds % 3) * 3 + wg;
            uint8_t* dst = (w2 ? g_p2 + ((b & (RING - 1)) * NP2 + (WIDE ? ds - 25 : (ds - 15) / 3)) * PART : g_p1 + ((b & (RING - 1)) * NP1 + ds / 3) * PART)
                         + (tile * 64 + ((tid >> 5) & 3) * 16 + ((tid & 31) >> 2) * 2) * 4 + (w2 ? 4 * t : t) * (DM * 4);
            const uint32_t js = w2 ? DM * 4 : DM * 16;
            wg_wait_acc<0, 32>(d);
            if (!WIDE) mbar_arrive_warp(bars + (DB_EMPTY + ((NB - 1) & 7)) * 8);
            else if (T == 2) {
#pragma unroll
                for (int blk = 0; blk < 4; blk++) mbar_arrive_warp(bars + (DB_EMPTY + blk) * 8);
            }
#pragma unroll
            for (int j = 0; j < 8; j++) stg64(dst + (j >> 2) * (DM * 64) + (j & 3) * js, pack2(d[4 * j], d[4 * j + 1]), pack2(d[4 * j + 2], d[4 * j + 3]));
        }
        mbar_wait(bars + (DB_P + 1) * 8, (b & 1) ^ 1);
        mbar_arrive_warp(bars + DB_P * 8);
    }
}
__device__ __forceinline__ void d_helper(const Params& P, int ds) {
    const int lane = threadIdx.x & 31, hw = warp_in_group();
    const bool w2 = ds >= 15, wide = ds >= 30;
    const int blk0 = wide ? 65 + (ds - 30) * 4 : ((w2 ? ds - 15 : ds) / 3) * 13, nb = wide ? 4 : 13;
    if (hw == 0) {
        const int nu = wide ? 48 : 52;
#pragma unroll 1
        for (int ph = 0; ph < 2; ph++) {
            if (ph) nbar_sync(NB_W, 416);
            if (lane == 0) mbar_expect(bars + DB_WL * 8, (wide ? 72 : ph ? 3 * (52 - NRD) : 3 * NRD) * 2048);
            __syncwarp();
#pragma unroll 1
            for (int x = lane; x < 3 * nu; x += 32) {
                const int wg = x / nu, u = x - wg * nu;
                if ((d_rf(u) < 0) == (ph != 0))
                    tma_unit(sb + (ph ? wg * (52 - NRD) + d_ss(u) : wg * NRD + d_rf(u)) * 2048, w2 ? &P.tmW2 : &P.tmWo,
                             blk0 * 4 + (wide ? u & 15 : u), wide ? wg * 3 + (u >> 4) : (ds % 3) * 3 + wg, bars + DB_WL * 8);
            }
        }
        __syncwarp();
        if (lane == 0) {
            const uint32_t target = (w2 ? NF1 : NENG) * this_launch();
#pragma unroll 1
            for (int b = 0; b < NSTEP; b++) {
                flag_wait(w2 ? F_H : F_O, b, target);
                TG(b, 29);
                const uint8_t* src = (w2 ? g_h + (b & (RING - 1)) * H_BYTES : g_o + (b & (RING - 1)) * O_BYTES) + blk0 * 8192;
#pragma unroll 1
                for (int blk = 0; blk < nb; blk++) {
                    const int c = blk;
                    mbar_wait(bars + (DB_EMPTY + (c & 7)) * 8, (wide || (c & 7) >= 5 ? b & 1 : c >> 3) ^ 1);
                    mbar_expect(bars + (DB_FULL + (c & 7)) * 8, 8192);
                    bulk_g2s(sb + D_B + (c & 7) * 8192, src + blk * 8192, 8192, bars + (DB_FULL + (c & 7)) * 8);
                }
            }
        }
    } else if (hw == 1 && lane == 0) {
        publisher(bars + DB_P * 8, bars + (DB_P + 1) * 8, w2 ? F_P2 : F_P1);
    }
    __syncwarp();
}

__device__ __forceinline__ void sign_off() { mbar_arrive_warp(sb + SM_DONE); }
__device__ __forceinline__ void sign_off_helper() {
    if (warp_in_group() < 3) { sign_off(); return; }
    uint32_t ok, t0, t1;
    asm volatile("mov.u32 %0, %%globaltimer_lo;" : "=r"(t0));
    while (true) {
        asm volatile("{.reg .pred p; mbarrier.try_wait.parity.shared::cta.b64 p, [%1], 0, 0x100000; selp.u32 %0, 1, 0, p;}" : "=r"(ok) : "r"(sb + SM_DONE) : "memory");
        if (ok) break;
        asm volatile("mov.u32 %0, %%globaltimer_lo;" : "=r"(t1));
        if (t1 - t0 > TIME_LIMIT) __trap();
    }
    if (fresh_tid() == NTHREADS - 32) { g_epoch[fresh_bid()][0] = this_launch(); TG(79, 1); }
    __syncwarp();
}

__global__ void __cluster_dims__(2, 1, 1) __launch_bounds__(NTHREADS, 1) fused_kernel(const __grid_constant__ Params P) {
    const int wg = __shfl_sync(~0u, threadIdx.x >> 7, 0);
    const int bid = blockIdx.x;
    if (threadIdx.x >= NTHREADS - 32) sts32(sb + SM_ONES + (threadIdx.x & 31) * 4, 0x3f803f80u);
    if (threadIdx.x == 0) {
        if ((sb & 0x3ffff) != SM_ORG) __trap();
        TG(79, 0);
        mbar_init(sb + SM_DONE, 15);
        sts32(sb + SM_XRDY, 0);
        if (bid < NENG) {
            for (int i = 0; i < 11; i++) mbar_init(bars + (EB_FULL + i) * 8, 1);
            mbar_init(bars + EB_V0 * 8, 4);
            for (int i = 0; i < 4; i++) mbar_init(bars + (EB_EMPTY + i) * 8, 12);
            mbar_init(bars + EB_WL * 8, 3); mbar_init(bars + EB_WO * 8, 1); mbar_init(bars + EB_STEP * 8, 8);
            mbar_init(bars + EB_VX * 8, 1); mbar_init(bars + EB_SM * 8, 1); mbar_init(bars + EB_SX * 8, 1); mbar_init(bars + EB_VM * 8, 5);
            mbar_init(bars + EB_QF * 8, 4); mbar_init(bars + EB_KF * 8, 8); mbar_init(bars + EB_MEM * 8, 13); mbar_init(bars + EB_PRDY * 8, 1);
            mbar_init(bars + EB_CONS * 8, 4); mbar_init(bars + EB_OST * 8, 4); mbar_init(bars + EB_OFREE * 8, 1);
        } else if (bid < NENG + NF1) {
            for (int i = 0; i < 9; i++) { mbar_init(bars + (FB_FULL + i) * 8, 1); mbar_init(bars + (FB_EMPTY + i) * 8, 8); }
            mbar_init(bars + FB_H * 8, 8); mbar_init(bars + FB_RACK * 8, 1); mbar_init(bars + FB_JOB * 8, 2); mbar_init(bars + FB_RDONE * 8, 3);
        } else {
            for (int i = 0; i < 8; i++) { mbar_init(bars + (DB_FULL + i) * 8, 1); mbar_init(bars + (DB_EMPTY + i) * 8, 12); }
            mbar_init(bars + DB_WL * 8, 1); mbar_init(bars + DB_P * 8, 12); mbar_init(bars + (DB_P + 1) * 8, 1);
        }
        asm volatile("fence.mbarrier_init.release.cluster;" ::: "memory");
    }
    __syncthreads();
    if (bid < NENG) {
        if (wg == 0) { reg_inc<REGQ>(); engine_main<0>(P); sign_off(); cluster_sync_all(); }
        else if (wg == 1) { reg_inc<REGK>(); engine_main<1>(P); sign_off(); cluster_sync_all(); }
        else if (wg == 2) { reg_inc<REGV>(); engine_main<2>(P); sign_off(); cluster_sync_all(); }
        else { reg_dec<24>(); engine_helper(P); sign_off_helper(); cluster_sync_all(); }
    } else if (bid < NENG + NF1) {
        if (wg < 2) {
            reg_inc<200>();
            if (wg == 0) f1_main<0>(P); else f1_main<1>(P);
            sign_off();
        } else if (wg == 2) {
            reg_dec<88>();
            if (bid >= NENG + 32) ln0_rows(P, (bid - NENG - 32) * 4 + ((threadIdx.x >> 5) & 3));
            else reducer(P);
            sign_off();
        } else {
            reg_dec<24>();
            f1_helper();
            sign_off_helper();
        }
    } else {
        const int ds = bid - NENG - NF1;
        if (wg < 3) {
            reg_inc<160>();
            if (ds < 30) { if (wg == 0) d_main<false, 0>(); else if (wg == 1) d_main<false, 1>(); else d_main<false, 2>(); }
            else { if (wg == 0) d_main<true, 0>(); else if (wg == 1) d_main<true, 1>(); else d_main<true, 2>(); }
            sign_off();
        } else {
            reg_dec<32>();
            d_helper(P, ds);
            sign_off_helper();
        }
    }
}

typedef CUresult (*EncodeFn)(CUtensorMap*, CUtensorMapDataType, cuuint32_t, void*, const cuuint64_t*, const cuuint64_t*,
                             const cuuint32_t*, const cuuint32_t*, CUtensorMapInterleave, CUtensorMapSwizzle,
                             CUtensorMapL2promotion, CUtensorMapFloatOOBfill);

void make_map(EncodeFn enc, CUtensorMap* m, const void* p, int rows, int cols) {
    cuuint64_t dims[2] = {(cuuint64_t)cols, (cuuint64_t)rows};
    cuuint64_t strides[1] = {(cuuint64_t)cols * 2};
    cuuint32_t box[2] = {64, 16};
    cuuint32_t es[2] = {1, 1};
    enc(m, CU_TENSOR_MAP_DATA_TYPE_BFLOAT16, 2, (void*)p, dims, strides, box, es, CU_TENSOR_MAP_INTERLEAVE_NONE,
        CU_TENSOR_MAP_SWIZZLE_128B, CU_TENSOR_MAP_L2_PROMOTION_L2_128B, CU_TENSOR_MAP_FLOAT_OOB_FILL_NONE);
}

}

extern "C" void kernel_launch(void* const* d_in, const int* in_sizes, int n_in, void* d_out, int out_size) {
    (void)in_sizes; (void)n_in; (void)out_size;
    static EncodeFn enc = nullptr;
    if (!enc) {
        void* fn = nullptr;
        cudaDriverEntryPointQueryResult qr;
        cudaGetDriverEntryPoint("cuTensorMapEncodeTiled", &fn, cudaEnableDefault, &qr);
        enc = (EncodeFn)fn;
        cudaFuncSetAttribute(fused_kernel, cudaFuncAttributeMaxDynamicSharedMemorySize, SM_TOTAL);
    }
    Params P;
    make_map(enc, &P.tmWq, d_in[2], DM, 4096);
    make_map(enc, &P.tmWk, d_in[3], DM, 4096);
    make_map(enc, &P.tmWv, d_in[4], DM, 4096);
    make_map(enc, &P.tmWo, d_in[5], 4096, DM);
    make_map(enc, &P.tmW2, d_in[10], FF, DM);
    P.x = (const bf16*)d_in[0];
    P.mem0 = (const bf16*)d_in[1];
    P.w1 = (const bf16*)d_in[8];
    P.w3 = (const bf16*)d_in[9];
    P.out = (bf16*)d_out;
    P.zero = 0;
    fused_kernel<<<NCTA, NTHREADS, SM_TOTAL>>>(P);
}
```

```cpp
#include <cuda_runtime.h>
#include <cuda_bf16.h>
#include <cuda.h>
#include <stdint.h>

typedef __nv_bfloat16 bf16;

namespace {

constexpr int DM = 576, FF = 4608, NSEG = 64;
constexpr int NENG = 64, NF1 = 36, ND = 32, NCTA = NENG + NF1 + ND;
constexpr int NTHREADS = 512;
#define LAG 7
#define RING 8
static_assert(RING > LAG, "ring too short");
constexpr int NSTEP = NSEG + LAG;

enum { F_X0 = 0, F_X1, F_O, F_P1, F_XF, F_H, F_P2, F_COUNT };
__device__ uint32_t g_flag[F_COUNT][96][8];
__device__ uint32_t g_epoch[NCTA][8];
constexpr int XIMG = 9 * 4096;
constexpr int O_BYTES = 65 * 8192;
constexpr int H_BYTES = 73 * 8192;
constexpr int PART = 32 * DM * 4;
constexpr int NP1 = 5, NP2 = 7;
__device__ __align__(1024) uint8_t g_x0[NSEG * XIMG];
__device__ __align__(1024) uint8_t g_x1[NSEG * XIMG];
__device__ __align__(1024) uint8_t g_xf[RING * 9 * 8192];
__device__ __align__(1024) uint8_t g_o[RING * O_BYTES];
__device__ __align__(1024) uint8_t g_h[RING * H_BYTES];
__device__ __align__(1024) uint8_t g_p1[RING * NP1 * PART];
__device__ __align__(1024) uint8_t g_p2[RING * NP2 * PART];
__device__ __align__(1024) uint8_t g_r1[RING * PART];
__device__ __align__(1024) uint8_t g_r2[NSEG * PART / 2];
#define AR_STR 4352
constexpr int AR_SLOT = 144 * AR_STR;
__device__ __align__(1024) uint8_t g_ar[4 * AR_SLOT];

struct Params {
    CUtensorMap tmWq, tmWk, tmWv, tmWo, tmW2;
    const bf16 *x, *mem0, *w1, *w3;
    bf16* out;
    uint32_t zero;
};

constexpr uint32_t SM_ORG = 1024;
extern __shared__ __align__(1024) uint8_t smem_raw[];
#define sb ((uint32_t)__cvta_generic_to_shared(smem_raw))
#define bars (sb + SM_BAR)
constexpr int SM_BAR = 231936;
constexpr int SM_TOTAL = SM_BAR + 512;
#define NRQ 25
#define NRK 25
#define NRV 25
#define REGQ 160
#define REGK 168
#define REGV 160
constexpr int E_WQ = 0;
constexpr int E_WK = E_WQ + (36 - NRQ) * 2048;
constexpr int E_WV = E_WK + (36 - NRK) * 2048;
constexpr int E_WO = E_WV + (36 - NRV) * 2048;
constexpr int E_MEM = E_WO + 36 * 2048;
constexpr int E_R0 = E_MEM + 18432;
constexpr int E_R1 = E_R0 + 8192, E_R2 = E_R1 + 8192;
constexpr int E_SX = E_R1;
constexpr int E_QT = E_R2 + 8192;
constexpr int E_KT = E_QT + 8192;
constexpr int E_VT = E_KT + 10240;
constexpr int E_VP = E_VT + 10240;
constexpr int E_VF = E_VP + 8192;
constexpr int E_QM = E_VF + 4096;
constexpr int E_SR = E_QM + 2048;
constexpr int E_SL = E_SR + 2560;
constexpr int E_END = E_SL + 2048;
constexpr int E_OM = E_MEM + 16384, OM_STR = E_QM - E_OM;
static_assert(E_END <= SM_BAR, "engine smem overflow");
static_assert(E_WO + (NRQ + NRK + NRV) * 2048 <= SM_BAR, "weight staging overflow");
enum {
    EB_FULL = 0, EB_EMPTY = 11  , EB_PRDY2 = 14, EB_V0, EB_WL, EB_WO, EB_STEP, EB_VX, EB_SM, EB_SX, EB_VM, EB_QF, EB_KF, EB_CONS, EB_OST, EB_OFREE,
    EB_MEM, EB_PRDY, EB_MEM0
};
enum { NB_G = 1, NB_LEAD, NB_QK, NB_S, NB_OM, NB_W, NB_R, NB_T, NB_PV, NB_WO, NB_V, NB_KT, NB_S2, NB_VL };
constexpr int NB_VL2 = NB_LEAD;
constexpr int NRF = 35;
constexpr int F_W = 0;
constexpr int F_X = 2 * (72 - NRF) * 2048;
constexpr int F_RED = F_X + 9 * 8192;
static_assert(F_RED + 512 <= SM_BAR, "F1 smem overflow");
enum { FB_FULL = 0, FB_EMPTY = 9, FB_H = 18, FB_RACK, FB_JOB, FB_RDONE };
constexpr int NRD = 25;
constexpr int D_B = 3 * (52 - NRD) * 2048;
static_assert(D_B + 8 * 8192 <= SM_BAR, "D smem overflow");
enum { DB_FULL = 0, DB_EMPTY = 8, DB_WL = 16, DB_P };
constexpr int SM_DONE = SM_BAR + 248, SM_XRDY = SM_BAR + 376, SM_ONES = SM_BAR + 384;
constexpr uint32_t TIME_LIMIT = 2000000000u;

#define SPIN_CHECK(n, code)

#define TS(thr, step, k)
#define TX(thr, k)
#define TG(step, k)
#define PROF_INC(n, k)

__device__ __forceinline__ uint32_t mapa(uint32_t a, uint32_t r) {
    uint32_t o; asm("mapa.shared::cluster.u32 %0, %1, %2;" : "=r"(o) : "r"(a), "r"(r)); return o;
}
__device__ __forceinline__ void mbar_init(uint32_t b, uint32_t cnt) {
    asm volatile("mbarrier.init.shared::cta.b64 [%0], %1;" :: "r"(b), "r"(cnt) : "memory");
}
__device__ __forceinline__ void mbar_arrive(uint32_t b) {
    asm volatile("mbarrier.arrive.shared::cta.b64 _, [%0];" :: "r"(b) : "memory");
}
__device__ __forceinline__ void mbar_arrive_warp(uint32_t b) {
    asm volatile("{.reg .pred p; bar.warp.sync -1; elect.sync _|p, -1; @p mbarrier.arrive.shared::cta.b64 _, [%0];}" :: "r"(b) : "memory");
}
__device__ __forceinline__ void mbar_arrive_remote(uint32_t b) {
    asm volatile("fence.release.sync_restrict::shared::cta.cluster; mbarrier.arrive.relaxed.cluster.shared::cluster.b64 _, [%0];" :: "r"(b) : "memory");
}
__device__ __forceinline__ void mbar_expect(uint32_t b, uint32_t bytes) {
    asm volatile("mbarrier.arrive.expect_tx.shared::cta.b64 _, [%0], %1;" :: "r"(b), "r"(bytes) : "memory");
}
__device__ __forceinline__ uint32_t mbar_wait(uint32_t b, uint32_t par) {
    uint32_t ok; [[maybe_unused]] int n = 0;
    while (true) {
        asm volatile("{.reg .pred p; mbarrier.try_wait.parity.shared::cta.b64 p, [%1], %2; selp.u32 %0, 1, 0, p;}"
                     : "=r"(ok) : "r"(b), "r"(par) : "memory");
        if (ok) break;
        SPIN_CHECK(n, 1000 + ((b & 511) >> 3));
    }
    return ok;
}
__device__ __forceinline__ void mbar_wait_cl(uint32_t b, uint32_t par) {
    uint32_t ok; [[maybe_unused]] int n = 0;
    while (true) {
        asm volatile("{.reg .pred p; mbarrier.try_wait.parity.relaxed.cluster.shared::cta.b64 p, [%1], %2; selp.u32 %0, 1, 0, p;}"
                     : "=r"(ok) : "r"(b), "r"(par) : "memory");
        if (ok) break;
        SPIN_CHECK(n, 1000 + ((b & 511) >> 3));
    }
    asm volatile("fence.acquire.sync_restrict::shared::cluster.cluster;" ::: "memory");
}
__device__ __forceinline__ void nbar_sync(int id, int n) { asm volatile("bar.sync %0, %1;" :: "r"(id), "r"(n) : "memory"); }
__device__ __forceinline__ void nbar_arrive(int id, int n) { asm volatile("bar.arrive %0, %1;" :: "r"(id), "r"(n) : "memory"); }
__device__ __forceinline__ void cluster_sync_all() {
    asm volatile("barrier.cluster.arrive.release.aligned; barrier.cluster.wait.acquire.aligned;" ::: "memory");
}
__device__ __forceinline__ void fence_async_smem() { asm volatile("fence.proxy.async.shared::cta;" ::: "memory"); }
__device__ __forceinline__ void fence_async_glb() { asm volatile("fence.proxy.async.global;" ::: "memory"); }
__device__ __forceinline__ void fence_rel_gpu() { asm volatile("fence.release.gpu;" ::: "memory"); }
__device__ __forceinline__ void fence_acq_gpu() { asm volatile("fence.acquire.gpu;" ::: "memory"); }
__device__ __forceinline__ void fence_gpu() { asm volatile("fence.acq_rel.gpu;" ::: "memory"); }
__device__ __forceinline__ int fresh_tid() { int t; asm volatile("mov.u32 %0, %%tid.x;" : "=r"(t)); return t; }
__device__ __forceinline__ int fresh_bid() { int t; asm volatile("mov.u32 %0, %%ctaid.x;" : "=r"(t)); return t; }
__device__ __forceinline__ uint32_t pin(uint32_t v) { asm volatile("" : "+r"(v)); return v; }
__device__ __forceinline__ int warp_in_group() { return __shfl_sync(~0u, (fresh_tid() >> 5) & 3, 0); }
__device__ __forceinline__ int cta_rank() { int t; asm volatile("mov.u32 %0, %%cluster_ctarank;" : "=r"(t)); return t; }
__device__ __forceinline__ uint32_t timer_lo() { uint32_t t; asm volatile("mov.u32 %0, %%globaltimer_lo;" : "=r"(t)); return t; }
__device__ __forceinline__ uint32_t keep(uint32_t v) { return __shfl_xor_sync(~0u, v, 0); }
__device__ __forceinline__ void red_add_u32(uint32_t* p, uint32_t v) {
    asm volatile("red.relaxed.gpu.global.add.u32 [%0], %1;" :: "l"(p), "r"(v) : "memory");
}
__device__ __forceinline__ uint32_t ld_rlx(const void* p) {
    uint32_t v; asm volatile("ld.relaxed.gpu.global.u32 %0, [%1];" : "=r"(v) : "l"(p) : "memory"); return v;
}
__device__ __forceinline__ uint2 ld_rlx64(const void* p) {
    uint2 v; asm volatile("ld.relaxed.gpu.global.v2.u32 {%0,%1}, [%2];" : "=r"(v.x), "=r"(v.y) : "l"(p) : "memory"); return v;
}
__device__ __forceinline__ uint4 ld_rlx128(const void* p) {
    uint4 v;
    asm volatile("ld.relaxed.gpu.global.v4.u32 {%0,%1,%2,%3}, [%4];" : "=r"(v.x), "=r"(v.y), "=r"(v.z), "=r"(v.w) : "l"(p) : "memory");
    return v;
}
__device__ __forceinline__ void stg128(void* p, uint4 v) {
    asm volatile("st.global.v4.b32 [%0], {%1,%2,%3,%4};" :: "l"(p), "r"(v.x), "r"(v.y), "r"(v.z), "r"(v.w) : "memory");
}
__device__ __forceinline__ void stg64(void* p, uint32_t a, uint32_t b) {
    asm volatile("st.global.v2.b32 [%0], {%1,%2};" :: "l"(p), "r"(a), "r"(b) : "memory");
}
__device__ __forceinline__ void st_async128(uint32_t a, uint32_t x, uint32_t y, uint32_t z, uint32_t w, uint32_t mb) {
    asm volatile("st.async.shared::cluster.mbarrier::complete_tx::bytes.v4.b32 [%0], {%1,%2,%3,%4}, [%5];"
                 :: "r"(a), "r"(x), "r"(y), "r"(z), "r"(w), "r"(mb) : "memory");
}
__device__ __forceinline__ void st_async64(uint32_t a, uint32_t x, uint32_t y, uint32_t mb) {
    asm volatile("st.async.shared::cluster.mbarrier::complete_tx::bytes.v2.b32 [%0], {%1,%2}, [%3];"
                 :: "r"(a), "r"(x), "r"(y), "r"(mb) : "memory");
}
__device__ __forceinline__ void sts128(uint32_t a, uint32_t x, uint32_t y, uint32_t z, uint32_t w) {
    asm volatile("st.shared.v4.b32 [%0], {%1,%2,%3,%4};" :: "r"(a), "r"(x), "r"(y), "r"(z), "r"(w) : "memory");
}
__device__ __forceinline__ void sts32(uint32_t a, uint32_t v) { asm volatile("st.shared.b32 [%0], %1;" :: "r"(a), "r"(v) : "memory"); }
__device__ __forceinline__ uint4 lds128(uint32_t a) {
    uint4 v; asm volatile("ld.shared.v4.b32 {%0,%1,%2,%3}, [%4];" : "=r"(v.x), "=r"(v.y), "=r"(v.z), "=r"(v.w) : "r"(a) : "memory"); return v;
}
__device__ __forceinline__ uint2 lds64(uint32_t a) {
    uint2 v; asm volatile("ld.shared.v2.b32 {%0,%1}, [%2];" : "=r"(v.x), "=r"(v.y) : "r"(a) : "memory"); return v;
}
__device__ __forceinline__ uint32_t lds32(uint32_t a) {
    uint32_t v; asm volatile("ld.shared.b32 %0, [%1];" : "=r"(v) : "r"(a) : "memory"); return v;
}
__device__ __forceinline__ void bulk_g2s(uint32_t dst, const void* src, uint32_t bytes, uint32_t mb) {
    asm volatile("cp.async.bulk.shared::cluster.global.mbarrier::complete_tx::bytes [%0], [%1], %2, [%3];"
                 :: "r"(dst), "l"(src), "r"(bytes), "r"(mb) : "memory");
}
__device__ __forceinline__ void bulk_s2g(void* dst, uint32_t src, uint32_t bytes) {
    asm volatile("cp.async.bulk.global.shared::cta.bulk_group [%0], [%1], %2;" :: "l"(dst), "r"(src), "r"(bytes) : "memory");
}
__device__ __forceinline__ void bulk_s2peer(uint32_t dst, uint32_t src, uint32_t bytes, uint32_t mb) {
    asm volatile("cp.async.bulk.shared::cluster.shared::cta.mbarrier::complete_tx::bytes [%0], [%1], %2, [%3];"
                 :: "r"(dst), "r"(src), "r"(bytes), "r"(mb) : "memory");
}
__device__ __forceinline__ void tma_unit(uint32_t dst, const CUtensorMap* tm, int kstep, int mgroup, uint32_t mb) {
    asm volatile("cp.async.bulk.tensor.2d.shared::cluster.global.mbarrier::complete_tx::bytes [%0], [%1, {%2,%3}], [%4];"
                 :: "r"(dst), "l"(tm), "r"(mgroup * 64), "r"(kstep * 16), "r"(mb) : "memory");
}
__device__ __forceinline__ void ldsm4(uint32_t* r, uint32_t a) {
    asm volatile("ldmatrix.sync.aligned.m8n8.x4.shared.b16 {%0,%1,%2,%3}, [%4];"
                 : "=r"(r[0]), "=r"(r[1]), "=r"(r[2]), "=r"(r[3]) : "r"(a) : "memory");
}
__device__ __forceinline__ void ldsm4t(uint32_t* r, uint32_t a) {
    asm volatile("ldmatrix.sync.aligned.m8n8.x4.trans.shared.b16 {%0,%1,%2,%3}, [%4];"
                 : "=r"(r[0]), "=r"(r[1]), "=r"(r[2]), "=r"(r[3]) : "r"(a) : "memory");
}
__device__ __forceinline__ void stsm4(uint32_t a, uint32_t r0, uint32_t r1, uint32_t r2, uint32_t r3) {
    asm volatile("stmatrix.sync.aligned.m8n8.x4.shared.b16 [%0], {%1,%2,%3,%4};" :: "r"(a), "r"(r0), "r"(r1), "r"(r2), "r"(r3) : "memory");
}
__device__ __forceinline__ void stsm4t(uint32_t a, uint32_t r0, uint32_t r1, uint32_t r2, uint32_t r3) {
    asm volatile("stmatrix.sync.aligned.m8n8.x4.trans.shared.b16 [%0], {%1,%2,%3,%4};" :: "r"(a), "r"(r0), "r"(r1), "r"(r2), "r"(r3) : "memory");
}
__device__ __forceinline__ uint32_t pack2(float lo, float hi) {
    uint32_t d; asm("cvt.rn.bf16x2.f32 %0, %1, %2;" : "=r"(d) : "f"(hi), "f"(lo)); return d;
}
__device__ __forceinline__ float bf_lo(uint32_t w) { return __uint_as_float(w << 16); }
__device__ __forceinline__ float bf_hi(uint32_t w) { return __uint_as_float(w & 0xffff0000u); }
__device__ __forceinline__ float ex2(float x) { float y; asm("ex2.approx.ftz.f32 %0, %1;" : "=f"(y) : "f"(x)); return y; }
__device__ __forceinline__ float rcp(float x) { float y; asm("rcp.approx.ftz.f32 %0, %1;" : "=f"(y) : "f"(x)); return y; }
__device__ __forceinline__ uint32_t fu(float x) { return __float_as_uint(x); }
__device__ __forceinline__ float uf(uint32_t x) { return __uint_as_float(x); }
__device__ __forceinline__ void mma16816(float* d, const uint32_t* a, uint32_t b0, uint32_t b1) {
    asm volatile("mma.sync.aligned.m16n8k16.row.col.f32.bf16.bf16.f32 {%0,%1,%2,%3}, {%4,%5,%6,%7}, {%8,%9}, {%0,%1,%2,%3};"
                 : "+f"(d[0]), "+f"(d[1]), "+f"(d[2]), "+f"(d[3]) : "r"(a[0]), "r"(a[1]), "r"(a[2]), "r"(a[3]), "r"(b0), "r"(b1));
}
__device__ __forceinline__ void mma1688(float* d, uint32_t a0, uint32_t a1, uint32_t b0) {
    asm volatile("mma.sync.aligned.m16n8k8.row.col.f32.bf16.bf16.f32 {%0,%1,%2,%3}, {%4,%5}, {%6}, {%0,%1,%2,%3};"
                 : "+f"(d[0]), "+f"(d[1]), "+f"(d[2]), "+f"(d[3]) : "r"(a0), "r"(a1), "r"(b0));
}
template <int N> __device__ __forceinline__ void reg_inc() { asm volatile("setmaxnreg.inc.sync.aligned.u32 %0;" :: "n"(N)); }
template <int N> __device__ __forceinline__ void reg_dec() { asm volatile("setmaxnreg.dec.sync.aligned.u32 %0;" :: "n"(N)); }

__device__ __forceinline__ uint64_t mkdesc(uint32_t addr, uint32_t lbo, uint32_t sbo, uint32_t swz) {
    return (uint64_t)((addr + SM_ORG) >> 4) | ((uint64_t)(lbo >> 4) << 16) | ((uint64_t)(sbo >> 4) << 32) | ((uint64_t)swz << 62);
}
__device__ __forceinline__ void wg_fence() { asm volatile("wgmma.fence.sync.aligned;" ::: "memory"); }
__device__ __forceinline__ void wg_commit() { asm volatile("wgmma.commit_group.sync.aligned;" ::: "memory"); }
template <int N> __device__ __forceinline__ void wg_wait() { asm volatile("wgmma.wait_group.sync.aligned %0;" :: "n"(N) : "memory"); }
template <int M> __device__ __forceinline__ void acc_ready(float* d) {
#pragma unroll
    for (int j = 0; j < M; j++) asm volatile("" : "+f"(d[j]) :: "memory");
}
template <int N, int M> __device__ __forceinline__ void wg_wait_acc(float* d) { wg_wait<N>(); acc_ready<M>(d); }

#define F8(c, d, o) c(d[o]), c(d[o + 1]), c(d[o + 2]), c(d[o + 3]), c(d[o + 4]), c(d[o + 5]), c(d[o + 6]), c(d[o + 7])
#define R8L "%0,%1,%2,%3,%4,%5,%6,%7"
#define R16L R8L ",%8,%9,%10,%11,%12,%13,%14,%15"
#define R32L R16L ",%16,%17,%18,%19,%20,%21,%22,%23,%24,%25,%26,%27,%28,%29,%30,%31"
#define R40L R32L ",%32,%33,%34,%35,%36,%37,%38,%39"
#define WG_BOTH(TXT_PRE, TXT_POST, OUTS, ...)                                                   \
    if (acc) asm volatile(TXT_PRE "1" TXT_POST : OUTS("+f") : __VA_ARGS__);                     \
    else asm volatile(TXT_PRE "0" TXT_POST : OUTS("=f") : __VA_ARGS__)
#define O8(c) F8(c, d, 0)
#define O16(c) F8(c, d, 0), F8(c, d, 8)
#define O32(c) O16(c), F8(c, d, 16), F8(c, d, 24)
#define O40(c) O32(c), F8(c, d, 32)
#define WGM(n) "wgmma.mma_async.sync.aligned.m64n" #n "k16.f32.bf16.bf16 "
__device__ __forceinline__ void wg_rs16(float* d, const uint32_t* a, uint64_t db, bool acc) {
    WG_BOTH(WGM(16) "{" R8L "}, {%8,%9,%10,%11}, %12, ", ", 1, 1, 1;", O8, "r"(a[0]), "r"(a[1]), "r"(a[2]), "r"(a[3]), "l"(db));
}
__device__ __forceinline__ void wg_ss16(float* d, uint64_t da, uint64_t db, bool acc) {
    WG_BOTH(WGM(16) "{" R8L "}, %8, %9, ", ", 1, 1, 1, 1;", O8, "l"(da), "l"(db));
}
__device__ __forceinline__ void wg_rs8(float* d, const uint32_t* a, uint64_t db, bool acc) {
#define O4(c) c(d[0]), c(d[1]), c(d[2]), c(d[3])
    WG_BOTH(WGM(8) "{%0,%1,%2,%3}, {%4,%5,%6,%7}, %8, ", ", 1, 1, 0;", O4, "r"(a[0]), "r"(a[1]), "r"(a[2]), "r"(a[3]), "l"(db));
}
__device__ __forceinline__ void wg_rs32(float* d, const uint32_t* a, uint64_t db, bool acc) {
    WG_BOTH(WGM(32) "{" R16L "}, {%16,%17,%18,%19}, %20, ", ", 1, 1, 0;", O16, "r"(a[0]), "r"(a[1]), "r"(a[2]), "r"(a[3]), "l"(db));
}
template <int TB> __device__ __forceinline__ void wg_rs64(float* d, const uint32_t* a, uint64_t db, bool acc) {
    WG_BOTH(WGM(64) "{" R32L "}, {%32,%33,%34,%35}, %36, ", ", 1, 1, %37;", O32, "r"(a[0]), "r"(a[1]), "r"(a[2]), "r"(a[3]), "l"(db), "n"(TB));
}
template <int TB> __device__ __forceinline__ void wg_ss64(float* d, uint64_t da, uint64_t db, bool acc) {
    WG_BOTH(WGM(64) "{" R32L "}, %32, %33, ", ", 1, 1, 1, %34;", O32, "l"(da), "l"(db), "n"(TB));
}
__device__ __forceinline__ void wg_ss80(float* d, uint64_t da, uint64_t db, bool acc) {
    WG_BOTH(WGM(80) "{" R40L "}, %40, %41, ", ", 1, 1, 1, 1;", O40, "l"(da), "l"(db));
}

constexpr float SM_SCALE = 0.08838834764831845f;
constexpr float LOG2E = 1.4426950408889634f;

__device__ __forceinline__ uint32_t* flag_ptr(int stage, int b) { return &g_flag[stage][b][0]; }
__device__ __forceinline__ uint32_t this_launch() { return ld_rlx(&g_epoch[fresh_bid()][0]) + 1; }
__device__ __forceinline__ bool flag_up(int stage, int b, uint32_t target) { return (int)(ld_rlx(flag_ptr(stage, b)) - target) >= 0; }
__device__ __forceinline__ void flag_wait(int stage, int b, uint32_t target) {
    [[maybe_unused]] int n = 0;
    while (!flag_up(stage, b, target)) {
        __nanosleep(20);
        SPIN_CHECK(n, 10 + stage);
    }
    fence_acq_gpu();
    fence_async_glb();
}
__device__ __forceinline__ void publish(int stage, int b) {
    fence_async_glb();
    fence_rel_gpu();
    red_add_u32(flag_ptr(stage, b), 1);
}
__device__ __forceinline__ uint32_t unit_frag_addr(int tid) {
    const int lane = tid & 31, w = (tid >> 5) & 3, i = lane & 7, j = lane >> 3;
    return ((j >> 1) * 8 + i) * 128 + ((((w << 1) + (j & 1)) ^ i) << 4);
}

#define V_BURST1 2
#define V_BURST2 1
#define V_PRE 8
#define SX_BF16 0
#define WO_MODE 0
#define V_LEAD 9
static_assert(V_BURST1 + V_BURST2 >= 2 && V_LEAD > V_BURST1 + V_BURST2, "q and k rely on v for the arrival of the blocks");
#define K_LEAD 0
#define Q_LEAD 36
#define V_FIRST 12
#define SX_GATE 1
#define PVX_LATE 1
#define V_EARLY 0
#define VM_EARLY 0
__host__ __device__ constexpr int x_order(int mat, int j) {
    return mat == 2 ? j : j < 2 ? j + 2 : j == 2 ? 8 : j == 3 ? 6 : j < 6 ? j : j == 6 ? 7 : 8 - j;
}
#define SS0Q 0
#define SS0K 0
#define SS0V 22
#define SSLQ 36
#define SSLK 36
#define SSLV 14
__host__ __device__ constexpr uint64_t ss_mask(int mat) {
    const int ns = 36 - (mat == 0 ? NRQ : mat == 1 ? NRK : NRV);
    const int j0 = mat == 0 ? SS0Q : mat == 1 ? SS0K : SS0V, len = mat == 0 ? SSLQ : mat == 1 ? SSLK : SSLV;
    uint64_t m = 0;
    for (int j = j0; j < j0 + len; j++)
        if ((j - j0) * ns / len != (j - j0 + 1) * ns / len) m |= 1ull << (x_order(mat, j >> 2) * 4 + (j & 3));
    return m;
}
__device__ __forceinline__ int popc_below(uint64_t m, int k) { return __popcll(m & ((1ull << k) - 1)); }
__host__ __device__ constexpr int x_slot(int f) {
    return f == 0 || f == 6 || f == 9 ? E_R0 : f == 1 || f == 7 ? E_R2 : f < 4 ? E_MEM + (f - 2) * 8192 : f == 4 ? E_QT : f == 5 ? E_KT : f == 8 ? E_VP : E_R1;
}
__host__ __device__ constexpr int x_empty(int blk) { return blk == 3 ? 0 : blk == 6 ? 1 : blk == 5 ? 2 : -1; }
__host__ __device__ constexpr int ar_tile(int j) { return WO_MODE == 2 ? (j == 8 ? 8 : (j & 1) * 4 + (j >> 1)) : j == 0 ? 8 : ((j - 1) & 1) * 4 + ((j - 1) & 2) + (j > 4); }
__host__ __device__ constexpr int sx_off(int u) { return u == 0 ? 0 : u == 1 ? 1536 : u == 2 ? 2560 : u == 3 ? 3072 : 5120; }

template <int MAT, int NR, int K0, int K1>
__device__ __forceinline__ void proj_mem(float* d, const uint32_t (&w)[NR][4]) {
    constexpr uint64_t M = ss_mask(MAT);
    const uint64_t db = mkdesc(E_MEM, 128, 9216, 0);
    const uint64_t da = mkdesc((MAT == 0 ? E_WQ : MAT == 1 ? E_WK : E_WV), 1024, 1024, 1);
#pragma unroll
    for (int ks = K0; ks < K1; ks++) {
        const int s = popc_below(M, ks);
        if ((M >> ks) & 1) wg_ss16(d, da + s * 128, db + ks * 16, ks > 0);
        else wg_rs16(d, w[ks - s], db + ks * 16, ks > 0);
    }
}
__device__ __forceinline__ uint32_t tl_lane(int tid, int group_bytes) {
    return ((tid >> 4) & 1) * group_bytes + (((tid >> 5) & 3) * 16 + (tid & 15)) * 16;
}
struct ArWords {
    uint32_t w[5];
    __device__ __forceinline__ ArWords(const float* y) {
        w[0] = pack2(y[0], y[1]); w[1] = pack2(y[2], y[3]); w[2] = pack2(y[4], y[5]); w[3] = pack2(y[6], 1.f); w[4] = pack2(y[7], 1.f);
    }
    __device__ __forceinline__ void force(uint32_t zero) {
        asm volatile("{.reg .pred p; setp.ne.u32 p, %0, 0; @p st.shared.v4.b32 [%5], {%1,%2,%3,%4};}" :: "r"(zero), "r"(w[0]), "r"(w[1]), "r"(w[2]), "r"(w[3]), "r"(w[4]) : "memory");
    }
    __device__ __forceinline__ void red(uint8_t* p, uint8_t* q) {
        asm volatile("red.relaxed.gpu.global.add.noftz.v4.bf16x2 [%0], {%1,%2,%3,%4};" :: "l"(p), "r"(w[0]), "r"(w[1]), "r"(w[2]), "r"(w[3]) : "memory");
        asm volatile("red.relaxed.gpu.global.add.noftz.bf16x2 [%0], %1;" :: "l"(q), "r"(w[4]) : "memory");
    }
};
__device__ __forceinline__ uint32_t ar_main(int tid) { return ((tid & 127) >> 3) * AR_STR + (tid & 7) * 16; }
__device__ __forceinline__ uint32_t ar_side(int tid) { return ((tid & 127) >> 5) * (4 * AR_STR) + AR_STR / 2 + (tid & 31) * 4; }

#define AR_LDQ 2
#define AR_LDK 2
#define AR_STQ 6
#define AR_STK 5
#define AR_VWAIT 1
#define AR_J1 3
#define AR_J2 5
template <int MAT> struct ArPart {
    static constexpr int J0 = MAT == 0 ? 0 : MAT == 1 ? AR_J1 : AR_J2, J1 = MAT == 0 ? AR_J1 : MAT == 1 ? AR_J2 : 9;
    uint4 av[J1 - J0];
    uint32_t as[J1 - J0];
    __device__ __forceinline__ void load(int i, int tid) {
        const uint8_t* pm = g_ar + ((i & 3) * AR_SLOT + ar_main(tid));
        const uint8_t* ps = g_ar + ((i & 3) * AR_SLOT + ar_side(tid));
#pragma unroll
        for (int j = J0; j < J1; j++) { av[j - J0] = ld_rlx128(pm + ar_tile(j) * (16 * AR_STR)); as[j - J0] = ld_rlx(ps + ar_tile(j) * (16 * AR_STR)); }
    }
    __device__ __forceinline__ void first_load(int i, int tid) {
        const uint8_t* pm = g_ar + ((i & 3) * AR_SLOT + ar_main(tid));
        const uint8_t* ps = g_ar + ((i & 3) * AR_SLOT + ar_side(tid));
#pragma unroll
        for (int j = 0; j < J1 - J0; j++) {
            av[j] = make_uint4(0, 0, 0, 0); as[j] = 0;
            asm volatile("{.reg .pred p; setp.ge.s32 p, %7, 0; @p ld.relaxed.gpu.global.v4.u32 {%0,%1,%2,%3}, [%5]; @p ld.relaxed.gpu.global.u32 %4, [%6];}"
                         : "+r"(av[j].x), "+r"(av[j].y), "+r"(av[j].z), "+r"(av[j].w), "+r"(as[j])
                         : "l"(pm + ar_tile(J0 + j) * (16 * AR_STR)), "l"(ps + ar_tile(J0 + j) * (16 * AR_STR)), "r"(i) : "memory");
        }
    }
    __device__ __forceinline__ bool complete(uint32_t one = 1) {
        bool ok = true;
#pragma unroll
        for (int j = J0; j < J1; j++) {
            ok &= __byte_perm(av[j - J0].w, as[j - J0], 0x7631 + one) == (ar_tile(j) == 8 ? 0x42804280u : 0x42004200u);
            av[j - J0].w = __byte_perm(av[j - J0].w, as[j - J0], 0x540f + one);
        }
        return __all_sync(~0u, ok);
    }
    __device__ __forceinline__ void store(const Params& P, int i, int tid) {
        [[maybe_unused]] int n = 0;
        const uint32_t one = MAT != 2 || !AR_VWAIT ? mbar_wait(bars + EB_EMPTY * 8, (i & 1) ^ 1) : 1;
        if (__builtin_expect(!complete(one) || i + 1 == LAG, 0)) {
            if (i >= 0) do { load(i, pin(tid << P.zero)); SPIN_CHECK(n, 2); PROF_INC(n, 1); } while (!complete());
            if (i < 0 || i + 1 == LAG) {
                mbar_wait(bars + EB_WO * 8, 0);
                const uint16_t* m = (const uint16_t*)P.mem0 + (tid & 3) * (2 * DM) + ((tid >> 5) & 3) * 16 + ((tid & 31) >> 2);
#pragma unroll
                for (int j = J0; j < J1; j++) {
                    const int f = ar_tile(j) * 64;
                    av[j - J0].z = (uint32_t)__ldg(m + f) | ((uint32_t)__ldg(m + f + DM) << 16);
                    av[j - J0].w = (uint32_t)__ldg(m + f + 8) | ((uint32_t)__ldg(m + f + DM + 8) << 16);
                    if (i < 0) { av[j - J0].x = av[j - J0].z; av[j - J0].y = av[j - J0].w; }
                }
            }
        }
        const uint32_t a = sb + E_MEM + tl_lane(tid, 9216);
#pragma unroll
        for (int j = J0; j < J1; j++) stsm4(a + ar_tile(j) * 1024, av[j - J0].x, av[j - J0].y, av[j - J0].z, av[j - J0].w);
    }
};

__device__ __forceinline__ void attn_mem(float* d, uint32_t par, int i, int tid) {
    const int lane = tid & 31, warp = tid >> 5, c = warp >> 1, hf = warp & 1;
    const int rank = cta_rank();
    const uint32_t peer = mapa(sb, rank ^ 1);
    const uint32_t l4 = (lane >> 4) * 1024 + (lane & 15) * 16;
    uint32_t kb[4][4];
    mbar_wait_cl(bars + EB_VX * 8, par);
    if (VM_EARLY) mbar_wait_cl(bars + EB_VM * 8, par);
    mbar_wait(bars + EB_STEP * 8, par);
    {
        const uint32_t aK = sb + E_KT + (c * 6 + hf * 2) * 1024 + l4;
#pragma unroll
        for (int ks = 0; ks < 4; ks++) ldsm4t(kb[ks], aK + ks * 256);
    }
    const uint32_t aQs = pin(sb + E_QM + tl_lane(tid, 1024));
    const uint32_t aQ = pin(sb + E_QM + c * 1024 + (((lane >> 3) & 1) * 16 + (lane >> 4) * 8 + (lane & 7)) * 16);
    const uint32_t aM = pin(sb + E_KT + (4 + c) * 1024 + lane * 16);
    const uint32_t oS = pin(tid * 16);
    const uint32_t aV = pin(sb + (hf == rank ? E_VT + c * 6144 : E_VP + c * 4096) + l4);
    wg_wait_acc<0, 8>(d);
    stsm4(aQs, pack2(d[0], d[1]), pack2(d[2], d[3]), pack2(d[4], d[5]), pack2(d[6], d[7]));
    nbar_sync(NB_QK, 256);
    TS(0, i, 1);
    float s[6];
    {
        uint32_t q[2][4], km[2][4];
        ldsm4t(q[0], aQ); ldsm4t(km[0], aM); ldsm4t(q[1], aQ + 512); ldsm4t(km[1], aM + 512);
        float a[6][4];
#pragma unroll
        for (int m = 0; m < 6; m++) a[m][0] = a[m][1] = a[m][2] = a[m][3] = 0.f;
#pragma unroll
        for (int j = 0; j < 2; j++) {
#pragma unroll
            for (int o = 0; o < 2; o++) {
                mma16816(a[o * 3], q[j], kb[2 * j + o][0], kb[2 * j + o][1]);
                mma16816(a[o * 3 + 1], q[j], kb[2 * j + o][2], kb[2 * j + o][3]);
            }
            mma16816(a[2], q[j], km[j][0], km[j][1]);
            mma16816(a[5], q[j], km[j][2], km[j][3]);
        }
        nbar_arrive(NB_S, 256);
        if (SX_GATE) nbar_arrive(NB_S2, 256);
#pragma unroll
        for (int m = 0; m < 3; m++) { s[2 * m] = a[m][0] + a[3 + m][2]; s[2 * m + 1] = a[m][1] + a[3 + m][3]; }
    }
    st_async128(peer + E_SR + oS, fu(s[0]), fu(s[1]), fu(s[2]), fu(s[3]), peer + SM_BAR + EB_SM * 8);
    const uint32_t oM = E_SR + 2048 + c * 256 + lane * 8;
    asm volatile("st.async.shared::cluster.mbarrier::complete_tx::bytes.b32 [%0], %1, [%2];"
                 :: "r"(peer + oM + hf * 4), "r"(fu(hf ? s[5] : s[4])), "r"(peer + SM_BAR + EB_SM * 8) : "memory");
    sts128(sb + E_SL + oS, fu(s[0]), fu(s[1]), fu(s[2]), fu(s[3]));
    mbar_arrive_warp(bars + EB_KF * 8);
    TS(0, i, 2);
#pragma unroll
    for (int T = 0; T < 4; T++) ldsm4(kb[T], aV + hf * 2048 + T * 256);
    nbar_sync(NB_G, 128);
    const uint32_t aO = sb + E_OM + c * OM_STR + (hf * 64 + lane) * 16;
    const uint32_t aR = sb + E_SR + oS, aR1 = sb + E_SR + (oS ^ 512), aRm = sb + oM, aV1 = aV + (hf ^ 1) * 2048;
    const uint4 l1 = lds128(aR1 + (E_SL - E_SR));
    mbar_wait_cl(bars + EB_SM * 8, par);
    TS(0, i, 3);
    float p[10];
    {
        const uint4 r0 = lds128(aR), r1 = lds128(aR1);
        const uint2 rm = lds64(aRm);
        p[0] = s[0] + uf(r0.x); p[1] = s[1] + uf(r0.y); p[2] = s[2] + uf(r0.z); p[3] = s[3] + uf(r0.w);
        p[4] = uf(l1.x) + uf(r1.x); p[5] = uf(l1.y) + uf(r1.y); p[6] = uf(l1.z) + uf(r1.z); p[7] = uf(l1.w) + uf(r1.w);
        p[8] = s[4] + uf(rm.x); p[9] = s[5] + uf(rm.y);
    }
    float mx = fmaxf(fmaxf(fmaxf(p[0], p[1]), fmaxf(p[2], p[3])), fmaxf(fmaxf(fmaxf(p[4], p[5]), fmaxf(p[6], p[7])), fmaxf(p[8], p[9])));
    mx = fmaxf(mx, __shfl_xor_sync(~0u, mx, 1));
    mx = fmaxf(mx, __shfl_xor_sync(~0u, mx, 2));
    const float mo = mx * (SM_SCALE * LOG2E);
    uint32_t pb[5];
    float o[5][4];
    const uint32_t ones[4] = {0x3f803f80u, 0x3f803f80u, 0x3f803f80u, 0x3f803f80u};
#pragma unroll
    for (int m = 0; m < 2; m++) pb[m] = pack2(ex2(fmaf(p[2 * m], SM_SCALE * LOG2E, -mo)), ex2(fmaf(p[2 * m + 1], SM_SCALE * LOG2E, -mo)));
#pragma unroll
    for (int T = 0; T < 5; T++) o[T][0] = o[T][1] = o[T][2] = o[T][3] = 0.f;
    mma16816(o[4], ones, pb[0], pb[1]);
#pragma unroll
    for (int T = 0; T < 4; T++) { mma16816(o[T], kb[T], pb[0], pb[1]); ldsm4(kb[T], aV1 + T * 256); }
#pragma unroll
    for (int m = 2; m < 5; m++) pb[m] = pack2(ex2(fmaf(p[2 * m], SM_SCALE * LOG2E, -mo)), ex2(fmaf(p[2 * m + 1], SM_SCALE * LOG2E, -mo)));
    if (!VM_EARLY) mbar_wait_cl(bars + EB_VM * 8, par);
    uint2 vm[4];
#pragma unroll
    for (int T = 0; T < 4; T++) vm[T] = lds64(sb + E_VF + hf * 2048 + lane * 16 + c * 8 + T * 512);
    mma16816(o[4], ones, pb[2], pb[3]);
#pragma unroll
    for (int T = 0; T < 4; T++) mma16816(o[T], kb[T], pb[2], pb[3]);
    mma1688(o[4], ones[0], ones[1], pb[4]);
#pragma unroll
    for (int T = 0; T < 4; T++) mma1688(o[T], vm[T].x, vm[T].y, pb[4]);
    nbar_arrive(NB_PV, 256);
    mbar_arrive_warp(bars + EB_CONS * 8);
    const float i0 = rcp(o[4][0]), i1 = rcp(o[4][1]);
#pragma unroll
    for (int j = 0; j < 2; j++)
        stsm4(aO + j * 512, pack2(o[2 * j][0] * i0, o[2 * j][1] * i1), pack2(o[2 * j][2] * i0, o[2 * j][3] * i1),
              pack2(o[2 * j + 1][0] * i0, o[2 * j + 1][1] * i1), pack2(o[2 * j + 1][2] * i0, o[2 * j + 1][3] * i1));
}

__device__ __forceinline__ void attn_x_scores(float (&p)[2][10], uint32_t par, int i, int tid) {
    {
        float s[40];
        const uint64_t da = mkdesc(E_QT, 128, 1024, 0), db = mkdesc(E_KT, 128, 1024, 0);
        wg_fence();
#pragma unroll
        for (int ks = 0; ks < 4; ks++) wg_ss80(s, da + ks * 16, db + ks * 16, ks > 0);
        wg_commit();
        const int dq = (tid >> 2) - 2 * (tid & 3);
        float mask[8];
#pragma unroll
        for (int j = 0; j < 8; j++) mask[j] = (j >> 1) * 8 + (j & 1) > dq ? -1e9f * LOG2E : 0.f;
        mbar_wait_cl(bars + EB_PRDY2 * 8, par);
        wg_wait_acc<0, 40>(s);
#pragma unroll
        for (int u = 0; u < 5; u++) {
            const int v = u < 4 ? 6 + u : 5;
            constexpr float C = SM_SCALE * LOG2E;
            const float m0 = u < 4 ? mask[2 * u & 7] : 0.f, m1 = u < 4 ? mask[(2 * u + 1) & 7] : 0.f;
            p[0][2 * u] = fmaf(s[4 * u], C, m0); p[0][2 * u + 1] = fmaf(s[4 * u + 1], C, m1); p[1][2 * u] = fmaf(s[4 * v + 2], C, m0); p[1][2 * u + 1] = fmaf(s[4 * v + 3], C, m1);
        }
    }
    mbar_arrive_warp(bars + EB_QF * 8);
    const int w = tid >> 5;
    if (!SX_BF16) {
        const uint32_t peer = mapa(sb, cta_rank() ^ 1);
#pragma unroll
        for (int u = 0; u < 5; u++)
            if (u == 0 || u <= w || u == 4) st_async128(peer + E_SX + sx_off(u) + tid * 16, fu(p[0][2 * u]), fu(p[0][2 * u + 1]), fu(p[1][2 * u]), fu(p[1][2 * u + 1]), peer + SM_BAR + EB_SX * 8);
    } else {
        const uint32_t peer = mapa(sb, cta_rank() ^ 1), a = peer + E_SX + tid * 16, mb = peer + SM_BAR + EB_SX * 8;
        st_async128(a, pack2(p[0][0], p[0][1]), pack2(p[1][0], p[1][1]), pack2(p[0][8], p[0][9]), pack2(p[1][8], p[1][9]), mb);
        if (w >= 1) st_async128(a + 2048, pack2(p[0][2], p[0][3]), pack2(p[1][2], p[1][3]), pack2(p[0][4], p[0][5]), pack2(p[1][4], p[1][5]), mb);
        if (w >= 3) st_async64(a + 4096, pack2(p[0][6], p[0][7]), pack2(p[1][6], p[1][7]), mb);
    }
    TS(128, i, 10);
}
__device__ __forceinline__ void attn_x_finish(float (&p)[2][10], uint32_t par, int i, int& tid, uint32_t zero) {
    const int w = tid >> 5;
    mbar_wait_cl(bars + EB_SX * 8, par);
    TS(128, i, 11);
    if (SX_BF16) {
        const uint32_t a = sb + E_SX + tid * 16;
        const uint4 r0 = lds128(a), r1 = lds128(a + (w >= 1 ? 2048 : 0));
        const uint2 r2 = lds64(a + (w >= 3 ? 4096 : 0));
        const uint32_t r[10] = {r0.x, r0.y, r1.x, r1.y, r1.z, r1.w, r2.x, r2.y, r0.z, r0.w};
#pragma unroll
        for (int j = 0; j < 10; j++) { p[j & 1][j & ~1] += bf_lo(r[j]); p[j & 1][j | 1] += bf_hi(r[j]); }
    } else
#pragma unroll
    for (int u = 0; u < 5; u++) {
        const uint4 r = lds128(pin(sb + tid * 16 + (u == 0 || u <= w ? sx_off(u) : sx_off(4))) + E_SX);
        p[0][2 * u] += uf(r.x); p[0][2 * u + 1] += uf(r.y); p[1][2 * u] += uf(r.z); p[1][2 * u + 1] += uf(r.w);
    }
    nbar_sync(NB_W, 128);
    uint32_t pa[5][4];
    float mx[2], inv[2];
#pragma unroll
    for (int h = 0; h < 2; h++) {
        const float* q = p[h];
        mx[h] = fmaxf(fmaxf(fmaxf(q[0], q[1]), fmaxf(q[2], q[3])), fmaxf(fmaxf(fmaxf(q[4], q[5]), fmaxf(q[6], q[7])), fmaxf(q[8], q[9])));
    }
#pragma unroll
    for (int o = 1; o < 4; o <<= 1) { mx[0] = fmaxf(mx[0], __shfl_xor_sync(~0u, mx[0], o)); mx[1] = fmaxf(mx[1], __shfl_xor_sync(~0u, mx[1], o)); }
#pragma unroll
    for (int h = 0; h < 2; h++) {
        float* q = p[h];
#pragma unroll
        for (int j = 0; j < 10; j++) q[j] = ex2(q[j] - mx[h]);
#pragma unroll
        for (int u = 0; u < 4; u++) {
            pa[h * 3 + (u >> 1)][(u & 1) * 2 + h] = pack2(q[2 * u], q[2 * u + 1]);
            pa[h * 3 + (u >> 1)][(u & 1) * 2 + (h ^ 1)] = zero << (h * 5 + u + 1);
        }
        pa[2][h * 3] = pack2(q[8], q[9]);
        pa[2][1 + h] = zero << (h * 5 + 5);
    }
    mbar_wait(bars + (PVX_LATE ? EB_CONS : EB_KF) * 8, par);
    fence_async_smem();
    tid = pin(tid << zero);
    const uint32_t aO = pin(sb + (((tid >> 4) & 1) * 8 + (tid & 7)) * 128 + (((((tid >> 3) & 1) * 4 + (tid >> 5)) ^ (tid & 7)) << 4)) + E_R1;
    TS(128, i, 12);
#pragma unroll
    for (int nh = 0; nh < 2; nh++) {
        float o[16], sum[4];
        const uint64_t db = mkdesc(E_VT + nh * 512, 1024, 128, 0);
        wg_fence();
#pragma unroll
        for (int kk = 0; kk < 5; kk++) {
            if (nh == 0) wg_rs8(sum, pa[kk], mkdesc(SM_ONES, 0, 0, 0), kk > 0);
            wg_rs32(o, pa[kk], db + kk * 128, kk > 0);
        }
        wg_commit();
        wg_wait_acc<0, 16>(o);
        if (nh == 0) { acc_ready<4>(sum); inv[0] = rcp(sum[0]); inv[1] = rcp(sum[2]); }
#pragma unroll
        for (int j = 0; j < 2; j++) {
            const float* y = &o[8 * j];
            stsm4t(aO + nh * 4096 + j * 2048, pack2(y[0] * inv[0], y[1] * inv[0]), pack2(y[2] * inv[1], y[3] * inv[1]), pack2(y[4] * inv[0], y[5] * inv[0]), pack2(y[6] * inv[1], y[7] * inv[1]));
        }
    }
    mbar_arrive_warp(bars + EB_OST * 8);
    TS(128, i, 13);
}

template <int MAT>
__device__ __forceinline__ void engine_main(const Params& P) {
    constexpr int NR = MAT == 0 ? NRQ : MAT == 1 ? NRK : NRV;
    constexpr uint64_t M = ss_mask(MAT);
    uint32_t w[NR][4];
    {
        const uint32_t a = sb + E_WO + (MAT == 0 ? 0 : MAT == 1 ? NRQ : NRQ + NRK) * 2048 + unit_frag_addr(fresh_tid());
        mbar_wait(bars + EB_WL * 8, 0);
#pragma unroll
        for (int u = 0; u < NR; u++) ldsm4t(w[u], a + u * 2048);
    }
    cluster_sync_all();
    int tid = fresh_tid() - MAT * 128;
#define TID (tid = pin(tid << P.zero))
    if (MAT == 0) { if (V_FIRST == 36) nbar_arrive(NB_S, 256); nbar_arrive(NB_PV, 256); nbar_arrive(NB_WO, 256); }
    auto project = [&](const int i) {
        const uint32_t par = i & 1;
        ArPart<MAT> ar;
        {
            float d[32];
            const uint64_t da = mkdesc((MAT == 0 ? E_WQ : MAT == 1 ? E_WK : E_WV), 1024, 1024, 1);
            constexpr int R1 = V_BURST1, R2 = V_BURST1 + V_BURST2;
#pragma unroll
            for (int n = 0; n < 9; n++) {
                const int blk = x_order(MAT, n), prev = n ? x_order(MAT, n - 1) : -1, f = MAT != 2 && blk < 2 ? 9 + blk : blk;
                if (MAT == 2) {
                    if (n == (R1 >= 2 ? R1 : R2)) { wg_wait<0>(); mbar_arrive_warp(bars + EB_V0 * 8); }
                    if ((n == 0 && (V_FIRST == 36 || i == 0)) || n == R1 || n == R2) {
#pragma unroll
                        for (int j = n; j < (n < R1 ? R1 : n < R2 ? R2 : V_PRE); j++) mbar_wait(bars + (EB_FULL + j) * 8, par);
                    }
                    if (n == 0 && V_FIRST == 36) nbar_sync(NB_S, 256);
                    if (n == R1) nbar_sync(NB_PV, 256);
                    if (n == R2) nbar_sync(NB_WO, 256);
                } else {
                    if (n == 0) nbar_sync(MAT ? NB_VL : NB_VL2, 256);
                }
                const bool wt = f >= (MAT == 2 || V_LEAD < V_PRE ? V_PRE : V_LEAD);
                if (wt) mbar_wait(bars + (EB_FULL + f) * 8, par);
                TX(MAT * 128, 1 + MAT * 9 + n);
                if (wt || n == 0 || (MAT == 2 ? n == R1 || n == R2 : n - 1 == (MAT ? AR_STK : AR_STQ))) wg_fence();
                if (n == 0) TS(MAT * 128, i, 20 + MAT);
                const uint64_t db = mkdesc(x_slot(f), 16, 1024, 1);
#pragma unroll
                for (int j = 0; j < 4; j++) {
                    const int ks = blk * 4 + j, s = popc_below(M, ks);
                    if ((M >> ks) & 1) wg_ss64<0>(d, da + s * 128, db + j * 2, n + j > 0);
                    else wg_rs64<0>(d, w[ks - s], db + j * 2, n + j > 0);
                }
                wg_commit();
                if (MAT == 2 && n + 1 == V_LEAD) { nbar_arrive(NB_VL, 256); if (!K_LEAD) nbar_arrive(NB_VL2, 256); }
                if (MAT == 1 && n + 1 == K_LEAD) nbar_arrive(NB_VL2, 256);
                if (MAT != 2 && n == (MAT ? AR_LDK : AR_LDQ)) { ar.first_load(i - 1, TID); }
                if (MAT != 2 && n == (MAT ? AR_STK : AR_STQ)) { ar.store(P, i - 1, TID); mbar_arrive_warp(bars + EB_MEM0 * 8); }
                if (MAT != 2 && x_empty(prev) >= 0) { wg_wait<1>(); mbar_arrive_warp(bars + (EB_EMPTY + x_empty(prev)) * 8); }
            }
            const uint32_t a = sb + (MAT == 0 ? E_QT : MAT == 1 ? E_KT : E_VT) + tl_lane(TID, MAT == 0 ? 2048 : 1024);
            if (MAT != 2) {
                mbar_wait(bars + (EB_EMPTY + 2) * 8, par);
                mbar_wait(bars + EB_MEM * 8, par);
            } else {
                mbar_wait(bars + EB_OST * 8, par ^ 1);
            }
            wg_wait_acc<0, 32>(d);
            TS(MAT * 128, i, 23 + MAT);
#pragma unroll
            for (int j = 0; j < 8; j += 2) {
                const int grp = MAT == 0 ? 2 * (j & 3) + (j >> 2) : j < 4 ? j : j + 2;
                stsm4(a + grp * 1024, pack2(d[4 * j], d[4 * j + 1]), pack2(d[4 * j + 2], d[4 * j + 3]), pack2(d[4 * j + 4], d[4 * j + 5]), pack2(d[4 * j + 6], d[4 * j + 7]));
            }
        }
        if (MAT != 2) {
            mbar_arrive_warp(bars + EB_STEP * 8);
        } else {
            __syncwarp();
            if ((TID & 31) < 3) mbar_arrive(bars + (EB_EMPTY + (tid & 31)) * 8);
            if (AR_VWAIT) mbar_wait(bars + EB_EMPTY * 8, par);
            ar.first_load(i - 1, TID);
            ar.store(P, i - 1, tid);
            TS(256, i, 19);
            mbar_wait(bars + EB_MEM0 * 8, par);
            fence_async_smem();
            mbar_arrive_warp(bars + EB_MEM * 8);
        }
    };
    auto step = [&](const int i) {
        const uint32_t par = i & 1;
        if (MAT == 2) {
            if (Q_LEAD) nbar_sync(NB_OM, 256);
            else mbar_wait(bars + EB_MEM * 8, par);
        }
        float d[8];
        TS(MAT * 128, i, MAT == 2 ? 26 : 14 + MAT);
        wg_fence();
        constexpr int MID = MAT == 0 ? Q_LEAD : MAT == 2 ? V_FIRST : 0;
        proj_mem<MAT, NR, 0, MID>(d, w);
        if (MAT == 0 && Q_LEAD) nbar_arrive(NB_OM, 256);
        if (MAT == 2 && V_FIRST < 36) {
#pragma unroll
            for (int j = 0; j < V_BURST1; j++) mbar_wait(bars + (EB_FULL + j) * 8, i == NSTEP - 1 ? par : par ^ 1);
            nbar_sync(NB_S, 256);
            wg_fence();
        }
        proj_mem<MAT, NR, MID, 36>(d, w);
        wg_commit();
        if (MAT == 0) {
            attn_mem(d, par, i, TID);
        } else if (MAT == 1) {
            tid *= mbar_wait(bars + EB_STEP * 8, par);
            const uint32_t a = pin(sb + E_KT + 4096 + tl_lane(tid, 1024));
            wg_wait_acc<0, 8>(d);
            stsm4(a, pack2(d[0], d[1]), pack2(d[2], d[3]), pack2(d[4], d[5]), pack2(d[6], d[7]));
            nbar_arrive(NB_QK, 256);
            TS(128, i, 18);
            fence_async_smem();
            nbar_sync(SX_GATE ? NB_S2 : NB_W, SX_GATE ? 256 : 128);
            float p[2][10];
            attn_x_scores(p, par, i, TID);
            attn_x_finish(p, par, i, TID, pin(P.zero));
        } else {
            const int rank = cta_rank();
            const uint32_t a = pin(sb + E_VT + 4096 + tl_lane(TID, 1024)), of = pin(E_VF + rank * 2048 + (tid & 127) * 16);
            const uint32_t peer = pin(mapa(sb, rank ^ 1));
            wg_wait_acc<0, 8>(d);
            const uint32_t v0 = pack2(d[0], d[1]), v1 = pack2(d[2], d[3]), v2 = pack2(d[4], d[5]), v3 = pack2(d[6], d[7]);
            st_async128(peer + of, v0, v1, v2, v3, peer + SM_BAR + EB_VM * 8);
            sts128(sb + of, v0, v1, v2, v3);
            stsm4(a, v0, v1, v2, v3);
            mbar_arrive_warp(bars + EB_VM * 8);
            mbar_arrive_warp(bars + EB_KF * 8);
            TS(256, i, 16);
        }
        if (MAT == 0) {
            const int rank = cta_rank();
            uint8_t* const ar = g_ar + (i & 3) * AR_SLOT;
            uint8_t* const pm = ar + pin(ar_main(TID) + rank * (64 * AR_STR));
            uint8_t* const ps = ar + pin(ar_side(tid) + rank * (64 * AR_STR));
            const uint32_t o8 = (128 - rank * 64) * AR_STR;
            const uint64_t db = mkdesc(E_OM, 128, OM_STR, 0), da = mkdesc(E_WO, 1024, 1024, 1);
            nbar_sync(NB_G, 128);
            fence_async_smem();
            TS(0, i, 6);
            if (i == NSTEP - 1) return;
            float y[4][8];
            wg_fence();
            if (WO_MODE == 2) {
#pragma unroll
                for (int T = 0; T < 4; T++) {
#pragma unroll
                    for (int ks = 0; ks < 8; ks++) wg_ss16(y[T], da + (T * 8 + ks) * 128, db + ks * 16, ks > 0);
                    wg_commit();
                }
                if (V_EARLY) nbar_arrive(NB_WO, 256);
                wg_wait_acc<2, 8>(y[0]); acc_ready<8>(y[1]);
                { ArWords z(y[0]); z.red(pm, ps); z.force(P.zero); }
                ArWords(y[1]).red(pm + 16 * AR_STR, ps + 16 * AR_STR);
                wg_wait_acc<1, 8>(y[2]);
                ArWords(y[2]).red(pm + 32 * AR_STR, ps + 32 * AR_STR);
                wg_fence();
#pragma unroll
                for (int ks = 0; ks < 4; ks++) wg_ss16(y[0], da + (32 + ks) * 128, db + (rank * 4 + ks) * 16, ks > 0);
                wg_commit();
                if (!V_EARLY) nbar_arrive(NB_WO, 256);
                wg_wait_acc<1, 8>(y[3]);
                ArWords(y[3]).red(pm + 48 * AR_STR, ps + 48 * AR_STR);
                wg_wait_acc<0, 8>(y[0]);
                ArWords(y[0]).red(pm + o8, ps + o8);
                return;
            }
#pragma unroll
            for (int ks = 0; ks < 4; ks++) wg_ss16(y[3], da + (32 + ks) * 128, db + (rank * 4 + ks) * 16, ks > 0);
            wg_commit();
#pragma unroll
            for (int ks = 0; ks < 8; ks++) wg_ss16(y[0], da + ks * 128, db + ks * 16, ks > 0);
            wg_commit();
            if (WO_MODE == 0) {
#pragma unroll
                for (int ks = 0; ks < 8; ks++) wg_ss16(y[2], da + (16 + ks) * 128, db + ks * 16, ks > 0);
                wg_commit();
                wg_wait_acc<2, 8>(y[3]);
                ArWords z(y[3]);
                z.force(P.zero);
                wg_fence();
#pragma unroll
                for (int ks = 0; ks < 8; ks++) wg_ss16(y[1], da + (8 + ks) * 128, db + ks * 16, ks > 0);
                wg_commit();
#pragma unroll
                for (int ks = 0; ks < 8; ks++) wg_ss16(y[3], da + (24 + ks) * 128, db + ks * 16, ks > 0);
                wg_commit();
                if (V_EARLY) nbar_arrive(NB_WO, 256);
                z.red(pm + o8, ps + o8);
                wg_wait_acc<2, 8>(y[2]); acc_ready<8>(y[0]);
                ArWords(y[0]).red(pm, ps);
                ArWords(y[2]).red(pm + 32 * AR_STR, ps + 32 * AR_STR);
            } else {
                wg_wait_acc<1, 8>(y[3]);
                { ArWords z(y[3]); z.red(pm + o8, ps + o8); z.force(P.zero); }
                wg_fence();
#pragma unroll
                for (int ks = 0; ks < 8; ks++) wg_ss16(y[2], da + (16 + ks) * 128, db + ks * 16, ks > 0);
                wg_commit();
                wg_wait_acc<1, 8>(y[0]);
                { ArWords z(y[0]); z.red(pm, ps); z.force(P.zero); }
                wg_fence();
#pragma unroll
                for (int ks = 0; ks < 8; ks++) wg_ss16(y[1], da + (8 + ks) * 128, db + ks * 16, ks > 0);
                wg_commit();
                wg_wait_acc<1, 8>(y[2]);
                { ArWords z(y[2]); z.red(pm + 32 * AR_STR, ps + 32 * AR_STR); z.force(P.zero); }
                wg_fence();
#pragma unroll
                for (int ks = 0; ks < 8; ks++) wg_ss16(y[3], da + (24 + ks) * 128, db + ks * 16, ks > 0);
                wg_commit();
                if (V_EARLY) nbar_arrive(NB_WO, 256);
            }
            wg_wait_acc<1, 8>(y[1]);
            ArWords(y[1]).red(pm + 16 * AR_STR, ps + 16 * AR_STR);
            wg_wait_acc<0, 8>(y[3]);
            ArWords(y[3]).red(pm + 48 * AR_STR, ps + 48 * AR_STR);
            if (!V_EARLY) nbar_arrive(NB_WO, 256);
            TS(0, i, 7);
        }
    };
    if (MAT != 2) {
#pragma unroll 1
        for (int i = 0; i < NSTEP; i++) { project(i); step(i); }
    } else {
#pragma unroll 1
        for (int i = -1; i < NSTEP; i++) {
            if (i >= 0) step(i);
            if (i < NSTEP - 1) project(i + 1);
        }
    }
    if (MAT == 2) { if (V_FIRST == 36) nbar_sync(NB_S, 256); nbar_sync(NB_PV, 256); }
}

__device__ __forceinline__ void engine_helper(const Params& P) {
    const int lane = threadIdx.x & 31, hw = warp_in_group(), e = blockIdx.x, rank = e & 1;
    if (hw < 3) {
        constexpr uint64_t M0 = ss_mask(0), M1 = ss_mask(1), M2 = ss_mask(2);
        const uint64_t m = hw == 0 ? M0 : hw == 1 ? M1 : M2;
        const uint32_t ws = sb + (hw == 0 ? E_WQ : hw == 1 ? E_WK : E_WV), wr = sb + E_WO + (hw == 0 ? 0 : hw == 1 ? NRQ : NRQ + NRK) * 2048;
        if (lane == 0) mbar_expect(bars + EB_WL * 8, 36 * 2048);
        __syncwarp();
        for (int ks = lane; ks < 36; ks += 32) {
            const int s = __popcll(m & ((1ull << ks) - 1));
            tma_unit(((m >> ks) & 1) ? ws + s * 2048 : wr + (ks - s) * 2048, hw == 0 ? &P.tmWq : hw == 1 ? &P.tmWk : &P.tmWv, ks, e, bars + EB_WL * 8);
        }
    }
    __syncwarp();
    cluster_sync_all();
    if (hw == 0) {
        if (lane == 0) {
            const uint32_t peer = mapa(sb, rank ^ 1);
#pragma unroll 1
            for (int n = 0; n < NSTEP; n++) {
                const uint32_t par = (n & 1) ^ 1;
                uint32_t rdy;
                do { asm volatile("ld.acquire.cta.shared.u32 %0, [%1];" : "=r"(rdy) : "r"(sb + SM_XRDY) : "memory"); } while (rdy <= n && (__nanosleep(20), true));
                fence_async_glb();
                TG(n, 30);
                const uint8_t* s0 = g_x0 + min(n, NSEG - 1) * XIMG;
                const uint8_t* s1 = n >= LAG ? g_x1 + (n - LAG) * XIMG : s0;
#pragma unroll
                for (int j = 0; j < 11; j++) {
                    const int f = j < 9 ? j : 19 - j, blk = f < 9 ? f : f - 9;
                    if (n > 0 && (f == 0 || f == 2 || f == 4 || f == 8 || f == 10))
                        mbar_wait(bars + (f == 0 ? EB_STEP : f == 2 ? EB_KF : f == 4 ? EB_QF : f == 8 ? EB_CONS : EB_OFREE) * 8, par);
                    if (f == 6 || f == 9) mbar_wait(bars + (f == 6 ? EB_V0 : EB_EMPTY + 1) * 8, par ^ 1);
                    const uint32_t fb = bars + (EB_FULL + f) * 8;
                    mbar_expect(fb, 8192);
                    bulk_g2s(sb + x_slot(f), s0 + blk * 4096, 4096, fb);
                    bulk_g2s(sb + x_slot(f) + 4096, s1 + blk * 4096, 4096, fb);
                }
                mbar_arrive_remote(peer + SM_BAR + EB_PRDY * 8);
            }
        }
    } else if (hw == 1) {
        if (lane == 0) {
#pragma unroll 1
            for (int i = 0; i < NSTEP; i++) {
                mbar_wait(bars + EB_STEP * 8, i & 1);
                mbar_arrive_remote(mapa(sb, rank ^ 1) + SM_BAR + EB_PRDY2 * 8);
                mbar_wait(bars + EB_OST * 8, i & 1);
                fence_async_smem();
                bulk_s2g(g_o + (i & (RING - 1)) * O_BYTES + e * 8192, sb + E_R1, 8192);
                asm volatile("cp.async.bulk.commit_group;" ::: "memory");
                asm volatile("cp.async.bulk.wait_group.read 0;" ::: "memory");
                mbar_arrive(bars + EB_OFREE * 8);
                asm volatile("cp.async.bulk.wait_group 0;" ::: "memory");
                publish(F_O, i);
                TG(i, 31);
            }
        }
    } else if (hw == 2) {
        const uint32_t peer = mapa(sb, rank ^ 1);
        const int idx = e * 23 + lane, line = idx >> 3;
        uint8_t* z = g_ar + (line < 144 ? line * AR_STR : (line - 144) * (4 * AR_STR) + AR_STR / 2) + (idx & 7) * 16;
        if (lane == 0) mbar_arrive(bars + EB_MEM * 8);
#pragma unroll 1
        for (int i = 0; i < NSTEP; i++) {
            mbar_wait(bars + EB_EMPTY * 8, i & 1);
            if (lane == 0) {
                mbar_wait_cl(bars + EB_PRDY * 8, i & 1);
                fence_async_smem();
                bulk_s2peer(peer + E_VP, sb + E_VT, 4096, peer + SM_BAR + EB_VX * 8);
                bulk_s2peer(peer + E_VP + 4096, sb + E_VT + 6144, 4096, peer + SM_BAR + EB_VX * 8);
                mbar_expect(bars + EB_VX * 8, 8192);
                mbar_expect(bars + EB_SX * 8, SX_BF16 ? 3840 : 7168);
                mbar_expect(bars + EB_SM * 8, 2560);
                mbar_expect(bars + EB_VM * 8, 2048);
            }
            __syncwarp();
            mbar_wait(bars + EB_MEM * 8, i & 1);
            if (i >= 2 && lane < 23 && idx < 1440) stg128(z + ((i + 2) & 3) * AR_SLOT, make_uint4(0, 0, 0, 0));
            __syncwarp();
            if (lane == 0) { fence_gpu(); mbar_arrive(bars + EB_MEM * 8); }
            __syncwarp();
        }
        flag_wait(F_O, NSTEP - 1, NENG * this_launch());
        if (lane < 23 && idx < 1440) stg128(z + ((NSTEP - 2) & 3) * AR_SLOT, make_uint4(0, 0, 0, 0));
    } else {
        if (lane == 0) mbar_expect(bars + EB_WO * 8, 36 * 2048);
        __syncwarp();
        for (int u = lane; u < 36; u += 32)
            tma_unit(sb + E_WO + u * 2048, &P.tmWo, (e >> 1) * 8 + (u < 32 ? u & 7 : rank * 4 + (u & 3)), u < 32 ? rank * 4 + (u >> 3) : 8, bars + EB_WO * 8);
        if (lane == 0) {
            const uint32_t ep = this_launch(), t0 = timer_lo();
#pragma unroll 1
            for (int n = 0; n < NSTEP; n++) {
                while ((n < NSEG && !flag_up(F_X0, n, 16 * ep)) || (n >= LAG && !flag_up(F_X1, n - LAG, 16 * ep))) {
                    __nanosleep(20);
                    if (timer_lo() - t0 > TIME_LIMIT) break;
                }
                fence_acq_gpu();
                asm volatile("st.release.cta.shared.u32 [%0], %1;" :: "r"(sb + SM_XRDY), "r"(n + 1) : "memory");
            }
        }
    }
    __syncwarp();
}

__device__ __forceinline__ void f1_fetch(const Params& P, uint32_t dst, int f0, int ks0, int n) {
    const int tid = threadIdx.x & 127, r = tid >> 3, c = tid & 7;
    const bf16* src = ((c & 1) ? P.w3 : P.w1) + (size_t)(ks0 * 16 + r) * FF + f0 + (c >> 1) * 8;
    dst += r * 128 + ((c ^ (r & 7)) << 4);
#pragma unroll 1
    for (int u = 0; u < n; u++)
        asm volatile("cp.async.cg.shared.global [%0], [%1], 16;" :: "r"(dst + u * 2048), "l"(src + (size_t)u * 16 * FF) : "memory");
}
template <bool RF, bool second>
__device__ __forceinline__ void f1_tile(const uint32_t (&w)[NRF][4], uint32_t ws, int b, int fo) {
    const uint32_t par = b & 1;
    float d[32];
    const uint64_t da = mkdesc(ws, 1024, 1024, 1), db = mkdesc(F_X, 16, 1024, 1);
#pragma unroll
    for (int blk = 0; blk < 9; blk++) {
        if (!second || blk == 0) mbar_wait(bars + (FB_FULL + blk) * 8, par);
        if (!second || blk == 0) wg_fence();
#pragma unroll
        for (int j = 0; j < 4; j++) {
            const int ks = blk * 4 + j;
            if (RF && ks < NRF) wg_rs64<0>(d, w[ks < NRF ? ks : 0], db + blk * 512 + j * 2, ks > 0);
            else wg_ss64<0>(d, da + (RF ? ks - NRF : 36 - NRF + ks) * 128, db + blk * 512 + j * 2, ks > 0);
        }
        wg_commit();
        if (blk > 0 && second) { wg_wait<1>(); mbar_arrive_warp(bars + (FB_EMPTY + blk - 1) * 8); }
    }
    const int tid = fresh_tid(), g = (tid & 31) >> 2;
    uint8_t* dst = g_h + (b & (RING - 1)) * H_BYTES + ((fresh_bid() - NENG) * 128 + fo + ((tid >> 5) & 3) * 8 + g) * 128;
    wg_wait_acc<0, 32>(d);
    if (second) mbar_arrive_warp(bars + (FB_EMPTY + 8) * 8);
    uint32_t h[8];
#pragma unroll
    for (int j = 0; j < 8; j++) {
        const float g0 = d[4 * j], g1 = d[4 * j + 1];
        const float e0 = 1.f + ex2(fminf(-LOG2E * g0, 60.f)), e1 = 1.f + ex2(fminf(-LOG2E * g1, 60.f));
        const float r = rcp(e0 * e1);
        h[j] = pack2(g0 * d[4 * j + 2] * (e1 * r), g1 * d[4 * j + 3] * (e0 * r));
    }
    stg128(dst + (((tid & 3) ^ g) << 4), make_uint4(h[0], h[1], h[2], h[3]));
    stg128(dst + ((((tid & 3) + 4) ^ g) << 4), make_uint4(h[4], h[5], h[6], h[7]));
}
template <int a>
__device__ __forceinline__ void f1_main(const Params& P) {
    constexpr uint32_t ws = F_W + a * (72 - NRF) * 2048;
    const int f0 = (blockIdx.x - NENG) * 128 + a * 64;
    uint32_t w[NRF][4];
    f1_fetch(P, sb + ws, f0, 0, NRF);
    asm volatile("cp.async.wait_all;" ::: "memory");
    nbar_sync(NB_G + a, 128);
    {
        const uint32_t fa = sb + ws + unit_frag_addr(threadIdx.x);
#pragma unroll
        for (int u = 0; u < NRF; u++) ldsm4t(w[u], fa + u * 2048);
    }
    nbar_sync(NB_G + a, 128);
    f1_fetch(P, sb + ws, f0, NRF, 36 - NRF);
    f1_fetch(P, sb + ws + (36 - NRF) * 2048, f0 + 32, 0, 36);
    asm volatile("cp.async.wait_all;" ::: "memory");
    fence_async_smem();
    nbar_sync(NB_G + a, 128);
#pragma unroll 1
    for (int b = 0; b < NSTEP; b++) {
        f1_tile<a == 0, false>(w, ws, b, a * 96);
        f1_tile<a == 1, true>(w, ws, b, 32 + a * 32);
        mbar_wait(bars + FB_RACK * 8, (b & 1) ^ 1);
        mbar_arrive_warp(bars + FB_H * 8);
    }
}
__device__ __forceinline__ uint32_t n_pairs(int b) { return (b < NSEG ? 16 : 0) + (b >= LAG ? 16 : 0); }
__device__ __forceinline__ void publisher(uint32_t done, uint32_t ack, int stage) {
#pragma unroll 1
    for (int b = 0; b < NSTEP; b++) {
        mbar_wait(done, b & 1);
        mbar_arrive(ack);
        TG(b, 30);
        publish(stage, b);
        TG(b, 31);
    }
}
__device__ __forceinline__ void f1_helper() {
    const int hw = warp_in_group();
    if ((threadIdx.x & 31) == 0) {
        if (hw == 0) {
            const uint32_t ep = this_launch();
#pragma unroll 1
            for (int b = 0; b < NSTEP; b++) {
                flag_wait(F_XF, b, n_pairs(b) * ep);
                TG(b, 29);
                const uint8_t* src = g_xf + (b & (RING - 1)) * (9 * 8192);
#pragma unroll 1
                for (int blk = 0; blk < 9; blk++) {
                    mbar_wait(bars + (FB_EMPTY + blk) * 8, (b & 1) ^ 1);
                    mbar_expect(bars + (FB_FULL + blk) * 8, 8192);
                    bulk_g2s(sb + F_X + blk * 8192, src + blk * 8192, 8192, bars + (FB_FULL + blk) * 8);
                }
            }
        } else if (hw == 1) {
            publisher(bars + FB_H * 8, bars + FB_RACK * 8, F_H);
        } else if (hw == 2 && blockIdx.x < NENG + 32) {
            const uint32_t ep = this_launch();
            int b1 = blockIdx.x < NENG + 16 ? 0 : LAG, b2 = b1;
            const int bend = b1 + NSEG;
#pragma unroll 1
            for (int j = 0; j < 2 * NSEG; j++) {
                [[maybe_unused]] int n = 0;
                bool second, any;
                const bool may1 = b1 < bend && b1 < b2 + RING;
                do {
                    const bool r1 = flag_up(F_P1, b1, 15 * ep);
                    second = flag_up(F_P2, b2, 17 * ep);
                    any = (r1 & may1) | second;
                    if (!any) __nanosleep(20);
                    SPIN_CHECK(n, 20);
                } while (!any);
                fence_acq_gpu();
                TG(second ? b2 : b1, 25 + 2 * second);
                if (j) mbar_wait(bars + FB_RDONE * 8, (j & 1) ^ 1);
                sts32(sb + F_RED + 64 + (j & 1) * 4, second ? b2 + 256 : b1);
                mbar_arrive(bars + FB_JOB * 8);
                if (second) b2++; else b1++;
            }
        }
    }
    __syncwarp();
}

__device__ __forceinline__ void add8(float* f, uint4 a) {
    f[0] += bf_lo(a.x); f[1] += bf_hi(a.x); f[2] += bf_lo(a.y); f[3] += bf_hi(a.y);
    f[4] += bf_lo(a.z); f[5] += bf_hi(a.z); f[6] += bf_lo(a.w); f[7] += bf_hi(a.w);
}
__device__ __forceinline__ void set8(float* f, uint4 a) {
    f[0] = bf_lo(a.x); f[1] = bf_hi(a.x); f[2] = bf_lo(a.y); f[3] = bf_hi(a.y);
    f[4] = bf_lo(a.z); f[5] = bf_hi(a.z); f[6] = bf_lo(a.w); f[7] = bf_hi(a.w);
}
__device__ __forceinline__ void ln0_rows(const Params& P, int r) {
    const int lane = threadIdx.x & 31, l = lane < 24 ? lane : 0;
    const uint4* xrow = (const uint4*)(P.x + r * DM) + l;
    uint4 xw[2][3];
#pragma unroll
    for (int k = 0; k < 6; k++) xw[k / 3][k % 3] = __ldg(xrow + (k / 3) * (16 * DM / 8) + 24 * (k % 3));
#pragma unroll 1
    for (int seg = 0; seg < NSEG; seg++) {
#pragma unroll
        for (int h = 0; h < 2; h++) {
            float f[24];
#pragma unroll
            for (int k = 0; k < 3; k++) set8(&f[k * 8], xw[h][k]);
            if (seg + 1 < NSEG) {
#pragma unroll
                for (int k = 0; k < 3; k++) xw[h][k] = __ldg(xrow + (2 * seg + 2 + h) * (16 * DM / 8) + 24 * k);
            }
            float s = 0.f, q = 0.f;
#pragma unroll
            for (int j = 0; j < 24; j++) s += f[j];
            if (lane >= 24) s = 0.f;
#pragma unroll
            for (int o = 16; o; o >>= 1) s += __shfl_xor_sync(~0u, s, o);
            const float mean = s * (1.f / DM);
#pragma unroll
            for (int j = 0; j < 24; j++) { f[j] -= mean; q += f[j] * f[j]; }
            if (lane >= 24) q = 0.f;
#pragma unroll
            for (int o = 16; o; o >>= 1) q += __shfl_xor_sync(~0u, q, o);
            const float rstd = rsqrtf(q * (1.f / DM) + 1e-5f);
            if (lane < 24) {
                uint8_t* d = g_x0 + seg * XIMG + (l >> 3) * 4096 + (r + 16 * h) * 128 + (((l & 7) ^ (r & 7)) << 4);
#pragma unroll
                for (int k = 0; k < 3; k++) {
                    const float* y = &f[8 * k];
                    stg128(d + k * 12288, make_uint4(pack2(y[0] * rstd, y[1] * rstd), pack2(y[2] * rstd, y[3] * rstd), pack2(y[4] * rstd, y[5] * rstd), pack2(y[6] * rstd, y[7] * rstd)));
                }
            }
        }
        __syncwarp();
        if (lane == 0) publish(F_X0, seg);
        __syncwarp();
    }
}

template <bool SECOND, bool CHAIN>
__device__ __forceinline__ void reduce_job(const Params& P, int b) {
    constexpr int NP = SECOND ? NP2 : NP1;
    const int tid = fresh_tid() & 127, lane = tid & 31, p = fresh_bid() - NENG, seg = CHAIN ? b - LAG : b;
    const bool act = lane < 24;
    const int i = (tid >> 5) * 24 + (act ? lane : 0);
    const uint32_t ro = (b & (RING - 1)), po = p * (DM * 4) + i * 32;
    const int fa = (i >> 1) * 16 + (i & 1) * 4;
    const uint32_t row = (seg * 32 + (p & 15) * 2) * DM + fa;
    uint8_t* const r1 = g_r1 + ro * PART + po;
    uint8_t* const r2 = g_r2 + seg * (PART / 2) + po - (CHAIN ? PART / 2 : 0);
    float f[16];
    uint4 x0, x1;
    {
        const uint8_t* src = (SECOND ? g_p2 : g_p1) + ro * (NP * PART) + po;
        uint4 a[NP][2];
#pragma unroll
        for (int k = 0; k < NP; k++) { a[k][0] = ld_rlx128(src + k * PART); a[k][1] = ld_rlx128(src + k * PART + 16); }
        if (SECOND || CHAIN) {
            x0 = ld_rlx128(SECOND ? r1 : r2); x1 = ld_rlx128((SECOND ? r1 : r2) + 16);
        } else {
            const uint2 a0 = ld_rlx64(P.x + row), b0 = ld_rlx64(P.x + row + 8), a1 = ld_rlx64(P.x + row + DM), c1 = ld_rlx64(P.x + row + DM + 8);
            x0 = make_uint4(__byte_perm(a0.x, a1.x, 0x5410), __byte_perm(b0.x, c1.x, 0x5410), __byte_perm(a0.x, a1.x, 0x7632), __byte_perm(b0.x, c1.x, 0x7632));
            x1 = make_uint4(__byte_perm(a0.y, a1.y, 0x5410), __byte_perm(b0.y, c1.y, 0x5410), __byte_perm(a0.y, a1.y, 0x7632), __byte_perm(b0.y, c1.y, 0x7632));
        }
        set8(f, a[0][0]);
#pragma unroll
        for (int k = 1; k < NP; k++) add8(f, a[k][0]);
        set8(f + 8, a[0][1]);
#pragma unroll
        for (int k = 1; k < NP; k++) add8(f + 8, a[k][1]);
    }
    add8(f, x0); add8(f + 8, x1);
    x0 = make_uint4(pack2(f[0], f[1]), pack2(f[2], f[3]), pack2(f[4], f[5]), pack2(f[6], f[7]));
    x1 = make_uint4(pack2(f[8], f[9]), pack2(f[10], f[11]), pack2(f[12], f[13]), pack2(f[14], f[15]));
    if (SECOND && CHAIN) {
        if (act) {
            stg64(P.out + row, __byte_perm(x0.x, x0.z, 0x5410), __byte_perm(x1.x, x1.z, 0x5410));
            stg64(P.out + row + 8, __byte_perm(x0.y, x0.w, 0x5410), __byte_perm(x1.y, x1.w, 0x5410));
            stg64(P.out + row + DM, __byte_perm(x0.x, x0.z, 0x7632), __byte_perm(x1.x, x1.z, 0x7632));
            stg64(P.out + row + DM + 8, __byte_perm(x0.y, x0.w, 0x7632), __byte_perm(x1.y, x1.w, 0x7632));
        }
        return;
    }
    set8(f, x0); set8(f + 8, x1);
    float st[4] = {0.f, 0.f, 0.f, 0.f};
#pragma unroll
    for (int j = 0; j < 16; j++) { st[j & 1] += f[j]; st[2 + (j & 1)] += f[j] * f[j]; }
    {
        const bool u = lane & 1, v = lane & 2;
        st[0] = (u ? st[1] : st[0]) + __shfl_xor_sync(~0u, u ? st[0] : st[1], 1);
        st[2] = (u ? st[3] : st[2]) + __shfl_xor_sync(~0u, u ? st[2] : st[3], 1);
        st[0] = (v ? st[2] : st[0]) + __shfl_xor_sync(~0u, v ? st[0] : st[2], 2);
        st[0] += __shfl_xor_sync(~0u, st[0], 4);
        if (act && !(lane & 4)) sts32(sb + F_RED + 128 + (i >> 3) * 16 + (lane & 3) * 4, fu(st[0]));
    }
    if (act) { stg128(SECOND ? r2 : r1, x0); stg128((SECOND ? r2 : r1) + 16, x1); }
    nbar_sync(NB_R, 96);
#pragma unroll
    for (int k = 0; k < 9; k++) {
        const uint4 t = lds128(sb + F_RED + 128 + k * 16);
        if (k == 0) { st[0] = uf(t.x); st[1] = uf(t.y); st[2] = uf(t.z); st[3] = uf(t.w); }
        else { st[0] += uf(t.x); st[1] += uf(t.y); st[2] += uf(t.z); st[3] += uf(t.w); }
    }
    const float m0 = st[0] * (1.f / DM), m1 = st[1] * (1.f / DM);
    const float q0 = rsqrtf(fmaxf(st[2] * (1.f / DM) - m0 * m0, 0.f) + 1e-5f), q1 = rsqrtf(fmaxf(st[3] * (1.f / DM) - m1 * m1, 0.f) + 1e-5f);
    if (act) {
        uint8_t* d = (SECOND ? g_x1 + seg * XIMG + (fa >> 6) * 4096 : g_xf + ro * (9 * 8192) + (fa >> 6) * 8192) + p * 256 + (i & 1) * 8;
#pragma unroll
        for (int e = 0; e < 2; e++) {
            const float m = e ? m1 : m0, q = e ? q1 : q0;
#pragma unroll
            for (int h = 0; h < 2; h++) {
                const float* y = &f[2 * h + e];
                stg64(d + e * 128 + (((((fa >> 3) & 6) + h) ^ ((2 * p + e) & 7)) << 4), pack2((y[0] - m) * q, (y[4] - m) * q), pack2((y[8] - m) * q, (y[12] - m) * q));
            }
        }
    }
}
__device__ __forceinline__ void reducer(const Params& P) {
    const bool chain = blockIdx.x >= NENG + 16;
    if (warp_in_group() < 3) {
#pragma unroll 1
        for (int j = 0; j < 2 * NSEG; j++) {
            mbar_wait(bars + FB_JOB * 8, j & 1);
            const int job = lds32(sb + F_RED + 64 + (j & 1) * 4);
            if (job >= 256) { if (chain) reduce_job<true, true>(P, job - 256); else reduce_job<true, false>(P, job - 256); }
            else { if (chain) reduce_job<false, true>(P, job); else reduce_job<false, false>(P, job); }
            mbar_arrive_warp(bars + FB_RDONE * 8);
        }
    } else if (threadIdx.x == 352) {
        mbar_arrive(bars + FB_JOB * 8);
#pragma unroll 1
        for (int j = 0; j < 2 * NSEG; j++) {
            mbar_wait(bars + FB_RDONE * 8, j & 1);
            const int job = lds32(sb + F_RED + 64 + (j & 1) * 4);
            mbar_arrive(bars + FB_JOB * 8);
            TG(job & 255, 23 + (job >> 8));
            if (job < 256 || !chain) publish(job < 256 ? F_XF : F_X1, job & 255);
            TG(job & 255, 26 + 2 * (job >> 8));
        }
    }
    __syncwarp();
}

__host__ __device__ constexpr int d_rf(int u) { return u < 48 ? ((u & 3) < 2 ? (u >> 2) * 2 + (u & 1) : -1) : u == 48 ? 24 : -1; }
__host__ __device__ constexpr int d_ss(int u) { return u < 48 ? (u >> 2) * 2 + (u & 1) : u - 25; }
template <bool WIDE, int wg>
__device__ __forceinline__ void d_main() {
    constexpr int NR = WIDE ? 24 : NRD;
    uint32_t w[NR][4];
    {
        const uint32_t fa = sb + wg * (NRD * 2048) + unit_frag_addr(threadIdx.x);
        mbar_wait(bars + DB_WL * 8, 0);
#pragma unroll
        for (int u = 0; u < NR; u++) ldsm4t(w[u], fa + u * 2048);
        nbar_arrive(NB_W, 416);
        mbar_wait(bars + DB_WL * 8, 1);
    }
    const uint64_t da = mkdesc(wg * ((52 - NRD) * 2048), 1024, 1024, 1);
#pragma unroll 1
    for (int b = 0; b < NSTEP; b++) {
#pragma unroll
        for (int T = 0; T < (WIDE ? 3 : 1); T++) {
            float d[32];
            constexpr int NB = WIDE ? 4 : 13;
#pragma unroll
            for (int blk = 0; blk < NB; blk++) {
                const int c = blk;
                if (T == 0 || blk == 0) mbar_wait(bars + (DB_FULL + (c & 7)) * 8, WIDE || (c & 7) >= 5 ? b & 1 : c >> 3);
                if (T == 0 || blk == 0) wg_fence();
                const uint64_t db = mkdesc(D_B + (c & 7) * 8192, 8192, 1024, 1);
#pragma unroll
                for (int j = 0; j < 4; j++) {
                    const int u = T * 16 + blk * 4 + j;
                    if (d_rf(u) >= 0) wg_rs64<1>(d, w[d_rf(u) >= 0 ? d_rf(u) : 0], db + j * 128, blk + j > 0);
                    else wg_ss64<1>(d, da + d_ss(u) * 128, db + j * 128, blk + j > 0);
                }
                wg_commit();
                if (!WIDE && blk > 0) { wg_wait<1>(); mbar_arrive_warp(bars + (DB_EMPTY + ((c - 1) & 7)) * 8); }
            }
            const int tid = fresh_tid(), t = tid & 3, ds = fresh_bid() - NENG - NF1;
            const bool w2 = ds >= 15;
            const int tile = WIDE ? wg * 3 + T : (ds % 3) * 3 + wg;
            uint8_t* dst = (w2 ? g_p2 + ((b & (RING - 1)) * NP2 + (WIDE ? ds - 25 : (ds - 15) / 3)) * PART : g_p1 + ((b & (RING - 1)) * NP1 + ds / 3) * PART)
                         + (tile * 64 + ((tid >> 5) & 3) * 16 + ((tid & 31) >> 2) * 2) * 4 + (w2 ? 4 * t : t) * (DM * 4);
            const uint32_t js = w2 ? DM * 4 : DM * 16;
            wg_wait_acc<0, 32>(d);
            if (!WIDE) mbar_arrive_warp(bars + (DB_EMPTY + ((NB - 1) & 7)) * 8);
            else if (T == 2) {
#pragma unroll
                for (int blk = 0; blk < 4; blk++) mbar_arrive_warp(bars + (DB_EMPTY + blk) * 8);
            }
#pragma unroll
            for (int j = 0; j < 8; j++) stg64(dst + (j >> 2) * (DM * 64) + (j & 3) * js, pack2(d[4 * j], d[4 * j + 1]), pack2(d[4 * j + 2], d[4 * j + 3]));
        }
        mbar_wait(bars + (DB_P + 1) * 8, (b & 1) ^ 1);
        mbar_arrive_warp(bars + DB_P * 8);
    }
}
__device__ __forceinline__ void d_helper(const Params& P, int ds) {
    const int lane = threadIdx.x & 31, hw = warp_in_group();
    const bool w2 = ds >= 15, wide = ds >= 30;
    const int blk0 = wide ? 65 + (ds - 30) * 4 : ((w2 ? ds - 15 : ds) / 3) * 13, nb = wide ? 4 : 13;
    if (hw == 0) {
        const int nu = wide ? 48 : 52;
#pragma unroll 1
        for (int ph = 0; ph < 2; ph++) {
            if (ph) nbar_sync(NB_W, 416);
            if (lane == 0) mbar_expect(bars + DB_WL * 8, (wide ? 72 : ph ? 3 * (52 - NRD) : 3 * NRD) * 2048);
            __syncwarp();
#pragma unroll 1
            for (int x = lane; x < 3 * nu; x += 32) {
                const int wg = x / nu, u = x - wg * nu;
                if ((d_rf(u) < 0) == (ph != 0))
                    tma_unit(sb + (ph ? wg * (52 - NRD) + d_ss(u) : wg * NRD + d_rf(u)) * 2048, w2 ? &P.tmW2 : &P.tmWo,
                             blk0 * 4 + (wide ? u & 15 : u), wide ? wg * 3 + (u >> 4) : (ds % 3) * 3 + wg, bars + DB_WL * 8);
            }
        }
        __syncwarp();
        if (lane == 0) {
            const uint32_t target = (w2 ? NF1 : NENG) * this_launch();
#pragma unroll 1
            for (int b = 0; b < NSTEP; b++) {
                flag_wait(w2 ? F_H : F_O, b, target);
                TG(b, 29);
                const uint8_t* src = (w2 ? g_h + (b & (RING - 1)) * H_BYTES : g_o + (b & (RING - 1)) * O_BYTES) + blk0 * 8192;
#pragma unroll 1
                for (int blk = 0; blk < nb; blk++) {
                    const int c = blk;
                    mbar_wait(bars + (DB_EMPTY + (c & 7)) * 8, (wide || (c & 7) >= 5 ? b & 1 : c >> 3) ^ 1);
                    mbar_expect(bars + (DB_FULL + (c & 7)) * 8, 8192);
                    bulk_g2s(sb + D_B + (c & 7) * 8192, src + blk * 8192, 8192, bars + (DB_FULL + (c & 7)) * 8);
                }
            }
        }
    } else if (hw == 1 && lane == 0) {
        publisher(bars + DB_P * 8, bars + (DB_P + 1) * 8, w2 ? F_P2 : F_P1);
    }
    __syncwarp();
}

__device__ __forceinline__ void sign_off() { mbar_arrive_warp(sb + SM_DONE); }
__device__ __forceinline__ void sign_off_helper() {
    if (warp_in_group() < 3) { sign_off(); return; }
    uint32_t ok;
    const uint32_t t0 = timer_lo();
    do {
        asm volatile("{.reg .pred p; mbarrier.try_wait.parity.shared::cta.b64 p, [%1], 0, 0x100000; selp.u32 %0, 1, 0, p;}" : "=r"(ok) : "r"(sb + SM_DONE) : "memory");
    } while (!ok && timer_lo() - t0 < TIME_LIMIT);
    if (!ok || (sb & 0x3ffff) != SM_ORG) __trap();
    if (fresh_tid() == NTHREADS - 32) { g_epoch[fresh_bid()][0] = this_launch(); TG(79, 1); }
    __syncwarp();
}

__global__ void __cluster_dims__(2, 1, 1) __launch_bounds__(NTHREADS, 1) fused_kernel(const __grid_constant__ Params P) {
    const int wg = __shfl_sync(~0u, threadIdx.x >> 7, 0);
    const int bid = blockIdx.x;
    if (threadIdx.x >= NTHREADS - 32) sts32(sb + SM_ONES + (threadIdx.x & 31) * 4, 0x3f803f80u);
    if (threadIdx.x == 0) {
        TG(79, 0);
        mbar_init(sb + SM_DONE, 15);
        sts32(sb + SM_XRDY, 0);
        if (bid < NENG) {
            for (int i = 0; i < 11; i++) mbar_init(bars + (EB_FULL + i) * 8, 1);
            mbar_init(bars + EB_V0 * 8, 4);
            for (int i = 0; i < 3; i++) mbar_init(bars + (EB_EMPTY + i) * 8, 12);
            mbar_init(bars + EB_PRDY2 * 8, 1);
            mbar_init(bars + EB_WL * 8, 3); mbar_init(bars + EB_WO * 8, 1); mbar_init(bars + EB_STEP * 8, 8);
            mbar_init(bars + EB_VX * 8, 1); mbar_init(bars + EB_SM * 8, 1); mbar_init(bars + EB_SX * 8, 1); mbar_init(bars + EB_VM * 8, 5);
            mbar_init(bars + EB_QF * 8, 4); mbar_init(bars + EB_KF * 8, 8); mbar_init(bars + EB_MEM * 8, 5); mbar_init(bars + EB_MEM0 * 8, 8); mbar_init(bars + EB_PRDY * 8, 1);
            mbar_init(bars + EB_CONS * 8, 4); mbar_init(bars + EB_OST * 8, 4); mbar_init(bars + EB_OFREE * 8, 1);
        } else if (bid < NENG + NF1) {
            for (int i = 0; i < 9; i++) { mbar_init(bars + (FB_FULL + i) * 8, 1); mbar_init(bars + (FB_EMPTY + i) * 8, 8); }
            mbar_init(bars + FB_H * 8, 8); mbar_init(bars + FB_RACK * 8, 1); mbar_init(bars + FB_JOB * 8, 2); mbar_init(bars + FB_RDONE * 8, 3);
        } else {
            for (int i = 0; i < 8; i++) { mbar_init(bars + (DB_FULL + i) * 8, 1); mbar_init(bars + (DB_EMPTY + i) * 8, 12); }
            mbar_init(bars + DB_WL * 8, 1); mbar_init(bars + DB_P * 8, 12); mbar_init(bars + (DB_P + 1) * 8, 1);
        }
        asm volatile("fence.mbarrier_init.release.cluster;" ::: "memory");
    }
    __syncthreads();
    if (bid < NENG) {
        if (wg == 0) { reg_inc<REGQ>(); engine_main<0>(P); sign_off(); cluster_sync_all(); }
        else if (wg == 1) { reg_inc<REGK>(); engine_main<1>(P); sign_off(); cluster_sync_all(); }
        else if (wg == 2) { reg_inc<REGV>(); engine_main<2>(P); sign_off(); cluster_sync_all(); }
        else { reg_dec<24>(); engine_helper(P); sign_off_helper(); cluster_sync_all(); }
    } else if (bid < NENG + NF1) {
        if (wg < 2) {
            reg_inc<200>();
            if (wg == 0) f1_main<0>(P); else f1_main<1>(P);
            sign_off();
        } else if (wg == 2) {
            reg_dec<88>();
            if (bid >= NENG + 32) ln0_rows(P, (bid - NENG - 32) * 4 + ((threadIdx.x >> 5) & 3));
            else reducer(P);
            sign_off();
        } else {
            reg_dec<24>();
            f1_helper();
            sign_off_helper();
        }
    } else {
        const int ds = bid - NENG - NF1;
        if (wg < 3) {
            reg_inc<160>();
            if (ds < 30) { if (wg == 0) d_main<false, 0>(); else if (wg == 1) d_main<false, 1>(); else d_main<false, 2>(); }
            else { if (wg == 0) d_main<true, 0>(); else if (wg == 1) d_main<true, 1>(); else d_main<true, 2>(); }
            sign_off();
        } else {
            reg_dec<32>();
            d_helper(P, ds);
            sign_off_helper();
        }
    }
}

typedef CUresult (*EncodeFn)(CUtensorMap*, CUtensorMapDataType, cuuint32_t, void*, const cuuint64_t*, const cuuint64_t*,
                             const cuuint32_t*, const cuuint32_t*, CUtensorMapInterleave, CUtensorMapSwizzle,
                             CUtensorMapL2promotion, CUtensorMapFloatOOBfill);

void make_map(EncodeFn enc, CUtensorMap* m, const void* p, int rows, int cols) {
    cuuint64_t dims[2] = {(cuuint64_t)cols, (cuuint64_t)rows};
    cuuint64_t strides[1] = {(cuuint64_t)cols * 2};
    cuuint32_t box[2] = {64, 16};
    cuuint32_t es[2] = {1, 1};
    enc(m, CU_TENSOR_MAP_DATA_TYPE_BFLOAT16, 2, (void*)p, dims, strides, box, es, CU_TENSOR_MAP_INTERLEAVE_NONE,
        CU_TENSOR_MAP_SWIZZLE_128B, CU_TENSOR_MAP_L2_PROMOTION_L2_128B, CU_TENSOR_MAP_FLOAT_OOB_FILL_NONE);
}

}

extern "C" void kernel_launch(void* const* d_in, const int* in_sizes, int n_in, void* d_out, int out_size) {
    (void)in_sizes; (void)n_in; (void)out_size;
    static EncodeFn enc = nullptr;
    if (!enc) {
        void* fn = nullptr;
        cudaDriverEntryPointQueryResult qr;
        cudaGetDriverEntryPoint("cuTensorMapEncodeTiled", &fn, cudaEnableDefault, &qr);
        enc = (EncodeFn)fn;
        cudaFuncSetAttribute(fused_kernel, cudaFuncAttributeMaxDynamicSharedMemorySize, SM_TOTAL);
    }
    Params P;
    make_map(enc, &P.tmWq, d_in[2], DM, 4096);
    make_map(enc, &P.tmWk, d_in[3], DM, 4096);
    make_map(enc, &P.tmWv, d_in[4], DM, 4096);
    make_map(enc, &P.tmWo, d_in[5], 4096, DM);
    make_map(enc, &P.tmW2, d_in[10], FF, DM);
    P.x = (const bf16*)d_in[0];
    P.mem0 = (const bf16*)d_in[1];
    P.w1 = (const bf16*)d_in[8];
    P.w3 = (const bf16*)d_in[9];
    P.out = (bf16*)d_out;
    P.zero = 0;
    fused_kernel<<<NCTA, NTHREADS, SM_TOTAL>>>(P);
}
```

```cpp
#include <cuda_runtime.h>
#include <cuda_bf16.h>
#include <cuda.h>
#include <stdint.h>

typedef __nv_bfloat16 bf16;

namespace {

constexpr int DM = 576, FF = 4608, NSEG = 64;
constexpr int NENG = 64, NF1 = 36, ND = 32, NCTA = NENG + NF1 + ND;
constexpr int NTHREADS = 512;
#define LAG 8
#define RING 16
static_assert(RING > LAG, "ring too short");
constexpr int NSTEP = NSEG + LAG;

enum { F_X0 = 0, F_X1, F_O, F_P1, F_XF, F_H, F_P2, F_COUNT };
constexpr int B_ZERO = 95;
__device__ uint32_t g_flag[F_COUNT][96][8];
__device__ uint32_t g_epoch[NCTA][8];
constexpr int XIMG = 9 * 4096;
constexpr int O_BYTES = 65 * 8192;
constexpr int H_BYTES = 73 * 8192;
constexpr int PART = 32 * DM * 4;
constexpr int NP1 = 5, NP2 = 7;
__device__ __align__(1024) uint8_t g_x0[NSEG * XIMG];
__device__ __align__(1024) uint8_t g_x1[NSEG * XIMG];
__device__ __align__(1024) uint8_t g_xf[RING * 9 * 8192];
__device__ __align__(1024) uint8_t g_o[RING * O_BYTES];
__device__ __align__(1024) uint8_t g_h[RING * H_BYTES];
__device__ __align__(1024) uint8_t g_p1[RING * NP1 * PART];
__device__ __align__(1024) uint8_t g_p2[RING * NP2 * PART];
__device__ __align__(1024) uint8_t g_r1[RING * PART];
__device__ __align__(1024) uint8_t g_r2[NSEG * PART / 2];
#define AR_STR 4352
constexpr int AR_SLOT = 144 * AR_STR;
__device__ __align__(1024) uint8_t g_ar[4 * AR_SLOT];

struct Params {
    CUtensorMap tmWq, tmWk, tmWv, tmWo, tmW2;
    const bf16 *x, *mem0, *w1, *w3, *w2;
    bf16* out;
    uint32_t zero;
};

constexpr uint32_t SM_ORG = 1024;
extern __shared__ __align__(1024) uint8_t smem_raw[];
#define sb ((uint32_t)__cvta_generic_to_shared(smem_raw))
#define bars (sb + SM_BAR)
constexpr int SM_BAR = 231936;
constexpr int SM_TOTAL = SM_BAR + 512;
#define NRQ 25
#define NRK 25
#define NRV 25
#define REGQ 160
#define REGK 168
#define REGV 160
constexpr int E_WQ = 0;
constexpr int E_WK = E_WQ + (36 - NRQ) * 2048;
constexpr int E_WV = E_WK + (36 - NRK) * 2048;
constexpr int E_WO = E_WV + (36 - NRV) * 2048;
constexpr int E_MEM = E_WO + 36 * 2048;
constexpr int E_R0 = E_MEM + 18432;
constexpr int E_R1 = E_R0 + 8192, E_R2 = E_R1 + 8192;
constexpr int E_SX = E_R1;
constexpr int E_QT = E_R2 + 8192;
constexpr int E_KT = E_QT + 8192;
constexpr int E_VT = E_KT + 10240;
constexpr int E_VP = E_VT + 10240;
constexpr int E_VF = E_VP + 8192;
constexpr int E_QM = E_VF + 4096;
constexpr int E_SR = E_QM + 2048;
constexpr int E_SL = E_SR + 2560;
constexpr int E_END = E_SL + 2048;
constexpr int E_OM = E_MEM + 16384, OM_STR = E_QM - E_OM;
static_assert(E_END <= SM_BAR, "engine smem overflow");
static_assert(E_WO + (NRQ + NRK + NRV) * 2048 <= E_VF, "weight staging: the peer writes there without asking");
enum {
    EB_FULL = 0, EB_EMPTY = 11  , EB_PRDY2 = 14, EB_V0, EB_WL, EB_WO, EB_STEP, EB_VX, EB_SM, EB_SX, EB_VM, EB_QF, EB_KF, EB_CONS, EB_OST, EB_OFREE,
    EB_MEM, EB_PRDY, EB_MEM0
};
enum { NB_G = 1, NB_LEAD, NB_QK, NB_S, NB_OM, NB_W, NB_R, NB_T, NB_PV, NB_WO, NB_V, NB_KT, NB_S2, NB_VL };
constexpr int NB_VL2 = NB_LEAD;
constexpr int NRF = 35;
constexpr int F_W = 0;
constexpr int F_X = 2 * (72 - NRF) * 2048;
constexpr int F_RED = F_X + 9 * 8192;
static_assert(F_RED + 512 <= SM_BAR, "F1 smem overflow");
enum { FB_FULL = 0, FB_EMPTY = 9, FB_H = 18, FB_RACK, FB_JOB, FB_RDONE };
constexpr int NRD = 25;
constexpr int D_B = 3 * (52 - NRD) * 2048;
static_assert(D_B + 8 * 8192 <= SM_BAR, "D smem overflow");
enum { DB_FULL = 0, DB_EMPTY = 8, DB_WL = 16, DB_P };
constexpr int SM_DONE = SM_BAR + 248, SM_XRDY = SM_BAR + 376, SM_ONES = SM_BAR + 384;
constexpr uint32_t TIME_LIMIT = 2000000000u;

#define SPIN_CHECK(n, code)

#define TS(thr, step, k)
#define TX(thr, k)
#define TG(step, k)
#define PROF_INC(n, k)

__device__ __forceinline__ uint32_t mapa(uint32_t a, uint32_t r) {
    uint32_t o; asm("mapa.shared::cluster.u32 %0, %1, %2;" : "=r"(o) : "r"(a), "r"(r)); return o;
}
__device__ __forceinline__ void mbar_init(uint32_t b, uint32_t cnt) {
    asm volatile("mbarrier.init.shared::cta.b64 [%0], %1;" :: "r"(b), "r"(cnt) : "memory");
}
__device__ __forceinline__ void mbar_arrive(uint32_t b) {
    asm volatile("mbarrier.arrive.shared::cta.b64 _, [%0];" :: "r"(b) : "memory");
}
__device__ __forceinline__ void mbar_arrive_warp(uint32_t b) {
    asm volatile("{.reg .pred p; bar.warp.sync -1; elect.sync _|p, -1; @p mbarrier.arrive.shared::cta.b64 _, [%0];}" :: "r"(b) : "memory");
}
__device__ __forceinline__ void mbar_arrive_remote(uint32_t b) {
    asm volatile("fence.release.sync_restrict::shared::cta.cluster; mbarrier.arrive.relaxed.cluster.shared::cluster.b64 _, [%0];" :: "r"(b) : "memory");
}
__device__ __forceinline__ void mbar_expect(uint32_t b, uint32_t bytes) {
    asm volatile("mbarrier.arrive.expect_tx.shared::cta.b64 _, [%0], %1;" :: "r"(b), "r"(bytes) : "memory");
}
__device__ __forceinline__ uint32_t mbar_wait(uint32_t b, uint32_t par) {
    uint32_t ok; [[maybe_unused]] int n = 0;
    while (true) {
        asm volatile("{.reg .pred p; mbarrier.try_wait.parity.shared::cta.b64 p, [%1], %2; selp.u32 %0, 1, 0, p;}"
                     : "=r"(ok) : "r"(b), "r"(par) : "memory");
        if (ok) break;
        SPIN_CHECK(n, 1000 + ((b & 511) >> 3));
    }
    return ok;
}
__device__ __forceinline__ void mbar_wait_cl(uint32_t b, uint32_t par) {
    uint32_t ok; [[maybe_unused]] int n = 0;
    while (true) {
        asm volatile("{.reg .pred p; mbarrier.try_wait.parity.relaxed.cluster.shared::cta.b64 p, [%1], %2; selp.u32 %0, 1, 0, p;}"
                     : "=r"(ok) : "r"(b), "r"(par) : "memory");
        if (ok) break;
        SPIN_CHECK(n, 1000 + ((b & 511) >> 3));
    }
    asm volatile("fence.acquire.sync_restrict::shared::cluster.cluster;" ::: "memory");
}
__device__ __forceinline__ void nbar_sync(int id, int n) { asm volatile("bar.sync %0, %1;" :: "r"(id), "r"(n) : "memory"); }
__device__ __forceinline__ void nbar_arrive(int id, int n) { asm volatile("bar.arrive %0, %1;" :: "r"(id), "r"(n) : "memory"); }
__device__ __forceinline__ void cluster_sync_all() {
    asm volatile("barrier.cluster.arrive.release.aligned; barrier.cluster.wait.acquire.aligned;" ::: "memory");
}
__device__ __forceinline__ void fence_async_smem() { asm volatile("fence.proxy.async.shared::cta;" ::: "memory"); }
__device__ __forceinline__ void fence_async_glb() { asm volatile("fence.proxy.async.global;" ::: "memory"); }
__device__ __forceinline__ void fence_rel_gpu() { asm volatile("fence.release.gpu;" ::: "memory"); }
__device__ __forceinline__ void fence_acq_gpu() { asm volatile("fence.acquire.gpu;" ::: "memory"); }
__device__ __forceinline__ void fence_gpu() { asm volatile("fence.acq_rel.gpu;" ::: "memory"); }
__device__ __forceinline__ int fresh_tid() { int t; asm volatile("mov.u32 %0, %%tid.x;" : "=r"(t)); return t; }
__device__ __forceinline__ int fresh_bid() { int t; asm volatile("mov.u32 %0, %%ctaid.x;" : "=r"(t)); return t; }
__device__ __forceinline__ uint32_t pin(uint32_t v) { asm volatile("" : "+r"(v)); return v; }
__device__ __forceinline__ int warp_in_group() { return __shfl_sync(~0u, (fresh_tid() >> 5) & 3, 0); }
__device__ __forceinline__ int cta_rank() { int t; asm volatile("mov.u32 %0, %%cluster_ctarank;" : "=r"(t)); return t; }
__device__ __forceinline__ uint32_t timer_lo() { uint32_t t; asm volatile("mov.u32 %0, %%globaltimer_lo;" : "=r"(t)); return t; }
__device__ __forceinline__ uint32_t keep(uint32_t v) { return __shfl_xor_sync(~0u, v, 0); }
__device__ __forceinline__ void red_add_u32(uint32_t* p, uint32_t v) {
    asm volatile("red.relaxed.gpu.global.add.u32 [%0], %1;" :: "l"(p), "r"(v) : "memory");
}
__device__ __forceinline__ uint32_t ld_rlx(const void* p) {
    uint32_t v; asm volatile("ld.relaxed.gpu.global.u32 %0, [%1];" : "=r"(v) : "l"(p) : "memory"); return v;
}
__device__ __forceinline__ uint2 ld_rlx64(const void* p) {
    uint2 v; asm volatile("ld.relaxed.gpu.global.v2.u32 {%0,%1}, [%2];" : "=r"(v.x), "=r"(v.y) : "l"(p) : "memory"); return v;
}
__device__ __forceinline__ uint4 ld_rlx128(const void* p) {
    uint4 v;
    asm volatile("ld.relaxed.gpu.global.v4.u32 {%0,%1,%2,%3}, [%4];" : "=r"(v.x), "=r"(v.y), "=r"(v.z), "=r"(v.w) : "l"(p) : "memory");
    return v;
}
__device__ __forceinline__ void stg128(void* p, uint4 v) {
    asm volatile("st.global.v4.b32 [%0], {%1,%2,%3,%4};" :: "l"(p), "r"(v.x), "r"(v.y), "r"(v.z), "r"(v.w) : "memory");
}
__device__ __forceinline__ void stg64(void* p, uint32_t a, uint32_t b) {
    asm volatile("st.global.v2.b32 [%0], {%1,%2};" :: "l"(p), "r"(a), "r"(b) : "memory");
}
__device__ __forceinline__ void st_async128(uint32_t a, uint32_t x, uint32_t y, uint32_t z, uint32_t w, uint32_t mb) {
    asm volatile("st.async.shared::cluster.mbarrier::complete_tx::bytes.v4.b32 [%0], {%1,%2,%3,%4}, [%5];"
                 :: "r"(a), "r"(x), "r"(y), "r"(z), "r"(w), "r"(mb) : "memory");
}
__device__ __forceinline__ void st_async64(uint32_t a, uint32_t x, uint32_t y, uint32_t mb) {
    asm volatile("st.async.shared::cluster.mbarrier::complete_tx::bytes.v2.b32 [%0], {%1,%2}, [%3];"
                 :: "r"(a), "r"(x), "r"(y), "r"(mb) : "memory");
}
__device__ __forceinline__ void sts128(uint32_t a, uint32_t x, uint32_t y, uint32_t z, uint32_t w) {
    asm volatile("st.shared.v4.b32 [%0], {%1,%2,%3,%4};" :: "r"(a), "r"(x), "r"(y), "r"(z), "r"(w) : "memory");
}
__device__ __forceinline__ void sts32(uint32_t a, uint32_t v) { asm volatile("st.shared.b32 [%0], %1;" :: "r"(a), "r"(v) : "memory"); }
__device__ __forceinline__ uint4 lds128(uint32_t a) {
    uint4 v; asm volatile("ld.shared.v4.b32 {%0,%1,%2,%3}, [%4];" : "=r"(v.x), "=r"(v.y), "=r"(v.z), "=r"(v.w) : "r"(a) : "memory"); return v;
}
__device__ __forceinline__ uint2 lds64(uint32_t a) {
    uint2 v; asm volatile("ld.shared.v2.b32 {%0,%1}, [%2];" : "=r"(v.x), "=r"(v.y) : "r"(a) : "memory"); return v;
}
__device__ __forceinline__ uint32_t lds32(uint32_t a) {
    uint32_t v; asm volatile("ld.shared.b32 %0, [%1];" : "=r"(v) : "r"(a) : "memory"); return v;
}
__device__ __forceinline__ void bulk_g2s(uint32_t dst, const void* src, uint32_t bytes, uint32_t mb) {
    asm volatile("cp.async.bulk.shared::cluster.global.mbarrier::complete_tx::bytes [%0], [%1], %2, [%3];"
                 :: "r"(dst), "l"(src), "r"(bytes), "r"(mb) : "memory");
}
__device__ __forceinline__ void bulk_s2g(void* dst, uint32_t src, uint32_t bytes) {
    asm volatile("cp.async.bulk.global.shared::cta.bulk_group [%0], [%1], %2;" :: "l"(dst), "r"(src), "r"(bytes) : "memory");
}
__device__ __forceinline__ void bulk_s2peer(uint32_t dst, uint32_t src, uint32_t bytes, uint32_t mb) {
    asm volatile("cp.async.bulk.shared::cluster.shared::cta.mbarrier::complete_tx::bytes [%0], [%1], %2, [%3];"
                 :: "r"(dst), "r"(src), "r"(bytes), "r"(mb) : "memory");
}
__device__ __forceinline__ void tma_unit(uint32_t dst, const CUtensorMap* tm, int kstep, int mgroup, uint32_t mb) {
    asm volatile("cp.async.bulk.tensor.2d.shared::cluster.global.mbarrier::complete_tx::bytes [%0], [%1, {%2,%3}], [%4];"
                 :: "r"(dst), "l"(tm), "r"(mgroup * 64), "r"(kstep * 16), "r"(mb) : "memory");
}
__device__ __forceinline__ void ldsm4(uint32_t* r, uint32_t a) {
    asm volatile("ldmatrix.sync.aligned.m8n8.x4.shared.b16 {%0,%1,%2,%3}, [%4];"
                 : "=r"(r[0]), "=r"(r[1]), "=r"(r[2]), "=r"(r[3]) : "r"(a) : "memory");
}
__device__ __forceinline__ void ldsm4t(uint32_t* r, uint32_t a) {
    asm volatile("ldmatrix.sync.aligned.m8n8.x4.trans.shared.b16 {%0,%1,%2,%3}, [%4];"
                 : "=r"(r[0]), "=r"(r[1]), "=r"(r[2]), "=r"(r[3]) : "r"(a) : "memory");
}
__device__ __forceinline__ void stsm4(uint32_t a, uint32_t r0, uint32_t r1, uint32_t r2, uint32_t r3) {
    asm volatile("stmatrix.sync.aligned.m8n8.x4.shared.b16 [%0], {%1,%2,%3,%4};" :: "r"(a), "r"(r0), "r"(r1), "r"(r2), "r"(r3) : "memory");
}
__device__ __forceinline__ void stsm4t(uint32_t a, uint32_t r0, uint32_t r1, uint32_t r2, uint32_t r3) {
    asm volatile("stmatrix.sync.aligned.m8n8.x4.trans.shared.b16 [%0], {%1,%2,%3,%4};" :: "r"(a), "r"(r0), "r"(r1), "r"(r2), "r"(r3) : "memory");
}
__device__ __forceinline__ uint32_t pack2(float lo, float hi) {
    uint32_t d; asm("cvt.rn.bf16x2.f32 %0, %1, %2;" : "=r"(d) : "f"(hi), "f"(lo)); return d;
}
__device__ __forceinline__ float bf_lo(uint32_t w) { return __uint_as_float(w << 16); }
__device__ __forceinline__ float bf_hi(uint32_t w) { return __uint_as_float(w & 0xffff0000u); }
__device__ __forceinline__ float ex2(float x) { float y; asm("ex2.approx.ftz.f32 %0, %1;" : "=f"(y) : "f"(x)); return y; }
__device__ __forceinline__ float rcp(float x) { float y; asm("rcp.approx.ftz.f32 %0, %1;" : "=f"(y) : "f"(x)); return y; }
__device__ __forceinline__ uint32_t fu(float x) { return __float_as_uint(x); }
__device__ __forceinline__ float uf(uint32_t x) { return __uint_as_float(x); }
__device__ __forceinline__ void mma16816(float* d, const uint32_t* a, uint32_t b0, uint32_t b1) {
    asm volatile("mma.sync.aligned.m16n8k16.row.col.f32.bf16.bf16.f32 {%0,%1,%2,%3}, {%4,%5,%6,%7}, {%8,%9}, {%0,%1,%2,%3};"
                 : "+f"(d[0]), "+f"(d[1]), "+f"(d[2]), "+f"(d[3]) : "r"(a[0]), "r"(a[1]), "r"(a[2]), "r"(a[3]), "r"(b0), "r"(b1));
}
__device__ __forceinline__ void mma1688(float* d, uint32_t a0, uint32_t a1, uint32_t b0) {
    asm volatile("mma.sync.aligned.m16n8k8.row.col.f32.bf16.bf16.f32 {%0,%1,%2,%3}, {%4,%5}, {%6}, {%0,%1,%2,%3};"
                 : "+f"(d[0]), "+f"(d[1]), "+f"(d[2]), "+f"(d[3]) : "r"(a0), "r"(a1), "r"(b0));
}
template <int N> __device__ __forceinline__ void reg_inc() { asm volatile("setmaxnreg.inc.sync.aligned.u32 %0;" :: "n"(N)); }
template <int N> __device__ __forceinline__ void reg_dec() { asm volatile("setmaxnreg.dec.sync.aligned.u32 %0;" :: "n"(N)); }

__device__ __forceinline__ uint64_t mkdesc(uint32_t addr, uint32_t lbo, uint32_t sbo, uint32_t swz) {
    return (uint64_t)((addr + SM_ORG) >> 4) | ((uint64_t)(lbo >> 4) << 16) | ((uint64_t)(sbo >> 4) << 32) | ((uint64_t)swz << 62);
}
__device__ __forceinline__ void wg_fence() { asm volatile("wgmma.fence.sync.aligned;" ::: "memory"); }
__device__ __forceinline__ void wg_commit() { asm volatile("wgmma.commit_group.sync.aligned;" ::: "memory"); }
template <int N> __device__ __forceinline__ void wg_wait() { asm volatile("wgmma.wait_group.sync.aligned %0;" :: "n"(N) : "memory"); }
template <int M> __device__ __forceinline__ void acc_ready(float* d) {
#pragma unroll
    for (int j = 0; j < M; j++) asm volatile("" : "+f"(d[j]) :: "memory");
}
template <int N, int M> __device__ __forceinline__ void wg_wait_acc(float* d) { wg_wait<N>(); acc_ready<M>(d); }

#define F8(c, d, o) c(d[o]), c(d[o + 1]), c(d[o + 2]), c(d[o + 3]), c(d[o + 4]), c(d[o + 5]), c(d[o + 6]), c(d[o + 7])
#define R8L "%0,%1,%2,%3,%4,%5,%6,%7"
#define R16L R8L ",%8,%9,%10,%11,%12,%13,%14,%15"
#define R32L R16L ",%16,%17,%18,%19,%20,%21,%22,%23,%24,%25,%26,%27,%28,%29,%30,%31"
#define R40L R32L ",%32,%33,%34,%35,%36,%37,%38,%39"
#define WG_BOTH(TXT_PRE, TXT_POST, OUTS, ...)                                                   \
    if (acc) asm volatile(TXT_PRE "1" TXT_POST : OUTS("+f") : __VA_ARGS__);                     \
    else asm volatile(TXT_PRE "0" TXT_POST : OUTS("=f") : __VA_ARGS__)
#define O8(c) F8(c, d, 0)
#define O16(c) F8(c, d, 0), F8(c, d, 8)
#define O32(c) O16(c), F8(c, d, 16), F8(c, d, 24)
#define O40(c) O32(c), F8(c, d, 32)
#define WGM(n) "wgmma.mma_async.sync.aligned.m64n" #n "k16.f32.bf16.bf16 "
__device__ __forceinline__ void wg_rs16(float* d, const uint32_t* a, uint64_t db, bool acc) {
    WG_BOTH(WGM(16) "{" R8L "}, {%8,%9,%10,%11}, %12, ", ", 1, 1, 1;", O8, "r"(a[0]), "r"(a[1]), "r"(a[2]), "r"(a[3]), "l"(db));
}
__device__ __forceinline__ void wg_ss16(float* d, uint64_t da, uint64_t db, bool acc) {
    WG_BOTH(WGM(16) "{" R8L "}, %8, %9, ", ", 1, 1, 1, 1;", O8, "l"(da), "l"(db));
}
__device__ __forceinline__ void wg_rs8(float* d, const uint32_t* a, uint64_t db, bool acc) {
#define O4(c) c(d[0]), c(d[1]), c(d[2]), c(d[3])
    WG_BOTH(WGM(8) "{%0,%1,%2,%3}, {%4,%5,%6,%7}, %8, ", ", 1, 1, 0;", O4, "r"(a[0]), "r"(a[1]), "r"(a[2]), "r"(a[3]), "l"(db));
}
__device__ __forceinline__ void wg_rs32(float* d, const uint32_t* a, uint64_t db, bool acc) {
    WG_BOTH(WGM(32) "{" R16L "}, {%16,%17,%18,%19}, %20, ", ", 1, 1, 0;", O16, "r"(a[0]), "r"(a[1]), "r"(a[2]), "r"(a[3]), "l"(db));
}
template <int TB> __device__ __forceinline__ void wg_rs64(float* d, const uint32_t* a, uint64_t db, bool acc) {
    WG_BOTH(WGM(64) "{" R32L "}, {%32,%33,%34,%35}, %36, ", ", 1, 1, %37;", O32, "r"(a[0]), "r"(a[1]), "r"(a[2]), "r"(a[3]), "l"(db), "n"(TB));
}
template <int TB> __device__ __forceinline__ void wg_ss64(float* d, uint64_t da, uint64_t db, bool acc) {
    WG_BOTH(WGM(64) "{" R32L "}, %32, %33, ", ", 1, 1, 1, %34;", O32, "l"(da), "l"(db), "n"(TB));
}
__device__ __forceinline__ void wg_ss80(float* d, uint64_t da, uint64_t db, bool acc) {
    WG_BOTH(WGM(80) "{" R40L "}, %40, %41, ", ", 1, 1, 1, 1;", O40, "l"(da), "l"(db));
}

constexpr float SM_SCALE = 0.08838834764831845f;
constexpr float LOG2E = 1.4426950408889634f;

#define WO_DELAY 3000
#define D_DELAY 7000
#define F1_DELAY 7000
#define W2_DELAY 16500
#define F1_DEPTH 30
#define PF_DELAY 6000
#define PF_PACE 400
__device__ __forceinline__ void hold_back(uint32_t ns) {
    const uint32_t t0 = timer_lo();
    while (timer_lo() - t0 < ns) __nanosleep(50);
}

__device__ __forceinline__ uint32_t* flag_ptr(int stage, int b) { return &g_flag[stage][b][0]; }
__device__ __forceinline__ uint32_t this_launch() { return ld_rlx(&g_epoch[fresh_bid()][0]) + 1; }
__device__ __forceinline__ bool flag_up(int stage, int b, uint32_t target) { return (int)(ld_rlx(flag_ptr(stage, b)) - target) >= 0; }
__device__ __forceinline__ void flag_wait(int stage, int b, uint32_t target) {
    [[maybe_unused]] int n = 0;
    while (!flag_up(stage, b, target)) {
        __nanosleep(20);
        SPIN_CHECK(n, 10 + stage);
    }
    fence_acq_gpu();
    fence_async_glb();
}
__device__ __forceinline__ void publish(int stage, int b) {
    fence_async_glb();
    fence_rel_gpu();
    red_add_u32(flag_ptr(stage, b), 1);
}
__device__ __forceinline__ uint32_t unit_frag_addr(int tid) {
    const int lane = tid & 31, w = (tid >> 5) & 3, i = lane & 7, j = lane >> 3;
    return ((j >> 1) * 8 + i) * 128 + ((((w << 1) + (j & 1)) ^ i) << 4);
}

#define V_BURST1 2
#define V_BURST2 1
#define V_PRE 8
#define SX_BF16 0
#define WO_MODE 0
#define V_LEAD 9
static_assert(V_BURST1 + V_BURST2 >= 2 && V_LEAD > V_BURST1 + V_BURST2, "q and k rely on v for the arrival of the blocks");
#define K_LEAD 0
#define Q_LEAD 36
#define V_FIRST 12
#define SX_GATE 1
#define PVX_LATE 1
#define V_EARLY 0
#define VM_EARLY 0
__host__ __device__ constexpr int x_order(int mat, int j) {
    return mat == 2 ? j : j < 2 ? j + 2 : j == 2 ? 8 : j == 3 ? 6 : j < 6 ? j : j == 6 ? 7 : 8 - j;
}
#define SS0Q 0
#define SS0K 0
#define SS0V 22
#define SSLQ 36
#define SSLK 36
#define SSLV 14
__host__ __device__ constexpr uint64_t ss_mask(int mat) {
    const int ns = 36 - (mat == 0 ? NRQ : mat == 1 ? NRK : NRV);
    const int j0 = mat == 0 ? SS0Q : mat == 1 ? SS0K : SS0V, len = mat == 0 ? SSLQ : mat == 1 ? SSLK : SSLV;
    uint64_t m = 0;
    for (int j = j0; j < j0 + len; j++)
        if ((j - j0) * ns / len != (j - j0 + 1) * ns / len) m |= 1ull << (x_order(mat, j >> 2) * 4 + (j & 3));
    return m;
}
__device__ __forceinline__ int popc_below(uint64_t m, int k) { return __popcll(m & ((1ull << k) - 1)); }
__host__ __device__ constexpr int x_slot(int f) {
    return f == 0 || f == 6 || f == 9 ? E_R0 : f == 1 || f == 7 ? E_R2 : f < 4 ? E_MEM + (f - 2) * 8192 : f == 4 ? E_QT : f == 5 ? E_KT : f == 8 ? E_VP : E_R1;
}
__host__ __device__ constexpr int x_empty(int blk) { return blk == 3 ? 0 : blk == 6 ? 1 : blk == 5 ? 2 : -1; }
__host__ __device__ constexpr int ar_tile(int j) { return WO_MODE == 2 ? (j == 8 ? 8 : (j & 1) * 4 + (j >> 1)) : j == 0 ? 8 : ((j - 1) & 1) * 4 + ((j - 1) & 2) + (j > 4); }
__host__ __device__ constexpr int sx_off(int u) { return u == 0 ? 0 : u == 1 ? 1536 : u == 2 ? 2560 : u == 3 ? 3072 : 5120; }

template <int MAT, int NR, int K0, int K1>
__device__ __forceinline__ void proj_mem(float* d, const uint32_t (&w)[NR][4]) {
    constexpr uint64_t M = ss_mask(MAT);
    const uint64_t db = mkdesc(E_MEM, 128, 9216, 0);
    const uint64_t da = mkdesc((MAT == 0 ? E_WQ : MAT == 1 ? E_WK : E_WV), 1024, 1024, 1);
#pragma unroll
    for (int ks = K0; ks < K1; ks++) {
        const int s = popc_below(M, ks);
        if ((M >> ks) & 1) wg_ss16(d, da + s * 128, db + ks * 16, ks > 0);
        else wg_rs16(d, w[ks - s], db + ks * 16, ks > 0);
    }
}
__device__ __forceinline__ uint32_t tl_lane(int tid, int group_bytes) {
    return ((tid >> 4) & 1) * group_bytes + (((tid >> 5) & 3) * 16 + (tid & 15)) * 16;
}
struct ArWords {
    uint32_t w[5];
    __device__ __forceinline__ ArWords(const float* y) {
        w[0] = pack2(y[0], y[1]); w[1] = pack2(y[2], y[3]); w[2] = pack2(y[4], y[5]); w[3] = pack2(y[6], 1.f); w[4] = pack2(y[7], 1.f);
    }
    __device__ __forceinline__ void force(uint32_t zero) {
        asm volatile("{.reg .pred p; setp.ne.u32 p, %0, 0; @p st.shared.v4.b32 [%5], {%1,%2,%3,%4};}" :: "r"(zero), "r"(w[0]), "r"(w[1]), "r"(w[2]), "r"(w[3]), "r"(w[4]) : "memory");
    }
    __device__ __forceinline__ void red(uint8_t* p, uint8_t* q) {
        asm volatile("red.relaxed.gpu.global.add.noftz.v4.bf16x2 [%0], {%1,%2,%3,%4};" :: "l"(p), "r"(w[0]), "r"(w[1]), "r"(w[2]), "r"(w[3]) : "memory");
        asm volatile("red.relaxed.gpu.global.add.noftz.bf16x2 [%0], %1;" :: "l"(q), "r"(w[4]) : "memory");
    }
};
__device__ __forceinline__ uint32_t ar_main(int tid) { return ((tid & 127) >> 3) * AR_STR + (tid & 7) * 16; }
__device__ __forceinline__ uint32_t ar_side(int tid) { return ((tid & 127) >> 5) * (4 * AR_STR) + AR_STR / 2 + (tid & 31) * 4; }

#define AR_LDQ 2
#define AR_LDK 2
#define AR_STQ 6
#define AR_STK 5
#define AR_VWAIT 1
#define AR_J1 3
#define AR_J2 5
template <int MAT> struct ArPart {
    static constexpr int J0 = MAT == 0 ? 0 : MAT == 1 ? AR_J1 : AR_J2, J1 = MAT == 0 ? AR_J1 : MAT == 1 ? AR_J2 : 9;
    uint4 av[J1 - J0];
    uint32_t as[J1 - J0];
    __device__ __forceinline__ void load(int i, int tid) {
        const uint8_t* pm = g_ar + ((i & 3) * AR_SLOT + ar_main(tid));
        const uint8_t* ps = g_ar + ((i & 3) * AR_SLOT + ar_side(tid));
#pragma unroll
        for (int j = J0; j < J1; j++) { av[j - J0] = ld_rlx128(pm + ar_tile(j) * (16 * AR_STR)); as[j - J0] = ld_rlx(ps + ar_tile(j) * (16 * AR_STR)); }
    }
    __device__ __forceinline__ void first_load(int i, int tid) {
        const uint8_t* pm = g_ar + ((i & 3) * AR_SLOT + ar_main(tid));
        const uint8_t* ps = g_ar + ((i & 3) * AR_SLOT + ar_side(tid));
#pragma unroll
        for (int j = 0; j < J1 - J0; j++) {
            av[j] = make_uint4(0, 0, 0, 0); as[j] = 0;
            asm volatile("{.reg .pred p; setp.ge.s32 p, %7, 0; @p ld.relaxed.gpu.global.v4.u32 {%0,%1,%2,%3}, [%5]; @p ld.relaxed.gpu.global.u32 %4, [%6];}"
                         : "+r"(av[j].x), "+r"(av[j].y), "+r"(av[j].z), "+r"(av[j].w), "+r"(as[j])
                         : "l"(pm + ar_tile(J0 + j) * (16 * AR_STR)), "l"(ps + ar_tile(J0 + j) * (16 * AR_STR)), "r"(i) : "memory");
        }
    }
    __device__ __forceinline__ bool complete(uint32_t one = 1) {
        bool ok = true;
#pragma unroll
        for (int j = J0; j < J1; j++) {
            ok &= __byte_perm(av[j - J0].w, as[j - J0], 0x7631 + one) == (ar_tile(j) == 8 ? 0x42804280u : 0x42004200u);
            av[j - J0].w = __byte_perm(av[j - J0].w, as[j - J0], 0x540f + one);
        }
        return __all_sync(~0u, ok);
    }
    __device__ __forceinline__ void store(const Params& P, int i, int tid) {
        [[maybe_unused]] int n = 0;
        const uint32_t one = MAT != 2 || !AR_VWAIT ? mbar_wait(bars + EB_EMPTY * 8, (i & 1) ^ 1) : 1;
        if (__builtin_expect(!complete(one) || i + 1 == LAG, 0)) {
            if (i >= 0) do { load(i, pin(tid << P.zero)); SPIN_CHECK(n, 2); PROF_INC(n, 1); } while (!complete());
            if (i < 0 || i + 1 == LAG) {
                const uint16_t* m = (const uint16_t*)P.mem0 + (tid & 3) * (2 * DM) + ((tid >> 5) & 3) * 16 + ((tid & 31) >> 2);
#pragma unroll
                for (int j = J0; j < J1; j++) {
                    const int f = ar_tile(j) * 64;
                    av[j - J0].z = (uint32_t)__ldg(m + f) | ((uint32_t)__ldg(m + f + DM) << 16);
                    av[j - J0].w = (uint32_t)__ldg(m + f + 8) | ((uint32_t)__ldg(m + f + DM + 8) << 16);
                    if (i < 0) { av[j - J0].x = av[j - J0].z; av[j - J0].y = av[j - J0].w; }
                }
            }
        }
        const uint32_t a = sb + E_MEM + tl_lane(tid, 9216);
#pragma unroll
        for (int j = J0; j < J1; j++) stsm4(a + ar_tile(j) * 1024, av[j - J0].x, av[j - J0].y, av[j - J0].z, av[j - J0].w);
    }
};

__device__ __forceinline__ void attn_mem(float* d, uint32_t par, int i, int tid) {
    const int lane = tid & 31, warp = tid >> 5, c = warp >> 1, hf = warp & 1;
    const int rank = cta_rank();
    const uint32_t peer = mapa(sb, rank ^ 1);
    const uint32_t l4 = (lane >> 4) * 1024 + (lane & 15) * 16;
    uint32_t kb[4][4];
    mbar_wait(bars + EB_WO * 8, 0);
    mbar_wait_cl(bars + EB_VX * 8, par);
    if (VM_EARLY) mbar_wait_cl(bars + EB_VM * 8, par);
    mbar_wait(bars + EB_STEP * 8, par);
    {
        const uint32_t aK = sb + E_KT + (c * 6 + hf * 2) * 1024 + l4;
#pragma unroll
        for (int ks = 0; ks < 4; ks++) ldsm4t(kb[ks], aK + ks * 256);
    }
    const uint32_t aQs = pin(sb + E_QM + tl_lane(tid, 1024));
    const uint32_t aQ = pin(sb + E_QM + c * 1024 + (((lane >> 3) & 1) * 16 + (lane >> 4) * 8 + (lane & 7)) * 16);
    const uint32_t aM = pin(sb + E_KT + (4 + c) * 1024 + lane * 16);
    const uint32_t oS = pin(tid * 16);
    const uint32_t aV = pin(sb + (hf == rank ? E_VT + c * 6144 : E_VP + c * 4096) + l4);
    wg_wait_acc<0, 8>(d);
    stsm4(aQs, pack2(d[0], d[1]), pack2(d[2], d[3]), pack2(d[4], d[5]), pack2(d[6], d[7]));
    nbar_sync(NB_QK, 256);
    TS(0, i, 1);
    float s[6];
    {
        uint32_t q[2][4], km[2][4];
        ldsm4t(q[0], aQ); ldsm4t(km[0], aM); ldsm4t(q[1], aQ + 512); ldsm4t(km[1], aM + 512);
        float a[6][4];
#pragma unroll
        for (int m = 0; m < 6; m++) a[m][0] = a[m][1] = a[m][2] = a[m][3] = 0.f;
#pragma unroll
        for (int j = 0; j < 2; j++) {
#pragma unroll
            for (int o = 0; o < 2; o++) {
                mma16816(a[o * 3], q[j], kb[2 * j + o][0], kb[2 * j + o][1]);
                mma16816(a[o * 3 + 1], q[j], kb[2 * j + o][2], kb[2 * j + o][3]);
            }
            mma16816(a[2], q[j], km[j][0], km[j][1]);
            mma16816(a[5], q[j], km[j][2], km[j][3]);
        }
        nbar_arrive(NB_S, 256);
        if (SX_GATE) nbar_arrive(NB_S2, 256);
#pragma unroll
        for (int m = 0; m < 3; m++) { s[2 * m] = a[m][0] + a[3 + m][2]; s[2 * m + 1] = a[m][1] + a[3 + m][3]; }
    }
    st_async128(peer + E_SR + oS, fu(s[0]), fu(s[1]), fu(s[2]), fu(s[3]), peer + SM_BAR + EB_SM * 8);
    const uint32_t oM = E_SR + 2048 + c * 256 + lane * 8;
    asm volatile("st.async.shared::cluster.mbarrier::complete_tx::bytes.b32 [%0], %1, [%2];"
                 :: "r"(peer + oM + hf * 4), "r"(fu(hf ? s[5] : s[4])), "r"(peer + SM_BAR + EB_SM * 8) : "memory");
    sts128(sb + E_SL + oS, fu(s[0]), fu(s[1]), fu(s[2]), fu(s[3]));
    mbar_arrive_warp(bars + EB_KF * 8);
    TS(0, i, 2);
#pragma unroll
    for (int T = 0; T < 4; T++) ldsm4(kb[T], aV + hf * 2048 + T * 256);
    nbar_sync(NB_G, 128);
    const uint32_t aO = sb + E_OM + c * OM_STR + (hf * 64 + lane) * 16;
    const uint32_t aR = sb + E_SR + oS, aR1 = sb + E_SR + (oS ^ 512), aRm = sb + oM, aV1 = aV + (hf ^ 1) * 2048;
    const uint4 l1 = lds128(aR1 + (E_SL - E_SR));
    mbar_wait_cl(bars + EB_SM * 8, par);
    TS(0, i, 3);
    float p[10];
    {
        const uint4 r0 = lds128(aR), r1 = lds128(aR1);
        const uint2 rm = lds64(aRm);
        p[0] = s[0] + uf(r0.x); p[1] = s[1] + uf(r0.y); p[2] = s[2] + uf(r0.z); p[3] = s[3] + uf(r0.w);
        p[4] = uf(l1.x) + uf(r1.x); p[5] = uf(l1.y) + uf(r1.y); p[6] = uf(l1.z) + uf(r1.z); p[7] = uf(l1.w) + uf(r1.w);
        p[8] = s[4] + uf(rm.x); p[9] = s[5] + uf(rm.y);
    }
    float mx = fmaxf(fmaxf(fmaxf(p[0], p[1]), fmaxf(p[2], p[3])), fmaxf(fmaxf(fmaxf(p[4], p[5]), fmaxf(p[6], p[7])), fmaxf(p[8], p[9])));
    mx = fmaxf(mx, __shfl_xor_sync(~0u, mx, 1));
    mx = fmaxf(mx, __shfl_xor_sync(~0u, mx, 2));
    const float mo = mx * (SM_SCALE * LOG2E);
    uint32_t pb[5];
    float o[5][4];
    const uint32_t ones[4] = {0x3f803f80u, 0x3f803f80u, 0x3f803f80u, 0x3f803f80u};
#pragma unroll
    for (int m = 0; m < 2; m++) pb[m] = pack2(ex2(fmaf(p[2 * m], SM_SCALE * LOG2E, -mo)), ex2(fmaf(p[2 * m + 1], SM_SCALE * LOG2E, -mo)));
#pragma unroll
    for (int T = 0; T < 5; T++) o[T][0] = o[T][1] = o[T][2] = o[T][3] = 0.f;
    mma16816(o[4], ones, pb[0], pb[1]);
#pragma unroll
    for (int T = 0; T < 4; T++) { mma16816(o[T], kb[T], pb[0], pb[1]); ldsm4(kb[T], aV1 + T * 256); }
#pragma unroll
    for (int m = 2; m < 5; m++) pb[m] = pack2(ex2(fmaf(p[2 * m], SM_SCALE * LOG2E, -mo)), ex2(fmaf(p[2 * m + 1], SM_SCALE * LOG2E, -mo)));
    if (!VM_EARLY) mbar_wait_cl(bars + EB_VM * 8, par);
    uint2 vm[4];
#pragma unroll
    for (int T = 0; T < 4; T++) vm[T] = lds64(sb + E_VF + hf * 2048 + lane * 16 + c * 8 + T * 512);
    mma16816(o[4], ones, pb[2], pb[3]);
#pragma unroll
    for (int T = 0; T < 4; T++) mma16816(o[T], kb[T], pb[2], pb[3]);
    mma1688(o[4], ones[0], ones[1], pb[4]);
#pragma unroll
    for (int T = 0; T < 4; T++) mma1688(o[T], vm[T].x, vm[T].y, pb[4]);
    nbar_arrive(NB_PV, 256);
    mbar_arrive_warp(bars + EB_CONS * 8);
    const float i0 = rcp(o[4][0]), i1 = rcp(o[4][1]);
#pragma unroll
    for (int j = 0; j < 2; j++)
        stsm4(aO + j * 512, pack2(o[2 * j][0] * i0, o[2 * j][1] * i1), pack2(o[2 * j][2] * i0, o[2 * j][3] * i1),
              pack2(o[2 * j + 1][0] * i0, o[2 * j + 1][1] * i1), pack2(o[2 * j + 1][2] * i0, o[2 * j + 1][3] * i1));
}

__device__ __forceinline__ void attn_x_scores(float (&p)[2][10], uint32_t par, int i, int tid) {
    {
        float s[40];
        const uint64_t da = mkdesc(E_QT, 128, 1024, 0), db = mkdesc(E_KT, 128, 1024, 0);
        wg_fence();
#pragma unroll
        for (int ks = 0; ks < 4; ks++) wg_ss80(s, da + ks * 16, db + ks * 16, ks > 0);
        wg_commit();
        const int dq = (tid >> 2) - 2 * (tid & 3);
        float mask[8];
#pragma unroll
        for (int j = 0; j < 8; j++) mask[j] = (j >> 1) * 8 + (j & 1) > dq ? -1e9f * LOG2E : 0.f;
        mbar_wait_cl(bars + EB_PRDY2 * 8, par);
        wg_wait_acc<0, 40>(s);
#pragma unroll
        for (int u = 0; u < 5; u++) {
            const int v = u < 4 ? 6 + u : 5;
            constexpr float C = SM_SCALE * LOG2E;
            const float m0 = u < 4 ? mask[2 * u & 7] : 0.f, m1 = u < 4 ? mask[(2 * u + 1) & 7] : 0.f;
            p[0][2 * u] = fmaf(s[4 * u], C, m0); p[0][2 * u + 1] = fmaf(s[4 * u + 1], C, m1); p[1][2 * u] = fmaf(s[4 * v + 2], C, m0); p[1][2 * u + 1] = fmaf(s[4 * v + 3], C, m1);
        }
    }
    mbar_arrive_warp(bars + EB_QF * 8);
    const int w = tid >> 5;
    if (!SX_BF16) {
        const uint32_t peer = mapa(sb, cta_rank() ^ 1);
#pragma unroll
        for (int u = 0; u < 5; u++)
            if (u == 0 || u <= w || u == 4) st_async128(peer + E_SX + sx_off(u) + tid * 16, fu(p[0][2 * u]), fu(p[0][2 * u + 1]), fu(p[1][2 * u]), fu(p[1][2 * u + 1]), peer + SM_BAR + EB_SX * 8);
    } else {
        const uint32_t peer = mapa(sb, cta_rank() ^ 1), a = peer + E_SX + tid * 16, mb = peer + SM_BAR + EB_SX * 8;
        st_async128(a, pack2(p[0][0], p[0][1]), pack2(p[1][0], p[1][1]), pack2(p[0][8], p[0][9]), pack2(p[1][8], p[1][9]), mb);
        if (w >= 1) st_async128(a + 2048, pack2(p[0][2], p[0][3]), pack2(p[1][2], p[1][3]), pack2(p[0][4], p[0][5]), pack2(p[1][4], p[1][5]), mb);
        if (w >= 3) st_async64(a + 4096, pack2(p[0][6], p[0][7]), pack2(p[1][6], p[1][7]), mb);
    }
    TS(128, i, 10);
}
__device__ __forceinline__ void attn_x_finish(float (&p)[2][10], uint32_t par, int i, int& tid, uint32_t zero) {
    const int w = tid >> 5;
    mbar_wait_cl(bars + EB_SX * 8, par);
    TS(128, i, 11);
    if (SX_BF16) {
        const uint32_t a = sb + E_SX + tid * 16;
        const uint4 r0 = lds128(a), r1 = lds128(a + (w >= 1 ? 2048 : 0));
        const uint2 r2 = lds64(a + (w >= 3 ? 4096 : 0));
        const uint32_t r[10] = {r0.x, r0.y, r1.x, r1.y, r1.z, r1.w, r2.x, r2.y, r0.z, r0.w};
#pragma unroll
        for (int j = 0; j < 10; j++) { p[j & 1][j & ~1] += bf_lo(r[j]); p[j & 1][j | 1] += bf_hi(r[j]); }
    } else
#pragma unroll
    for (int u = 0; u < 5; u++) {
        const uint4 r = lds128(pin(sb + tid * 16 + (u == 0 || u <= w ? sx_off(u) : sx_off(4))) + E_SX);
        p[0][2 * u] += uf(r.x); p[0][2 * u + 1] += uf(r.y); p[1][2 * u] += uf(r.z); p[1][2 * u + 1] += uf(r.w);
    }
    nbar_sync(NB_W, 128);
    uint32_t pa[5][4];
    float mx[2], inv[2];
#pragma unroll
    for (int h = 0; h < 2; h++) {
        const float* q = p[h];
        mx[h] = fmaxf(fmaxf(fmaxf(q[0], q[1]), fmaxf(q[2], q[3])), fmaxf(fmaxf(fmaxf(q[4], q[5]), fmaxf(q[6], q[7])), fmaxf(q[8], q[9])));
    }
#pragma unroll
    for (int o = 1; o < 4; o <<= 1) { mx[0] = fmaxf(mx[0], __shfl_xor_sync(~0u, mx[0], o)); mx[1] = fmaxf(mx[1], __shfl_xor_sync(~0u, mx[1], o)); }
#pragma unroll
    for (int h = 0; h < 2; h++) {
        float* q = p[h];
#pragma unroll
        for (int j = 0; j < 10; j++) q[j] = ex2(q[j] - mx[h]);
#pragma unroll
        for (int u = 0; u < 4; u++) {
            pa[h * 3 + (u >> 1)][(u & 1) * 2 + h] = pack2(q[2 * u], q[2 * u + 1]);
            pa[h * 3 + (u >> 1)][(u & 1) * 2 + (h ^ 1)] = zero << (h * 5 + u + 1);
        }
        pa[2][h * 3] = pack2(q[8], q[9]);
        pa[2][1 + h] = zero << (h * 5 + 5);
    }
    mbar_wait(bars + (PVX_LATE ? EB_CONS : EB_KF) * 8, par);
    fence_async_smem();
    tid = pin(tid << zero);
    const uint32_t aO = pin(sb + (((tid >> 4) & 1) * 8 + (tid & 7)) * 128 + (((((tid >> 3) & 1) * 4 + (tid >> 5)) ^ (tid & 7)) << 4)) + E_R1;
    TS(128, i, 12);
#pragma unroll
    for (int nh = 0; nh < 2; nh++) {
        float o[16], sum[4];
        const uint64_t db = mkdesc(E_VT + nh * 512, 1024, 128, 0);
        wg_fence();
#pragma unroll
        for (int kk = 0; kk < 5; kk++) {
            if (nh == 0) wg_rs8(sum, pa[kk], mkdesc(SM_ONES, 0, 0, 0), kk > 0);
            wg_rs32(o, pa[kk], db + kk * 128, kk > 0);
        }
        wg_commit();
        wg_wait_acc<0, 16>(o);
        if (nh == 0) { acc_ready<4>(sum); inv[0] = rcp(sum[0]); inv[1] = rcp(sum[2]); }
#pragma unroll
        for (int j = 0; j < 2; j++) {
            const float* y = &o[8 * j];
            stsm4t(aO + nh * 4096 + j * 2048, pack2(y[0] * inv[0], y[1] * inv[0]), pack2(y[2] * inv[1], y[3] * inv[1]), pack2(y[4] * inv[0], y[5] * inv[0]), pack2(y[6] * inv[1], y[7] * inv[1]));
        }
    }
    mbar_arrive_warp(bars + EB_OST * 8);
    TS(128, i, 13);
}

template <int MAT>
__device__ __forceinline__ void engine_main(const Params& P) {
    constexpr int NR = MAT == 0 ? NRQ : MAT == 1 ? NRK : NRV;
    constexpr uint64_t M = ss_mask(MAT);
    uint32_t w[NR][4];
    {
        const uint32_t a = sb + E_WO + (MAT == 0 ? 0 : MAT == 1 ? NRQ : NRQ + NRK) * 2048 + unit_frag_addr(fresh_tid());
        mbar_wait(bars + EB_WL * 8, 0);
        if (MAT == 0 && threadIdx.x == 0) TG(79, 2);
#pragma unroll
        for (int u = 0; u < NR; u++) ldsm4t(w[u], a + u * 2048);
    }
    nbar_arrive(NB_T, 448);
    int tid = fresh_tid() - MAT * 128;
#define TID (tid = pin(tid << P.zero))
    if (MAT == 0) { if (V_FIRST == 36) nbar_arrive(NB_S, 256); nbar_arrive(NB_PV, 256); nbar_arrive(NB_WO, 256); }
    auto project = [&](const int i) {
        const uint32_t par = i & 1;
        ArPart<MAT> ar;
        {
            float d[32];
            const uint64_t da = mkdesc((MAT == 0 ? E_WQ : MAT == 1 ? E_WK : E_WV), 1024, 1024, 1);
            constexpr int R1 = V_BURST1, R2 = V_BURST1 + V_BURST2;
#pragma unroll
            for (int n = 0; n < 9; n++) {
                const int blk = x_order(MAT, n), prev = n ? x_order(MAT, n - 1) : -1, f = MAT != 2 && blk < 2 ? 9 + blk : blk;
                if (MAT == 2) {
                    if (n == (R1 >= 2 ? R1 : R2)) { wg_wait<0>(); mbar_arrive_warp(bars + EB_V0 * 8); }
                    if ((n == 0 && (V_FIRST == 36 || i == 0)) || n == R1 || n == R2) {
#pragma unroll
                        for (int j = n; j < (n < R1 ? R1 : n < R2 ? R2 : V_PRE); j++) mbar_wait(bars + (EB_FULL + j) * 8, par);
                    }
                    if (n == 0 && V_FIRST == 36) nbar_sync(NB_S, 256);
                    if (n == R1) nbar_sync(NB_PV, 256);
                    if (n == R2) nbar_sync(NB_WO, 256);
                } else {
                    if (n == 0) nbar_sync(MAT ? NB_VL : NB_VL2, 256);
                }
                const bool wt = f >= (MAT == 2 || V_LEAD < V_PRE ? V_PRE : V_LEAD);
                if (wt) mbar_wait(bars + (EB_FULL + f) * 8, par);
                TX(MAT * 128, 1 + MAT * 9 + n);
                if (wt || n == 0 || (MAT == 2 ? n == R1 || n == R2 : n - 1 == (MAT ? AR_STK : AR_STQ))) wg_fence();
                if (n == 0) TS(MAT * 128, i, 20 + MAT);
                const uint64_t db = mkdesc(x_slot(f), 16, 1024, 1);
#pragma unroll
                for (int j = 0; j < 4; j++) {
                    const int ks = blk * 4 + j, s = popc_below(M, ks);
                    if ((M >> ks) & 1) wg_ss64<0>(d, da + s * 128, db + j * 2, n + j > 0);
                    else wg_rs64<0>(d, w[ks - s], db + j * 2, n + j > 0);
                }
                wg_commit();
                if (MAT == 2 && n + 1 == V_LEAD) { nbar_arrive(NB_VL, 256); if (!K_LEAD) nbar_arrive(NB_VL2, 256); }
                if (MAT == 1 && n + 1 == K_LEAD) nbar_arrive(NB_VL2, 256);
                if (MAT != 2 && n == (MAT ? AR_LDK : AR_LDQ)) { ar.first_load(i - 1, TID); }
                if (MAT != 2 && n == (MAT ? AR_STK : AR_STQ)) { ar.store(P, i - 1, TID); mbar_arrive_warp(bars + EB_MEM0 * 8); }
                if (MAT != 2 && x_empty(prev) >= 0) { wg_wait<1>(); mbar_arrive_warp(bars + (EB_EMPTY + x_empty(prev)) * 8); }
            }
            const uint32_t a = sb + (MAT == 0 ? E_QT : MAT == 1 ? E_KT : E_VT) + tl_lane(TID, MAT == 0 ? 2048 : 1024);
            if (MAT != 2) {
                mbar_wait(bars + (EB_EMPTY + 2) * 8, par);
                mbar_wait(bars + EB_MEM * 8, par);
            } else {
                mbar_wait(bars + EB_OST * 8, par ^ 1);
            }
            wg_wait_acc<0, 32>(d);
            TS(MAT * 128, i, 23 + MAT);
#pragma unroll
            for (int j = 0; j < 8; j += 2) {
                const int grp = MAT == 0 ? 2 * (j & 3) + (j >> 2) : j < 4 ? j : j + 2;
                stsm4(a + grp * 1024, pack2(d[4 * j], d[4 * j + 1]), pack2(d[4 * j + 2], d[4 * j + 3]), pack2(d[4 * j + 4], d[4 * j + 5]), pack2(d[4 * j + 6], d[4 * j + 7]));
            }
        }
        if (MAT != 2) {
            mbar_arrive_warp(bars + EB_STEP * 8);
        } else {
            __syncwarp();
            if ((TID & 31) < 3) mbar_arrive(bars + (EB_EMPTY + (tid & 31)) * 8);
            if (AR_VWAIT) mbar_wait(bars + EB_EMPTY * 8, par);
            ar.first_load(i - 1, TID);
            ar.store(P, i - 1, tid);
            TS(256, i, 19);
            mbar_wait(bars + EB_MEM0 * 8, par);
            fence_async_smem();
            mbar_arrive_warp(bars + EB_MEM * 8);
        }
    };
    auto step = [&](const int i) {
        const uint32_t par = i & 1;
        if (MAT == 2) {
            if (Q_LEAD) nbar_sync(NB_OM, 256);
            else mbar_wait(bars + EB_MEM * 8, par);
        }
        float d[8];
        TS(MAT * 128, i, MAT == 2 ? 26 : 14 + MAT);
        wg_fence();
        constexpr int MID = MAT == 0 ? Q_LEAD : MAT == 2 ? V_FIRST : 0;
        proj_mem<MAT, NR, 0, MID>(d, w);
        if (MAT == 0 && Q_LEAD) nbar_arrive(NB_OM, 256);
        if (MAT == 2 && V_FIRST < 36) {
#pragma unroll
            for (int j = 0; j < V_BURST1; j++) mbar_wait(bars + (EB_FULL + j) * 8, i == NSTEP - 1 ? par : par ^ 1);
            nbar_sync(NB_S, 256);
            wg_fence();
        }
        proj_mem<MAT, NR, MID, 36>(d, w);
        wg_commit();
        if (MAT == 0) {
            attn_mem(d, par, i, TID);
        } else if (MAT == 1) {
            tid *= mbar_wait(bars + EB_STEP * 8, par);
            const uint32_t a = pin(sb + E_KT + 4096 + tl_lane(tid, 1024));
            wg_wait_acc<0, 8>(d);
            stsm4(a, pack2(d[0], d[1]), pack2(d[2], d[3]), pack2(d[4], d[5]), pack2(d[6], d[7]));
            nbar_arrive(NB_QK, 256);
            TS(128, i, 18);
            fence_async_smem();
            nbar_sync(SX_GATE ? NB_S2 : NB_W, SX_GATE ? 256 : 128);
            float p[2][10];
            attn_x_scores(p, par, i, TID);
            attn_x_finish(p, par, i, TID, pin(P.zero));
        } else {
            const int rank = cta_rank();
            const uint32_t a = pin(sb + E_VT + 4096 + tl_lane(TID, 1024)), of = pin(E_VF + rank * 2048 + (tid & 127) * 16);
            const uint32_t peer = pin(mapa(sb, rank ^ 1));
            wg_wait_acc<0, 8>(d);
            const uint32_t v0 = pack2(d[0], d[1]), v1 = pack2(d[2], d[3]), v2 = pack2(d[4], d[5]), v3 = pack2(d[6], d[7]);
            st_async128(peer + of, v0, v1, v2, v3, peer + SM_BAR + EB_VM * 8);
            sts128(sb + of, v0, v1, v2, v3);
            stsm4(a, v0, v1, v2, v3);
            mbar_arrive_warp(bars + EB_VM * 8);
            mbar_arrive_warp(bars + EB_KF * 8);
            TS(256, i, 16);
        }
        if (MAT == 0) {
            const int rank = cta_rank();
            uint8_t* const ar = g_ar + (i & 3) * AR_SLOT;
            uint8_t* const pm = ar + pin(ar_main(TID) + rank * (64 * AR_STR));
            uint8_t* const ps = ar + pin(ar_side(tid) + rank * (64 * AR_STR));
            const uint32_t o8 = (128 - rank * 64) * AR_STR;
            const uint64_t db = mkdesc(E_OM, 128, OM_STR, 0), da = mkdesc(E_WO, 1024, 1024, 1);
            nbar_sync(NB_G, 128);
            fence_async_smem();
            TS(0, i, 6);
            if (i == NSTEP - 1) return;
            float y[4][8];
            wg_fence();
            if (WO_MODE == 2) {
#pragma unroll
                for (int T = 0; T < 4; T++) {
#pragma unroll
                    for (int ks = 0; ks < 8; ks++) wg_ss16(y[T], da + (T * 8 + ks) * 128, db + ks * 16, ks > 0);
                    wg_commit();
                }
                if (V_EARLY) nbar_arrive(NB_WO, 256);
                wg_wait_acc<2, 8>(y[0]); acc_ready<8>(y[1]);
                { ArWords z(y[0]); z.red(pm, ps); z.force(P.zero); }
                ArWords(y[1]).red(pm + 16 * AR_STR, ps + 16 * AR_STR);
                wg_wait_acc<1, 8>(y[2]);
                ArWords(y[2]).red(pm + 32 * AR_STR, ps + 32 * AR_STR);
                wg_fence();
#pragma unroll
                for (int ks = 0; ks < 4; ks++) wg_ss16(y[0], da + (32 + ks) * 128, db + (rank * 4 + ks) * 16, ks > 0);
                wg_commit();
                if (!V_EARLY) nbar_arrive(NB_WO, 256);
                wg_wait_acc<1, 8>(y[3]);
                ArWords(y[3]).red(pm + 48 * AR_STR, ps + 48 * AR_STR);
                wg_wait_acc<0, 8>(y[0]);
                ArWords(y[0]).red(pm + o8, ps + o8);
                return;
            }
#pragma unroll
            for (int ks = 0; ks < 4; ks++) wg_ss16(y[3], da + (32 + ks) * 128, db + (rank * 4 + ks) * 16, ks > 0);
            wg_commit();
#pragma unroll
            for (int ks = 0; ks < 8; ks++) wg_ss16(y[0], da + ks * 128, db + ks * 16, ks > 0);
            wg_commit();
            if (WO_MODE == 0) {
#pragma unroll
                for (int ks = 0; ks < 8; ks++) wg_ss16(y[2], da + (16 + ks) * 128, db + ks * 16, ks > 0);
                wg_commit();
                wg_wait_acc<2, 8>(y[3]);
                ArWords z(y[3]);
                z.force(P.zero);
                wg_fence();
#pragma unroll
                for (int ks = 0; ks < 8; ks++) wg_ss16(y[1], da + (8 + ks) * 128, db + ks * 16, ks > 0);
                wg_commit();
#pragma unroll
                for (int ks = 0; ks < 8; ks++) wg_ss16(y[3], da + (24 + ks) * 128, db + ks * 16, ks > 0);
                wg_commit();
                if (V_EARLY) nbar_arrive(NB_WO, 256);
                z.red(pm + o8, ps + o8);
                wg_wait_acc<2, 8>(y[2]); acc_ready<8>(y[0]);
                ArWords(y[0]).red(pm, ps);
                ArWords(y[2]).red(pm + 32 * AR_STR, ps + 32 * AR_STR);
            } else {
                wg_wait_acc<1, 8>(y[3]);
                { ArWords z(y[3]); z.red(pm + o8, ps + o8); z.force(P.zero); }
                wg_fence();
#pragma unroll
                for (int ks = 0; ks < 8; ks++) wg_ss16(y[2], da + (16 + ks) * 128, db + ks * 16, ks > 0);
                wg_commit();
                wg_wait_acc<1, 8>(y[0]);
                { ArWords z(y[0]); z.red(pm, ps); z.force(P.zero); }
                wg_fence();
#pragma unroll
                for (int ks = 0; ks < 8; ks++) wg_ss16(y[1], da + (8 + ks) * 128, db + ks * 16, ks > 0);
                wg_commit();
                wg_wait_acc<1, 8>(y[2]);
                { ArWords z(y[2]); z.red(pm + 32 * AR_STR, ps + 32 * AR_STR); z.force(P.zero); }
                wg_fence();
#pragma unroll
                for (int ks = 0; ks < 8; ks++) wg_ss16(y[3], da + (24 + ks) * 128, db + ks * 16, ks > 0);
                wg_commit();
                if (V_EARLY) nbar_arrive(NB_WO, 256);
            }
            wg_wait_acc<1, 8>(y[1]);
            ArWords(y[1]).red(pm + 16 * AR_STR, ps + 16 * AR_STR);
            wg_wait_acc<0, 8>(y[3]);
            ArWords(y[3]).red(pm + 48 * AR_STR, ps + 48 * AR_STR);
            if (!V_EARLY) nbar_arrive(NB_WO, 256);
            TS(0, i, 7);
        }
    };
    if (MAT != 2) {
#pragma unroll 1
        for (int i = 0; i < NSTEP; i++) { project(i); step(i); }
    } else {
#pragma unroll 1
        for (int i = -1; i < NSTEP; i++) {
            if (i >= 0) step(i);
            if (i < NSTEP - 1) project(i + 1);
        }
    }
    if (MAT == 2) { if (V_FIRST == 36) nbar_sync(NB_S, 256); nbar_sync(NB_PV, 256); }
}

__device__ __forceinline__ void engine_helper(const Params& P) {
    const int lane = threadIdx.x & 31, hw = warp_in_group(), e = blockIdx.x, rank = e & 1;
    if (hw < 3) {
        constexpr uint64_t M0 = ss_mask(0), M1 = ss_mask(1), M2 = ss_mask(2);
        const uint64_t m = hw == 0 ? M0 : hw == 1 ? M1 : M2;
        const uint32_t ws = sb + (hw == 0 ? E_WQ : hw == 1 ? E_WK : E_WV), wr = sb + E_WO + (hw == 0 ? 0 : hw == 1 ? NRQ : NRQ + NRK) * 2048;
        if (lane == 0) mbar_expect(bars + EB_WL * 8, 36 * 2048);
        __syncwarp();
        for (int ks = lane; ks < 36; ks += 32) {
            const int s = __popcll(m & ((1ull << ks) - 1));
            tma_unit(((m >> ks) & 1) ? ws + s * 2048 : wr + (ks - s) * 2048, hw == 0 ? &P.tmWq : hw == 1 ? &P.tmWk : &P.tmWv, ks, e, bars + EB_WL * 8);
        }
    }
    if (hw == 1) {
        hold_back(WO_DELAY);
        for (int u = lane; u < 36; u += 32)
            asm volatile("cp.async.bulk.prefetch.tensor.2d.L2.global [%0, {%1,%2}];"
                         :: "l"(&P.tmWo), "r"((u < 32 ? rank * 4 + (u >> 3) : 8) * 64), "r"(((e >> 1) * 8 + (u < 32 ? u & 7 : rank * 4 + (u & 3))) * 16) : "memory");
    }
    __syncwarp();
    if (hw < 2) nbar_sync(NB_T, 448);
    if (lane == 0) TG(79, 3);
    if (hw == 0) {
        if (lane == 0) {
            const uint32_t peer = mapa(sb, rank ^ 1);
#pragma unroll 1
            for (int n = 0; n < NSTEP; n++) {
                const uint32_t par = (n & 1) ^ 1;
                uint32_t rdy;
                do { asm volatile("ld.acquire.cta.shared.u32 %0, [%1];" : "=r"(rdy) : "r"(sb + SM_XRDY) : "memory"); } while (rdy <= n && (__nanosleep(20), true));
                fence_async_glb();
                TG(n, 30);
                const uint8_t* s0 = g_x0 + min(n, NSEG - 1) * XIMG;
                const uint8_t* s1 = n >= LAG ? g_x1 + (n - LAG) * XIMG : s0;
#pragma unroll
                for (int j = 0; j < 11; j++) {
                    const int f = j < 9 ? j : 19 - j, blk = f < 9 ? f : f - 9;
                    if (n > 0 && (f == 0 || f == 2 || f == 4 || f == 8 || f == 10))
                        mbar_wait(bars + (f == 0 ? EB_STEP : f == 2 ? EB_KF : f == 4 ? EB_QF : f == 8 ? EB_CONS : EB_OFREE) * 8, par);
                    if (f == 6 || f == 9) mbar_wait(bars + (f == 6 ? EB_V0 : EB_EMPTY + 1) * 8, par ^ 1);
                    const uint32_t fb = bars + (EB_FULL + f) * 8;
                    mbar_expect(fb, 8192);
                    bulk_g2s(sb + x_slot(f), s0 + blk * 4096, 4096, fb);
                    bulk_g2s(sb + x_slot(f) + 4096, s1 + blk * 4096, 4096, fb);
                }
                mbar_arrive_remote(peer + SM_BAR + EB_PRDY * 8);
            }
        }
    } else if (hw == 1) {
        if (lane == 0) mbar_expect(bars + EB_WO * 8, 36 * 2048);
        __syncwarp();
        for (int u = lane; u < 36; u += 32)
            tma_unit(sb + E_WO + u * 2048, &P.tmWo, (e >> 1) * 8 + (u < 32 ? u & 7 : rank * 4 + (u & 3)), u < 32 ? rank * 4 + (u >> 3) : 8, bars + EB_WO * 8);
        __syncwarp();
        if (lane == 0) {
#pragma unroll 1
            for (int i = 0; i < NSTEP; i++) {
                mbar_wait(bars + EB_STEP * 8, i & 1);
                mbar_arrive_remote(mapa(sb, rank ^ 1) + SM_BAR + EB_PRDY2 * 8);
                mbar_wait(bars + EB_OST * 8, i & 1);
                fence_async_smem();
                bulk_s2g(g_o + (i & (RING - 1)) * O_BYTES + e * 8192, sb + E_R1, 8192);
                asm volatile("cp.async.bulk.commit_group;" ::: "memory");
                asm volatile("cp.async.bulk.wait_group.read 0;" ::: "memory");
                mbar_arrive(bars + EB_OFREE * 8);
                asm volatile("cp.async.bulk.wait_group 0;" ::: "memory");
                publish(F_O, i);
                TG(i, 31);
            }
        }
    } else if (hw == 2) {
        const uint32_t peer = mapa(sb, rank ^ 1);
        const int idx = e * 23 + lane, line = idx >> 3;
        uint8_t* z = g_ar + (line < 144 ? line * AR_STR : (line - 144) * (4 * AR_STR) + AR_STR / 2) + (idx & 7) * 16;
        if (lane < 23 && idx < 1440) { stg128(z, make_uint4(0, 0, 0, 0)); stg128(z + AR_SLOT, make_uint4(0, 0, 0, 0)); }
        __syncwarp();
        if (lane == 0) {
            publish(F_X0, B_ZERO);
            mbar_arrive(bars + EB_MEM * 8);
            flag_wait(F_X0, B_ZERO, NENG * this_launch());
            mbar_arrive(bars + EB_WO * 8);
            TG(79, 5);
        }
        __syncwarp();
#pragma unroll 1
        for (int i = 0; i < NSTEP; i++) {
            mbar_wait(bars + EB_EMPTY * 8, i & 1);
            if (lane == 0) {
                mbar_wait_cl(bars + EB_PRDY * 8, i & 1);
                fence_async_smem();
                bulk_s2peer(peer + E_VP, sb + E_VT, 4096, peer + SM_BAR + EB_VX * 8);
                bulk_s2peer(peer + E_VP + 4096, sb + E_VT + 6144, 4096, peer + SM_BAR + EB_VX * 8);
                mbar_expect(bars + EB_VX * 8, 8192);
                mbar_expect(bars + EB_SX * 8, SX_BF16 ? 3840 : 7168);
                mbar_expect(bars + EB_SM * 8, 2560);
                mbar_expect(bars + EB_VM * 8, 2048);
            }
            __syncwarp();
            mbar_wait(bars + EB_MEM * 8, i & 1);
            if (lane < 23 && idx < 1440) stg128(z + ((i + 2) & 3) * AR_SLOT, make_uint4(0, 0, 0, 0));
            __syncwarp();
            if (lane == 0) { fence_gpu(); mbar_arrive(bars + EB_MEM * 8); }
            __syncwarp();
        }
    } else {
        for (int j = lane; j < 72; j += 32) asm volatile("prefetch.global.L2 [%0];" :: "l"(P.mem0 + j * 64));
        const uint32_t ep = this_launch(), t0 = timer_lo();
        if (lane == 0) {
#pragma unroll 1
            for (int n = 0; n < NSTEP; n++) {
                while ((n < NSEG && !flag_up(F_X0, n, 16 * ep)) || (n >= LAG && !flag_up(F_X1, n - LAG, 16 * ep))) {
                    __nanosleep(20);
                    if (timer_lo() - t0 > TIME_LIMIT) break;
                }
                fence_acq_gpu();
                asm volatile("st.release.cta.shared.u32 [%0], %1;" :: "r"(sb + SM_XRDY), "r"(n + 1) : "memory");
            }
        }
    }
    __syncwarp();
}

__device__ __forceinline__ void f1_fetch(const Params& P, uint32_t dst, int f0, int ks0, int n) {
    const int tid = threadIdx.x & 127, r = tid >> 3, c = (tid & 3) * 2 + ((tid >> 2) & 1);
    const bf16* src = ((c & 1) ? P.w3 : P.w1) + (size_t)(ks0 * 16 + r) * FF + f0 + (c >> 1) * 8;
    dst += r * 128 + ((c ^ (r & 7)) << 4);
#pragma unroll 1
    for (int u = 0; u < n; u++) {
        asm volatile("cp.async.cg.shared.global [%0], [%1], 16;" :: "r"(dst + u * 2048), "l"(src + (size_t)u * 16 * FF) : "memory");
        asm volatile("cp.async.commit_group; cp.async.wait_group %0;" :: "n"(F1_DEPTH) : "memory");
    }
}
template <bool RF, bool second>
__device__ __forceinline__ void f1_tile(const uint32_t (&w)[NRF][4], uint32_t ws, int b, int fo) {
    const uint32_t par = b & 1;
    float d[32];
    const uint64_t da = mkdesc(ws, 1024, 1024, 1), db = mkdesc(F_X, 16, 1024, 1);
#pragma unroll
    for (int blk = 0; blk < 9; blk++) {
        if (!second || blk == 0) mbar_wait(bars + (FB_FULL + blk) * 8, par);
        if (!second || blk == 0) wg_fence();
#pragma unroll
        for (int j = 0; j < 4; j++) {
            const int ks = blk * 4 + j;
            if (RF && ks < NRF) wg_rs64<0>(d, w[ks < NRF ? ks : 0], db + blk * 512 + j * 2, ks > 0);
            else wg_ss64<0>(d, da + (RF ? ks - NRF : 36 - NRF + ks) * 128, db + blk * 512 + j * 2, ks > 0);
        }
        wg_commit();
        if (blk > 0 && second) { wg_wait<1>(); mbar_arrive_warp(bars + (FB_EMPTY + blk - 1) * 8); }
    }
    const int tid = fresh_tid(), g = (tid & 31) >> 2;
    uint8_t* dst = g_h + (b & (RING - 1)) * H_BYTES + ((fresh_bid() - NENG) * 128 + fo + ((tid >> 5) & 3) * 8 + g) * 128;
    wg_wait_acc<0, 32>(d);
    if (second) mbar_arrive_warp(bars + (FB_EMPTY + 8) * 8);
    uint32_t h[8];
#pragma unroll
    for (int j = 0; j < 8; j++) {
        const float g0 = d[4 * j], g1 = d[4 * j + 1];
        const float e0 = 1.f + ex2(fminf(-LOG2E * g0, 60.f)), e1 = 1.f + ex2(fminf(-LOG2E * g1, 60.f));
        const float r = rcp(e0 * e1);
        h[j] = pack2(g0 * d[4 * j + 2] * (e1 * r), g1 * d[4 * j + 3] * (e0 * r));
    }
    stg128(dst + (((tid & 3) ^ g) << 4), make_uint4(h[0], h[1], h[2], h[3]));
    stg128(dst + ((((tid & 3) + 4) ^ g) << 4), make_uint4(h[4], h[5], h[6], h[7]));
}
template <int a>
__device__ __forceinline__ void f1_main(const Params& P) {
    constexpr uint32_t ws = F_W + a * (72 - NRF) * 2048;
    const int f0 = (blockIdx.x - NENG) * 128 + a * 64;
    uint32_t w[NRF][4];
    hold_back(F1_DELAY);
    f1_fetch(P, sb + ws, f0, 0, NRF);
    asm volatile("cp.async.wait_all;" ::: "memory");
    nbar_sync(NB_G + a, 128);
    {
        const uint32_t fa = sb + ws + unit_frag_addr(threadIdx.x);
#pragma unroll
        for (int u = 0; u < NRF; u++) ldsm4t(w[u], fa + u * 2048);
    }
    nbar_sync(NB_G + a, 128);
    f1_fetch(P, sb + ws, f0, NRF, 36 - NRF);
    f1_fetch(P, sb + ws + (36 - NRF) * 2048, f0 + 32, 0, 36);
    asm volatile("cp.async.wait_all;" ::: "memory");
    fence_async_smem();
    nbar_sync(NB_G + a, 128);
    if (threadIdx.x == 0) TG(79, 2);
#pragma unroll 1
    for (int b = 0; b < NSTEP; b++) {
        f1_tile<a == 0, false>(w, ws, b, a * 96);
        f1_tile<a == 1, true>(w, ws, b, 32 + a * 32);
        mbar_wait(bars + FB_RACK * 8, (b & 1) ^ 1);
        mbar_arrive_warp(bars + FB_H * 8);
    }
}
__device__ __forceinline__ uint32_t n_pairs(int b) { return (b < NSEG ? 16 : 0) + (b >= LAG ? 16 : 0); }
__device__ __forceinline__ void publisher(uint32_t done, uint32_t ack, int stage) {
#pragma unroll 1
    for (int b = 0; b < NSTEP; b++) {
        mbar_wait(done, b & 1);
        mbar_arrive(ack);
        TG(b, 30);
        publish(stage, b);
        TG(b, 31);
    }
}
__device__ __forceinline__ void f1_helper(const Params& P) {
    const int hw = warp_in_group();
    if ((threadIdx.x & 31) == 0) {
        if (hw == 0) {
            const uint32_t ep = this_launch();
#pragma unroll 1
            for (int b = 0; b < NSTEP; b++) {
                flag_wait(F_XF, b, n_pairs(b) * ep);
                TG(b, 29);
                const uint8_t* src = g_xf + (b & (RING - 1)) * (9 * 8192);
#pragma unroll 1
                for (int blk = 0; blk < 9; blk++) {
                    mbar_wait(bars + (FB_EMPTY + blk) * 8, (b & 1) ^ 1);
                    mbar_expect(bars + (FB_FULL + blk) * 8, 8192);
                    bulk_g2s(sb + F_X + blk * 8192, src + blk * 8192, 8192, bars + (FB_FULL + blk) * 8);
                }
            }
        } else if (hw == 1) {
            hold_back(PF_DELAY);
#pragma unroll 1
            for (int j = 0; j < 24; j++) {
                const bf16* w = j >= 16 ? P.w2 : (j & 1) ? P.w3 : P.w1;
                asm volatile("cp.async.bulk.prefetch.L2.global [%0], %1;" :: "l"(w + (size_t)((j >= 16 ? j - 16 : j >> 1) * NF1 + blockIdx.x - NENG) * (2 * FF)), "r"(4 * FF) : "memory");
                hold_back(PF_PACE);
            }
            publisher(bars + FB_H * 8, bars + FB_RACK * 8, F_H);
        } else if (hw == 2 && blockIdx.x < NENG + 32) {
            const uint32_t ep = this_launch();
            int b1 = blockIdx.x < NENG + 16 ? 0 : LAG, b2 = b1;
            const int bend = b1 + NSEG;
#pragma unroll 1
            for (int j = 0; j < 2 * NSEG; j++) {
                [[maybe_unused]] int n = 0;
                bool second, any;
                const bool may1 = b1 < bend && b1 < b2 + RING;
                do {
                    const bool r1 = flag_up(F_P1, b1, 15 * ep);
                    second = flag_up(F_P2, b2, 17 * ep);
                    any = (r1 & may1) | second;
                    if (!any) __nanosleep(20);
                    SPIN_CHECK(n, 20);
                } while (!any);
                fence_acq_gpu();
                TG(second ? b2 : b1, 25 + 2 * second);
                if (j) mbar_wait(bars + FB_RDONE * 8, (j & 1) ^ 1);
                sts32(sb + F_RED + 64 + (j & 1) * 4, second ? b2 + 256 : b1);
                mbar_arrive(bars + FB_JOB * 8);
                if (second) b2++; else b1++;
            }
        }
    }
    __syncwarp();
}

__device__ __forceinline__ void add8(float* f, uint4 a) {
    f[0] += bf_lo(a.x); f[1] += bf_hi(a.x); f[2] += bf_lo(a.y); f[3] += bf_hi(a.y);
    f[4] += bf_lo(a.z); f[5] += bf_hi(a.z); f[6] += bf_lo(a.w); f[7] += bf_hi(a.w);
}
__device__ __forceinline__ void set8(float* f, uint4 a) {
    f[0] = bf_lo(a.x); f[1] = bf_hi(a.x); f[2] = bf_lo(a.y); f[3] = bf_hi(a.y);
    f[4] = bf_lo(a.z); f[5] = bf_hi(a.z); f[6] = bf_lo(a.w); f[7] = bf_hi(a.w);
}
__device__ __forceinline__ void ln0_rows(const Params& P, int r) {
    const int lane = threadIdx.x & 31, l = lane < 24 ? lane : 0;
    const uint4* xrow = (const uint4*)(P.x + r * DM) + l;
    uint4 xw[2][3];
#pragma unroll
    for (int k = 0; k < 6; k++) xw[k / 3][k % 3] = __ldg(xrow + (k / 3) * (16 * DM / 8) + 24 * (k % 3));
#pragma unroll 1
    for (int seg = 0; seg < NSEG; seg++) {
#pragma unroll 1
        for (int h = 0; h < 2; h++) {
            float f[24];
#pragma unroll
            for (int k = 0; k < 3; k++) { set8(&f[k * 8], xw[0][k]); xw[0][k] = xw[1][k]; }
            if (seg + 1 < NSEG) {
#pragma unroll
                for (int k = 0; k < 3; k++) xw[1][k] = __ldg(xrow + (2 * seg + 2 + h) * (16 * DM / 8) + 24 * k);
            }
            float s = 0.f, q = 0.f;
#pragma unroll
            for (int j = 0; j < 24; j++) s += f[j];
            if (lane >= 24) s = 0.f;
#pragma unroll
            for (int o = 16; o; o >>= 1) s += __shfl_xor_sync(~0u, s, o);
            const float mean = s * (1.f / DM);
#pragma unroll
            for (int j = 0; j < 24; j++) { f[j] -= mean; q += f[j] * f[j]; }
            if (lane >= 24) q = 0.f;
#pragma unroll
            for (int o = 16; o; o >>= 1) q += __shfl_xor_sync(~0u, q, o);
            const float rstd = rsqrtf(q * (1.f / DM) + 1e-5f);
            if (lane < 24) {
                uint8_t* d = g_x0 + seg * XIMG + (l >> 3) * 4096 + (r + 16 * h) * 128 + (((l & 7) ^ (r & 7)) << 4);
#pragma unroll
                for (int k = 0; k < 3; k++) {
                    const float* y = &f[8 * k];
                    stg128(d + k * 12288, make_uint4(pack2(y[0] * rstd, y[1] * rstd), pack2(y[2] * rstd, y[3] * rstd), pack2(y[4] * rstd, y[5] * rstd), pack2(y[6] * rstd, y[7] * rstd)));
                }
            }
        }
        __syncwarp();
        if (lane == 0 && seg == 0) TG(79, 4);
        if (lane == 0) publish(F_X0, seg);
        if (lane == 0 && seg == 0) TG(79, 5);
        __syncwarp();
    }
}

template <bool SECOND, bool CHAIN>
__device__ __forceinline__ void reduce_job(const Params& P, int b) {
    constexpr int NP = SECOND ? NP2 : NP1;
    const int tid = fresh_tid() & 127, lane = tid & 31, p = fresh_bid() - NENG, seg = CHAIN ? b - LAG : b;
    const bool act = lane < 24;
    const int i = (tid >> 5) * 24 + (act ? lane : 0);
    const uint32_t ro = (b & (RING - 1)), po = p * (DM * 4) + i * 32;
    const int fa = (i >> 1) * 16 + (i & 1) * 4;
    const uint32_t row = (seg * 32 + (p & 15) * 2) * DM + fa;
    uint8_t* const r1 = g_r1 + ro * PART + po;
    uint8_t* const r2 = g_r2 + seg * (PART / 2) + po - (CHAIN ? PART / 2 : 0);
    float f[16];
    uint4 x0, x1;
    {
        const uint8_t* src = (SECOND ? g_p2 : g_p1) + ro * (NP * PART) + po;
        uint4 a[NP][2];
#pragma unroll
        for (int k = 0; k < NP; k++) { a[k][0] = ld_rlx128(src + k * PART); a[k][1] = ld_rlx128(src + k * PART + 16); }
        if (SECOND || CHAIN) {
            x0 = ld_rlx128(SECOND ? r1 : r2); x1 = ld_rlx128((SECOND ? r1 : r2) + 16);
        } else {
            const uint2 a0 = ld_rlx64(P.x + row), b0 = ld_rlx64(P.x + row + 8), a1 = ld_rlx64(P.x + row + DM), c1 = ld_rlx64(P.x + row + DM + 8);
            x0 = make_uint4(__byte_perm(a0.x, a1.x, 0x5410), __byte_perm(b0.x, c1.x, 0x5410), __byte_perm(a0.x, a1.x, 0x7632), __byte_perm(b0.x, c1.x, 0x7632));
            x1 = make_uint4(__byte_perm(a0.y, a1.y, 0x5410), __byte_perm(b0.y, c1.y, 0x5410), __byte_perm(a0.y, a1.y, 0x7632), __byte_perm(b0.y, c1.y, 0x7632));
        }
        set8(f, a[0][0]);
#pragma unroll
        for (int k = 1; k < NP; k++) add8(f, a[k][0]);
        set8(f + 8, a[0][1]);
#pragma unroll
        for (int k = 1; k < NP; k++) add8(f + 8, a[k][1]);
    }
    add8(f, x0); add8(f + 8, x1);
    x0 = make_uint4(pack2(f[0], f[1]), pack2(f[2], f[3]), pack2(f[4], f[5]), pack2(f[6], f[7]));
    x1 = make_uint4(pack2(f[8], f[9]), pack2(f[10], f[11]), pack2(f[12], f[13]), pack2(f[14], f[15]));
    if (SECOND && CHAIN) {
        if (act) {
            stg64(P.out + row, __byte_perm(x0.x, x0.z, 0x5410), __byte_perm(x1.x, x1.z, 0x5410));
            stg64(P.out + row + 8, __byte_perm(x0.y, x0.w, 0x5410), __byte_perm(x1.y, x1.w, 0x5410));
            stg64(P.out + row + DM, __byte_perm(x0.x, x0.z, 0x7632), __byte_perm(x1.x, x1.z, 0x7632));
            stg64(P.out + row + DM + 8, __byte_perm(x0.y, x0.w, 0x7632), __byte_perm(x1.y, x1.w, 0x7632));
        }
        return;
    }
    set8(f, x0); set8(f + 8, x1);
    float st[4] = {0.f, 0.f, 0.f, 0.f};
#pragma unroll
    for (int j = 0; j < 16; j++) { st[j & 1] += f[j]; st[2 + (j & 1)] += f[j] * f[j]; }
    {
        const bool u = lane & 1, v = lane & 2;
        st[0] = (u ? st[1] : st[0]) + __shfl_xor_sync(~0u, u ? st[0] : st[1], 1);
        st[2] = (u ? st[3] : st[2]) + __shfl_xor_sync(~0u, u ? st[2] : st[3], 1);
        st[0] = (v ? st[2] : st[0]) + __shfl_xor_sync(~0u, v ? st[0] : st[2], 2);
        st[0] += __shfl_xor_sync(~0u, st[0], 4);
        if (act && !(lane & 4)) sts32(sb + F_RED + 128 + (i >> 3) * 16 + (lane & 3) * 4, fu(st[0]));
    }
    if (act) { stg128(SECOND ? r2 : r1, x0); stg128((SECOND ? r2 : r1) + 16, x1); }
    nbar_sync(NB_R, 96);
#pragma unroll
    for (int k = 0; k < 9; k++) {
        const uint4 t = lds128(sb + F_RED + 128 + k * 16);
        if (k == 0) { st[0] = uf(t.x); st[1] = uf(t.y); st[2] = uf(t.z); st[3] = uf(t.w); }
        else { st[0] += uf(t.x); st[1] += uf(t.y); st[2] += uf(t.z); st[3] += uf(t.w); }
    }
    const float m0 = st[0] * (1.f / DM), m1 = st[1] * (1.f / DM);
    const float q0 = rsqrtf(fmaxf(st[2] * (1.f / DM) - m0 * m0, 0.f) + 1e-5f), q1 = rsqrtf(fmaxf(st[3] * (1.f / DM) - m1 * m1, 0.f) + 1e-5f);
    if (act) {
        uint8_t* d = (SECOND ? g_x1 + seg * XIMG + (fa >> 6) * 4096 : g_xf + ro * (9 * 8192) + (fa >> 6) * 8192) + p * 256 + (i & 1) * 8;
#pragma unroll
        for (int e = 0; e < 2; e++) {
            const float m = e ? m1 : m0, q = e ? q1 : q0;
#pragma unroll
            for (int h = 0; h < 2; h++) {
                const float* y = &f[2 * h + e];
                stg64(d + e * 128 + (((((fa >> 3) & 6) + h) ^ ((2 * p + e) & 7)) << 4), pack2((y[0] - m) * q, (y[4] - m) * q), pack2((y[8] - m) * q, (y[12] - m) * q));
            }
        }
    }
}
__device__ __forceinline__ void reducer(const Params& P) {
    const bool chain = blockIdx.x >= NENG + 16;
    if (warp_in_group() < 3) {
#pragma unroll 1
        for (int j = 0; j < 2 * NSEG; j++) {
            mbar_wait(bars + FB_JOB * 8, j & 1);
            const int job = lds32(sb + F_RED + 64 + (j & 1) * 4);
            if (job >= 256) { if (chain) reduce_job<true, true>(P, job - 256); else reduce_job<true, false>(P, job - 256); }
            else { if (chain) reduce_job<false, true>(P, job); else reduce_job<false, false>(P, job); }
            mbar_arrive_warp(bars + FB_RDONE * 8);
        }
    } else if (threadIdx.x == 352) {
        mbar_arrive(bars + FB_JOB * 8);
#pragma unroll 1
        for (int j = 0; j < 2 * NSEG; j++) {
            mbar_wait(bars + FB_RDONE * 8, j & 1);
            const int job = lds32(sb + F_RED + 64 + (j & 1) * 4);
            mbar_arrive(bars + FB_JOB * 8);
            TG(job & 255, 23 + (job >> 8));
            if (job < 256 || !chain) publish(job < 256 ? F_XF : F_X1, job & 255);
            TG(job & 255, 26 + 2 * (job >> 8));
        }
    }
    __syncwarp();
}

__host__ __device__ constexpr int d_rf(int u) { return u < 48 ? ((u & 3) < 2 ? (u >> 2) * 2 + (u & 1) : -1) : u == 48 ? 24 : -1; }
__host__ __device__ constexpr int d_ss(int u) { return u < 48 ? (u >> 2) * 2 + (u & 1) : u - 25; }
template <bool WIDE, int wg>
__device__ __forceinline__ void d_main() {
    constexpr int NR = WIDE ? 24 : NRD;
    uint32_t w[NR][4];
    {
        const uint32_t fa = sb + wg * (NRD * 2048) + unit_frag_addr(threadIdx.x);
        mbar_wait(bars + DB_WL * 8, 0);
#pragma unroll
        for (int u = 0; u < NR; u++) ldsm4t(w[u], fa + u * 2048);
        nbar_arrive(NB_W, 416);
        mbar_wait(bars + DB_WL * 8, 1);
        if (threadIdx.x == 0) TG(79, 2);
    }
    const uint64_t da = mkdesc(wg * ((52 - NRD) * 2048), 1024, 1024, 1);
#pragma unroll 1
    for (int b = 0; b < NSTEP; b++) {
#pragma unroll
        for (int T = 0; T < (WIDE ? 3 : 1); T++) {
            float d[32];
            constexpr int NB = WIDE ? 4 : 13;
#pragma unroll
            for (int blk = 0; blk < NB; blk++) {
                const int c = blk;
                if (T == 0 || blk == 0) mbar_wait(bars + (DB_FULL + (c & 7)) * 8, WIDE || (c & 7) >= 5 ? b & 1 : c >> 3);
                if (T == 0 || blk == 0) wg_fence();
                const uint64_t db = mkdesc(D_B + (c & 7) * 8192, 8192, 1024, 1);
#pragma unroll
                for (int j = 0; j < 4; j++) {
                    const int u = T * 16 + blk * 4 + j;
                    if (d_rf(u) >= 0) wg_rs64<1>(d, w[d_rf(u) >= 0 ? d_rf(u) : 0], db + j * 128, blk + j > 0);
                    else wg_ss64<1>(d, da + d_ss(u) * 128, db + j * 128, blk + j > 0);
                }
                wg_commit();
                if (!WIDE && blk > 0) { wg_wait<1>(); mbar_arrive_warp(bars + (DB_EMPTY + ((c - 1) & 7)) * 8); }
            }
            const int tid = fresh_tid(), t = tid & 3, ds = fresh_bid() - NENG - NF1;
            const bool w2 = ds >= 15;
            const int tile = WIDE ? wg * 3 + T : (ds % 3) * 3 + wg;
            uint8_t* dst = (w2 ? g_p2 + ((b & (RING - 1)) * NP2 + (WIDE ? ds - 25 : (ds - 15) / 3)) * PART : g_p1 + ((b & (RING - 1)) * NP1 + ds / 3) * PART)
                         + (tile * 64 + ((tid >> 5) & 3) * 16 + ((tid & 31) >> 2) * 2) * 4 + (w2 ? 4 * t : t) * (DM * 4);
            const uint32_t js = w2 ? DM * 4 : DM * 16;
            wg_wait_acc<0, 32>(d);
            if (!WIDE) mbar_arrive_warp(bars + (DB_EMPTY + ((NB - 1) & 7)) * 8);
            else if (T == 2) {
#pragma unroll
                for (int blk = 0; blk < 4; blk++) mbar_arrive_warp(bars + (DB_EMPTY + blk) * 8);
            }
#pragma unroll
            for (int j = 0; j < 8; j++) stg64(dst + (j >> 2) * (DM * 64) + (j & 3) * js, pack2(d[4 * j], d[4 * j + 1]), pack2(d[4 * j + 2], d[4 * j + 3]));
        }
        mbar_wait(bars + (DB_P + 1) * 8, (b & 1) ^ 1);
        mbar_arrive_warp(bars + DB_P * 8);
    }
}
__device__ __forceinline__ void d_helper(const Params& P, int ds) {
    const int lane = threadIdx.x & 31, hw = warp_in_group();
    const bool w2 = ds >= 15, wide = ds >= 30;
    const int blk0 = wide ? 65 + (ds - 30) * 4 : ((w2 ? ds - 15 : ds) / 3) * 13, nb = wide ? 4 : 13;
    if (hw == 0) {
        const int nu = wide ? 48 : 52;
        hold_back(w2 ? W2_DELAY : D_DELAY);
#pragma unroll 1
        for (int ph = 0; ph < 2; ph++) {
            if (ph) nbar_sync(NB_W, 416);
            if (lane == 0) mbar_expect(bars + DB_WL * 8, (wide ? 72 : ph ? 3 * (52 - NRD) : 3 * NRD) * 2048);
            __syncwarp();
#pragma unroll 1
            for (int x = lane; x < 3 * nu; x += 32) {
                const int wg = x / nu, u = x - wg * nu;
                if ((d_rf(u) < 0) == (ph != 0))
                    tma_unit(sb + (ph ? wg * (52 - NRD) + d_ss(u) : wg * NRD + d_rf(u)) * 2048, w2 ? &P.tmW2 : &P.tmWo,
                             blk0 * 4 + (wide ? u & 15 : u), wide ? wg * 3 + (u >> 4) : (ds % 3) * 3 + wg, bars + DB_WL * 8);
            }
        }
        __syncwarp();
        if (lane == 0) {
            const uint32_t target = (w2 ? NF1 : NENG) * this_launch();
#pragma unroll 1
            for (int b = 0; b < NSTEP; b++) {
                flag_wait(w2 ? F_H : F_O, b, target);
                TG(b, 29);
                const uint8_t* src = (w2 ? g_h + (b & (RING - 1)) * H_BYTES : g_o + (b & (RING - 1)) * O_BYTES) + blk0 * 8192;
#pragma unroll 1
                for (int blk = 0; blk < nb; blk++) {
                    const int c = blk;
                    mbar_wait(bars + (DB_EMPTY + (c & 7)) * 8, (wide || (c & 7) >= 5 ? b & 1 : c >> 3) ^ 1);
                    mbar_expect(bars + (DB_FULL + (c & 7)) * 8, 8192);
                    bulk_g2s(sb + D_B + (c & 7) * 8192, src + blk * 8192, 8192, bars + (DB_FULL + (c & 7)) * 8);
                }
            }
        }
    } else if (hw == 1 && lane == 0) {
        publisher(bars + DB_P * 8, bars + (DB_P + 1) * 8, w2 ? F_P2 : F_P1);
    }
    __syncwarp();
}

__device__ __forceinline__ void sign_off() { mbar_arrive_warp(sb + SM_DONE); }
__device__ __forceinline__ void sign_off_helper() {
    if (warp_in_group() < 3) { sign_off(); return; }
    uint32_t ok;
    const uint32_t t0 = timer_lo();
    do {
        asm volatile("{.reg .pred p; mbarrier.try_wait.parity.shared::cta.b64 p, [%1], 0, 0x100000; selp.u32 %0, 1, 0, p;}" : "=r"(ok) : "r"(sb + SM_DONE) : "memory");
    } while (!ok && timer_lo() - t0 < TIME_LIMIT);
    if (!ok || (sb & 0x3ffff) != SM_ORG) __trap();
    if (fresh_tid() == NTHREADS - 32) { g_epoch[fresh_bid()][0] = this_launch(); TG(79, 1); }
    __syncwarp();
}

__global__ void __cluster_dims__(2, 1, 1) __launch_bounds__(NTHREADS, 1) fused_kernel(const __grid_constant__ Params P) {
    const int wg = __shfl_sync(~0u, threadIdx.x >> 7, 0);
    const int bid = blockIdx.x;
    if (threadIdx.x >= NTHREADS - 32) sts32(sb + SM_ONES + (threadIdx.x & 31) * 4, 0x3f803f80u);
    if (threadIdx.x == 0) {
        TG(79, 0);
        mbar_init(sb + SM_DONE, 15);
        sts32(sb + SM_XRDY, 0);
        if (bid < NENG) {
            for (int i = 0; i < 11; i++) mbar_init(bars + (EB_FULL + i) * 8, 1);
            mbar_init(bars + EB_V0 * 8, 4);
            for (int i = 0; i < 3; i++) mbar_init(bars + (EB_EMPTY + i) * 8, 12);
            mbar_init(bars + EB_PRDY2 * 8, 1);
            mbar_init(bars + EB_WL * 8, 3); mbar_init(bars + EB_WO * 8, 2); mbar_init(bars + EB_STEP * 8, 8);
            mbar_init(bars + EB_VX * 8, 1); mbar_init(bars + EB_SM * 8, 1); mbar_init(bars + EB_SX * 8, 1); mbar_init(bars + EB_VM * 8, 5);
            mbar_init(bars + EB_QF * 8, 4); mbar_init(bars + EB_KF * 8, 8); mbar_init(bars + EB_MEM * 8, 5); mbar_init(bars + EB_MEM0 * 8, 8); mbar_init(bars + EB_PRDY * 8, 1);
            mbar_init(bars + EB_CONS * 8, 4); mbar_init(bars + EB_OST * 8, 4); mbar_init(bars + EB_OFREE * 8, 1);
        } else if (bid < NENG + NF1) {
            for (int i = 0; i < 9; i++) { mbar_init(bars + (FB_FULL + i) * 8, 1); mbar_init(bars + (FB_EMPTY + i) * 8, 8); }
            mbar_init(bars + FB_H * 8, 8); mbar_init(bars + FB_RACK * 8, 1); mbar_init(bars + FB_JOB * 8, 2); mbar_init(bars + FB_RDONE * 8, 3);
        } else {
            for (int i = 0; i < 8; i++) { mbar_init(bars + (DB_FULL + i) * 8, 1); mbar_init(bars + (DB_EMPTY + i) * 8, 12); }
            mbar_init(bars + DB_WL * 8, 1); mbar_init(bars + DB_P * 8, 12); mbar_init(bars + (DB_P + 1) * 8, 1);
        }
        asm volatile("fence.mbarrier_init.release.cluster;" ::: "memory");
    }
    __syncthreads();
    asm volatile("barrier.cluster.arrive.relaxed.aligned; barrier.cluster.wait.aligned;" ::: "memory");
    if (bid < NENG) {
        if (wg == 0) { reg_inc<REGQ>(); engine_main<0>(P); sign_off(); cluster_sync_all(); }
        else if (wg == 1) { reg_inc<REGK>(); engine_main<1>(P); sign_off(); cluster_sync_all(); }
        else if (wg == 2) { reg_inc<REGV>(); engine_main<2>(P); sign_off(); cluster_sync_all(); }
        else { reg_dec<24>(); engine_helper(P); sign_off_helper(); cluster_sync_all(); }
    } else if (bid < NENG + NF1) {
        if (wg < 2) {
            reg_inc<200>();
            if (wg == 0) f1_main<0>(P); else f1_main<1>(P);
            sign_off();
        } else if (wg == 2) {
            reg_dec<88>();
            if (bid >= NENG + 32) ln0_rows(P, (bid - NENG - 32) * 4 + ((threadIdx.x >> 5) & 3));
            else reducer(P);
            sign_off();
        } else {
            reg_dec<24>();
            f1_helper(P);
            sign_off_helper();
        }
    } else {
        const int ds = bid - NENG - NF1;
        if (wg < 3) {
            reg_inc<160>();
            if (ds < 30) { if (wg == 0) d_main<false, 0>(); else if (wg == 1) d_main<false, 1>(); else d_main<false, 2>(); }
            else { if (wg == 0) d_main<true, 0>(); else if (wg == 1) d_main<true, 1>(); else d_main<true, 2>(); }
            sign_off();
        } else {
            reg_dec<32>();
            d_helper(P, ds);
            sign_off_helper();
        }
    }
}

typedef CUresult (*EncodeFn)(CUtensorMap*, CUtensorMapDataType, cuuint32_t, void*, const cuuint64_t*, const cuuint64_t*,
                             const cuuint32_t*, const cuuint32_t*, CUtensorMapInterleave, CUtensorMapSwizzle,
                             CUtensorMapL2promotion, CUtensorMapFloatOOBfill);

void make_map(EncodeFn enc, CUtensorMap* m, const void* p, int rows, int cols) {
    cuuint64_t dims[2] = {(cuuint64_t)cols, (cuuint64_t)rows};
    cuuint64_t strides[1] = {(cuuint64_t)cols * 2};
    cuuint32_t box[2] = {64, 16};
    cuuint32_t es[2] = {1, 1};
    enc(m, CU_TENSOR_MAP_DATA_TYPE_BFLOAT16, 2, (void*)p, dims, strides, box, es, CU_TENSOR_MAP_INTERLEAVE_NONE,
        CU_TENSOR_MAP_SWIZZLE_128B, CU_TENSOR_MAP_L2_PROMOTION_L2_128B, CU_TENSOR_MAP_FLOAT_OOB_FILL_NONE);
}

}

extern "C" void kernel_launch(void* const* d_in, const int* in_sizes, int n_in, void* d_out, int out_size) {
    (void)in_sizes; (void)n_in; (void)out_size;
    static EncodeFn enc = nullptr;
    if (!enc) {
        void* fn = nullptr;
        cudaDriverEntryPointQueryResult qr;
        cudaGetDriverEntryPoint("cuTensorMapEncodeTiled", &fn, cudaEnableDefault, &qr);
        enc = (EncodeFn)fn;
        cudaFuncSetAttribute(fused_kernel, cudaFuncAttributeMaxDynamicSharedMemorySize, SM_TOTAL);
    }
    Params P;
    make_map(enc, &P.tmWq, d_in[2], DM, 4096);
    make_map(enc, &P.tmWk, d_in[3], DM, 4096);
    make_map(enc, &P.tmWv, d_in[4], DM, 4096);
    make_map(enc, &P.tmWo, d_in[5], 4096, DM);
    make_map(enc, &P.tmW2, d_in[10], FF, DM);
    P.x = (const bf16*)d_in[0];
    P.mem0 = (const bf16*)d_in[1];
    P.w1 = (const bf16*)d_in[8];
    P.w3 = (const bf16*)d_in[9];
    P.w2 = (const bf16*)d_in[10];
    P.out = (bf16*)d_out;
    P.zero = 0;
    fused_kernel<<<NCTA, NTHREADS, SM_TOTAL>>>(P);
}
```

```cpp
#include <cuda_runtime.h>
#include <cuda_bf16.h>
#include <cuda.h>
#include <stdint.h>

typedef __nv_bfloat16 bf16;

namespace {

constexpr int DM = 576, FF = 4608, NSEG = 64;
constexpr int NENG = 64, NF1 = 36, ND = 32, NCTA = NENG + NF1 + ND;
constexpr int NTHREADS = 512;
#define LAG 8
#define RING 16
static_assert(RING > LAG, "ring too short");
constexpr int NSTEP = NSEG + LAG;

enum { F_X0 = 0, F_X1, F_O, F_P1, F_XF, F_H, F_P2, F_H2, F_COUNT };
constexpr int B_ZERO = 95;
__device__ uint32_t g_flag[F_COUNT][96][8];
__device__ uint32_t g_epoch[NCTA][8];
constexpr int XIMG = 9 * 4096;
constexpr int O_BYTES = 65 * 8192;
constexpr int H_BYTES = 73 * 8192;
constexpr int PART = 32 * DM * 4;
constexpr int NP1 = 5, NP2 = 7;
__device__ __align__(1024) uint8_t g_x0[NSEG * XIMG];
__device__ __align__(1024) uint8_t g_x1[NSEG * XIMG];
__device__ __align__(1024) uint8_t g_xf[RING * 9 * 8192];
__device__ __align__(1024) uint8_t g_o[RING * O_BYTES];
__device__ __align__(1024) uint8_t g_h[RING * H_BYTES];
__device__ __align__(1024) uint8_t g_p1[RING * NP1 * PART];
__device__ __align__(1024) uint8_t g_p2[RING * NP2 * PART];
__device__ __align__(1024) uint8_t g_r1[RING * PART];
__device__ __align__(1024) uint8_t g_r2[NSEG * PART / 2];
#define AR_STR 4352
constexpr int AR_SLOT = 144 * AR_STR;
__device__ __align__(1024) uint8_t g_ar[4 * AR_SLOT];

struct Params {
    CUtensorMap tmWq, tmWk, tmWv, tmWo, tmW2;
    const bf16 *x, *mem0, *w1, *w3, *w2;
    bf16* out;
    uint32_t zero;
};

constexpr uint32_t SM_ORG = 1024;
extern __shared__ __align__(1024) uint8_t smem_raw[];
#define sb ((uint32_t)__cvta_generic_to_shared(smem_raw))
#define bars (sb + SM_BAR)
constexpr int SM_BAR = 231936;
constexpr int SM_TOTAL = SM_BAR + 512;
#define NRQ 25
#define NRK 25
#define NRV 25
#define REGQ 160
#define REGK 168
#define REGV 160
constexpr int E_WQ = 0;
constexpr int E_WK = E_WQ + (36 - NRQ) * 2048;
constexpr int E_WV = E_WK + (36 - NRK) * 2048;
constexpr int E_WO = E_WV + (36 - NRV) * 2048;
constexpr int E_MEM = E_WO + 36 * 2048;
constexpr int E_R0 = E_MEM + 18432;
constexpr int E_R1 = E_R0 + 8192, E_R2 = E_R1 + 8192;
constexpr int E_SX = E_R1;
constexpr int E_QT = E_R2 + 8192;
constexpr int E_KT = E_QT + 8192;
constexpr int E_VT = E_KT + 10240;
constexpr int E_VP = E_VT + 10240;
constexpr int E_VF = E_VP + 8192;
constexpr int E_QM = E_VF + 4096;
constexpr int E_SR = E_QM + 2048;
constexpr int E_SL = E_SR + 2560;
constexpr int E_END = E_SL + 2048;
constexpr int E_OM = E_MEM + 16384, OM_STR = E_QM - E_OM;
static_assert(E_END <= SM_BAR, "engine smem overflow");
static_assert(E_WO + (NRQ + NRK + NRV) * 2048 <= E_VF, "weight staging: the peer writes there without asking");
enum {
    EB_FULL = 0, EB_EMPTY = 11  , EB_PRDY2 = 14, EB_V0, EB_WL, EB_WO, EB_STEP, EB_VX, EB_SM, EB_SX, EB_VM, EB_QF, EB_KF, EB_CONS, EB_OST, EB_OFREE,
    EB_MEM, EB_PRDY, EB_MEM0
};
enum { NB_G = 1, NB_LEAD, NB_QK, NB_S, NB_OM, NB_W, NB_R, NB_T, NB_PV, NB_WO, NB_V, NB_KT, NB_S2, NB_VL };
constexpr int NB_VL2 = NB_LEAD;
#define REGF 208
constexpr int NRF = REGF == 200 ? 35 : 36;
constexpr int F_W = 0;
constexpr int F_X = 2 * (72 - NRF) * 2048;
constexpr int F_RED = F_X + 9 * 8192;
static_assert(F_RED + 512 <= SM_BAR, "F1 smem overflow");
enum { FB_FULL = 0, FB_EMPTY = 9, FB_H = 18, FB_H2, FB_RACK, FB_JOB, FB_RDONE };
constexpr int NRD = 25;
constexpr int D_B = 3 * (52 - NRD) * 2048;
static_assert(D_B + 8 * 8192 <= SM_BAR, "D smem overflow");
enum { DB_FULL = 0, DB_EMPTY = 8, DB_WL = 16, DB_P };
constexpr int SM_DONE = SM_BAR + 248, SM_XRDY = SM_BAR + 376, SM_ONES = SM_BAR + 384;
constexpr uint32_t TIME_LIMIT = 2000000000u;

#define SPIN_CHECK(n, code)

#define TS(thr, step, k)
#define TX(thr, k)
#define TG(step, k)
#define PROF_INC(n, k)

__device__ __forceinline__ uint32_t mapa(uint32_t a, uint32_t r) {
    uint32_t o; asm("mapa.shared::cluster.u32 %0, %1, %2;" : "=r"(o) : "r"(a), "r"(r)); return o;
}
__device__ __forceinline__ void mbar_init(uint32_t b, uint32_t cnt) {
    asm volatile("mbarrier.init.shared::cta.b64 [%0], %1;" :: "r"(b), "r"(cnt) : "memory");
}
__device__ __forceinline__ void mbar_arrive(uint32_t b) {
    asm volatile("mbarrier.arrive.shared::cta.b64 _, [%0];" :: "r"(b) : "memory");
}
__device__ __forceinline__ void mbar_arrive_warp(uint32_t b) {
    asm volatile("{.reg .pred p; bar.warp.sync -1; elect.sync _|p, -1; @p mbarrier.arrive.shared::cta.b64 _, [%0];}" :: "r"(b) : "memory");
}
__device__ __forceinline__ void mbar_arrive_remote(uint32_t b) {
    asm volatile("fence.release.sync_restrict::shared::cta.cluster; mbarrier.arrive.relaxed.cluster.shared::cluster.b64 _, [%0];" :: "r"(b) : "memory");
}
__device__ __forceinline__ void mbar_expect(uint32_t b, uint32_t bytes) {
    asm volatile("mbarrier.arrive.expect_tx.shared::cta.b64 _, [%0], %1;" :: "r"(b), "r"(bytes) : "memory");
}
__device__ __forceinline__ uint32_t mbar_wait(uint32_t b, uint32_t par) {
    uint32_t ok; [[maybe_unused]] int n = 0;
    while (true) {
        asm volatile("{.reg .pred p; mbarrier.try_wait.parity.shared::cta.b64 p, [%1], %2; selp.u32 %0, 1, 0, p;}"
                     : "=r"(ok) : "r"(b), "r"(par) : "memory");
        if (ok) break;
        SPIN_CHECK(n, 1000 + ((b & 511) >> 3));
    }
    return ok;
}
__device__ __forceinline__ bool mbar_test(uint32_t b, uint32_t par) {
    uint32_t ok;
    asm volatile("{.reg .pred p; mbarrier.test_wait.parity.shared::cta.b64 p, [%1], %2; selp.u32 %0, 1, 0, p;}" : "=r"(ok) : "r"(b), "r"(par) : "memory");
    return ok;
}
__device__ __forceinline__ void mbar_wait_cl(uint32_t b, uint32_t par) {
    uint32_t ok; [[maybe_unused]] int n = 0;
    while (true) {
        asm volatile("{.reg .pred p; mbarrier.try_wait.parity.relaxed.cluster.shared::cta.b64 p, [%1], %2; selp.u32 %0, 1, 0, p;}"
                     : "=r"(ok) : "r"(b), "r"(par) : "memory");
        if (ok) break;
        SPIN_CHECK(n, 1000 + ((b & 511) >> 3));
    }
    asm volatile("fence.acquire.sync_restrict::shared::cluster.cluster;" ::: "memory");
}
__device__ __forceinline__ void nbar_sync(int id, int n) { asm volatile("bar.sync %0, %1;" :: "r"(id), "r"(n) : "memory"); }
__device__ __forceinline__ void nbar_arrive(int id, int n) { asm volatile("bar.arrive %0, %1;" :: "r"(id), "r"(n) : "memory"); }
__device__ __forceinline__ void cluster_sync_all() {
    asm volatile("barrier.cluster.arrive.release.aligned; barrier.cluster.wait.acquire.aligned;" ::: "memory");
}
__device__ __forceinline__ void fence_async_smem() { asm volatile("fence.proxy.async.shared::cta;" ::: "memory"); }
__device__ __forceinline__ void fence_async_glb() { asm volatile("fence.proxy.async.global;" ::: "memory"); }
__device__ __forceinline__ void fence_rel_gpu() { asm volatile("fence.release.gpu;" ::: "memory"); }
__device__ __forceinline__ void fence_acq_gpu() { asm volatile("fence.acquire.gpu;" ::: "memory"); }
__device__ __forceinline__ void fence_gpu() { asm volatile("fence.acq_rel.gpu;" ::: "memory"); }
__device__ __forceinline__ int fresh_tid() { int t; asm volatile("mov.u32 %0, %%tid.x;" : "=r"(t)); return t; }
__device__ __forceinline__ int fresh_bid() { int t; asm volatile("mov.u32 %0, %%ctaid.x;" : "=r"(t)); return t; }
__device__ __forceinline__ uint32_t pin(uint32_t v) { asm volatile("" : "+r"(v)); return v; }
__device__ __forceinline__ int warp_in_group() { return __shfl_sync(~0u, (fresh_tid() >> 5) & 3, 0); }
__device__ __forceinline__ int cta_rank() { int t; asm volatile("mov.u32 %0, %%cluster_ctarank;" : "=r"(t)); return t; }
__device__ __forceinline__ uint32_t timer_lo() { uint32_t t; asm volatile("mov.u32 %0, %%globaltimer_lo;" : "=r"(t)); return t; }
__device__ __forceinline__ uint32_t keep(uint32_t v) { return __shfl_xor_sync(~0u, v, 0); }
__device__ __forceinline__ void red_add_u32(uint32_t* p, uint32_t v) {
    asm volatile("red.relaxed.gpu.global.add.u32 [%0], %1;" :: "l"(p), "r"(v) : "memory");
}
__device__ __forceinline__ uint32_t ld_rlx(const void* p) {
    uint32_t v; asm volatile("ld.relaxed.gpu.global.u32 %0, [%1];" : "=r"(v) : "l"(p) : "memory"); return v;
}
__device__ __forceinline__ uint2 ld_rlx64(const void* p) {
    uint2 v; asm volatile("ld.relaxed.gpu.global.v2.u32 {%0,%1}, [%2];" : "=r"(v.x), "=r"(v.y) : "l"(p) : "memory"); return v;
}
__device__ __forceinline__ uint4 ld_rlx128(const void* p) {
    uint4 v;
    asm volatile("ld.relaxed.gpu.global.v4.u32 {%0,%1,%2,%3}, [%4];" : "=r"(v.x), "=r"(v.y), "=r"(v.z), "=r"(v.w) : "l"(p) : "memory");
    return v;
}
__device__ __forceinline__ void stg128(void* p, uint4 v) {
    asm volatile("st.global.v4.b32 [%0], {%1,%2,%3,%4};" :: "l"(p), "r"(v.x), "r"(v.y), "r"(v.z), "r"(v.w) : "memory");
}
__device__ __forceinline__ void stg64(void* p, uint32_t a, uint32_t b) {
    asm volatile("st.global.v2.b32 [%0], {%1,%2};" :: "l"(p), "r"(a), "r"(b) : "memory");
}
__device__ __forceinline__ void stg16(void* p, uint32_t a) { asm volatile("st.global.b16 [%0], %1;" :: "l"(p), "h"((uint16_t)a) : "memory"); }
__device__ __forceinline__ void stg32(void* p, uint32_t a) { asm volatile("st.global.b32 [%0], %1;" :: "l"(p), "r"(a) : "memory"); }
__device__ __forceinline__ void st_async128(uint32_t a, uint32_t x, uint32_t y, uint32_t z, uint32_t w, uint32_t mb) {
    asm volatile("st.async.shared::cluster.mbarrier::complete_tx::bytes.v4.b32 [%0], {%1,%2,%3,%4}, [%5];"
                 :: "r"(a), "r"(x), "r"(y), "r"(z), "r"(w), "r"(mb) : "memory");
}
__device__ __forceinline__ void st_async64(uint32_t a, uint32_t x, uint32_t y, uint32_t mb) {
    asm volatile("st.async.shared::cluster.mbarrier::complete_tx::bytes.v2.b32 [%0], {%1,%2}, [%3];"
                 :: "r"(a), "r"(x), "r"(y), "r"(mb) : "memory");
}
__device__ __forceinline__ void sts128(uint32_t a, uint32_t x, uint32_t y, uint32_t z, uint32_t w) {
    asm volatile("st.shared.v4.b32 [%0], {%1,%2,%3,%4};" :: "r"(a), "r"(x), "r"(y), "r"(z), "r"(w) : "memory");
}
__device__ __forceinline__ void sts32(uint32_t a, uint32_t v) { asm volatile("st.shared.b32 [%0], %1;" :: "r"(a), "r"(v) : "memory"); }
__device__ __forceinline__ uint4 lds128(uint32_t a) {
    uint4 v; asm volatile("ld.shared.v4.b32 {%0,%1,%2,%3}, [%4];" : "=r"(v.x), "=r"(v.y), "=r"(v.z), "=r"(v.w) : "r"(a) : "memory"); return v;
}
__device__ __forceinline__ uint2 lds64(uint32_t a) {
    uint2 v; asm volatile("ld.shared.v2.b32 {%0,%1}, [%2];" : "=r"(v.x), "=r"(v.y) : "r"(a) : "memory"); return v;
}
__device__ __forceinline__ uint32_t lds32(uint32_t a) {
    uint32_t v; asm volatile("ld.shared.b32 %0, [%1];" : "=r"(v) : "r"(a) : "memory"); return v;
}
__device__ __forceinline__ void bulk_g2s(uint32_t dst, const void* src, uint32_t bytes, uint32_t mb) {
    asm volatile("cp.async.bulk.shared::cluster.global.mbarrier::complete_tx::bytes [%0], [%1], %2, [%3];"
                 :: "r"(dst), "l"(src), "r"(bytes), "r"(mb) : "memory");
}
__device__ __forceinline__ void bulk_s2g(void* dst, uint32_t src, uint32_t bytes) {
    asm volatile("cp.async.bulk.global.shared::cta.bulk_group [%0], [%1], %2;" :: "l"(dst), "r"(src), "r"(bytes) : "memory");
}
__device__ __forceinline__ void bulk_s2peer(uint32_t dst, uint32_t src, uint32_t bytes, uint32_t mb) {
    asm volatile("cp.async.bulk.shared::cluster.shared::cta.mbarrier::complete_tx::bytes [%0], [%1], %2, [%3];"
                 :: "r"(dst), "r"(src), "r"(bytes), "r"(mb) : "memory");
}
__device__ __forceinline__ void tma_unit(uint32_t dst, const CUtensorMap* tm, int kstep, int mgroup, uint32_t mb) {
    asm volatile("cp.async.bulk.tensor.2d.shared::cluster.global.mbarrier::complete_tx::bytes [%0], [%1, {%2,%3}], [%4];"
                 :: "r"(dst), "l"(tm), "r"(mgroup * 64), "r"(kstep * 16), "r"(mb) : "memory");
}
__device__ __forceinline__ void ldsm4(uint32_t* r, uint32_t a) {
    asm volatile("ldmatrix.sync.aligned.m8n8.x4.shared.b16 {%0,%1,%2,%3}, [%4];"
                 : "=r"(r[0]), "=r"(r[1]), "=r"(r[2]), "=r"(r[3]) : "r"(a) : "memory");
}
__device__ __forceinline__ void ldsm4t(uint32_t* r, uint32_t a) {
    asm volatile("ldmatrix.sync.aligned.m8n8.x4.trans.shared.b16 {%0,%1,%2,%3}, [%4];"
                 : "=r"(r[0]), "=r"(r[1]), "=r"(r[2]), "=r"(r[3]) : "r"(a) : "memory");
}
__device__ __forceinline__ void stsm4(uint32_t a, uint32_t r0, uint32_t r1, uint32_t r2, uint32_t r3) {
    asm volatile("stmatrix.sync.aligned.m8n8.x4.shared.b16 [%0], {%1,%2,%3,%4};" :: "r"(a), "r"(r0), "r"(r1), "r"(r2), "r"(r3) : "memory");
}
__device__ __forceinline__ void stsm4t(uint32_t a, uint32_t r0, uint32_t r1, uint32_t r2, uint32_t r3) {
    asm volatile("stmatrix.sync.aligned.m8n8.x4.trans.shared.b16 [%0], {%1,%2,%3,%4};" :: "r"(a), "r"(r0), "r"(r1), "r"(r2), "r"(r3) : "memory");
}
__device__ __forceinline__ uint32_t pack2(float lo, float hi) {
    uint32_t d; asm("cvt.rn.bf16x2.f32 %0, %1, %2;" : "=r"(d) : "f"(hi), "f"(lo)); return d;
}
__device__ __forceinline__ float bf_lo(uint32_t w) { return __uint_as_float(w << 16); }
__device__ __forceinline__ float bf_hi(uint32_t w) { return __uint_as_float(w & 0xffff0000u); }
__device__ __forceinline__ float ex2(float x) { float y; asm("ex2.approx.ftz.f32 %0, %1;" : "=f"(y) : "f"(x)); return y; }
__device__ __forceinline__ float rcp(float x) { float y; asm("rcp.approx.ftz.f32 %0, %1;" : "=f"(y) : "f"(x)); return y; }
__device__ __forceinline__ uint32_t fu(float x) { return __float_as_uint(x); }
__device__ __forceinline__ float uf(uint32_t x) { return __uint_as_float(x); }
__device__ __forceinline__ void mma16816(float* d, const uint32_t* a, uint32_t b0, uint32_t b1) {
    asm volatile("mma.sync.aligned.m16n8k16.row.col.f32.bf16.bf16.f32 {%0,%1,%2,%3}, {%4,%5,%6,%7}, {%8,%9}, {%0,%1,%2,%3};"
                 : "+f"(d[0]), "+f"(d[1]), "+f"(d[2]), "+f"(d[3]) : "r"(a[0]), "r"(a[1]), "r"(a[2]), "r"(a[3]), "r"(b0), "r"(b1));
}
__device__ __forceinline__ void mma1688(float* d, uint32_t a0, uint32_t a1, uint32_t b0) {
    asm volatile("mma.sync.aligned.m16n8k8.row.col.f32.bf16.bf16.f32 {%0,%1,%2,%3}, {%4,%5}, {%6}, {%0,%1,%2,%3};"
                 : "+f"(d[0]), "+f"(d[1]), "+f"(d[2]), "+f"(d[3]) : "r"(a0), "r"(a1), "r"(b0));
}
template <int N> __device__ __forceinline__ void reg_inc() { asm volatile("setmaxnreg.inc.sync.aligned.u32 %0;" :: "n"(N)); }
template <int N> __device__ __forceinline__ void reg_dec() { asm volatile("setmaxnreg.dec.sync.aligned.u32 %0;" :: "n"(N)); }

__device__ __forceinline__ uint64_t mkdesc(uint32_t addr, uint32_t lbo, uint32_t sbo, uint32_t swz) {
    return (uint64_t)((addr + SM_ORG) >> 4) | ((uint64_t)(lbo >> 4) << 16) | ((uint64_t)(sbo >> 4) << 32) | ((uint64_t)swz << 62);
}
__device__ __forceinline__ void wg_fence() { asm volatile("wgmma.fence.sync.aligned;" ::: "memory"); }
__device__ __forceinline__ void wg_commit() { asm volatile("wgmma.commit_group.sync.aligned;" ::: "memory"); }
template <int N> __device__ __forceinline__ void wg_wait() { asm volatile("wgmma.wait_group.sync.aligned %0;" :: "n"(N) : "memory"); }
template <int M> __device__ __forceinline__ void acc_ready(float* d) {
#pragma unroll
    for (int j = 0; j < M; j++) asm volatile("" : "+f"(d[j]) :: "memory");
}
template <int N, int M> __device__ __forceinline__ void wg_wait_acc(float* d) { wg_wait<N>(); acc_ready<M>(d); }

#define F8(c, d, o) c(d[o]), c(d[o + 1]), c(d[o + 2]), c(d[o + 3]), c(d[o + 4]), c(d[o + 5]), c(d[o + 6]), c(d[o + 7])
#define R8L "%0,%1,%2,%3,%4,%5,%6,%7"
#define R16L R8L ",%8,%9,%10,%11,%12,%13,%14,%15"
#define R32L R16L ",%16,%17,%18,%19,%20,%21,%22,%23,%24,%25,%26,%27,%28,%29,%30,%31"
#define R40L R32L ",%32,%33,%34,%35,%36,%37,%38,%39"
#define WG_BOTH(TXT_PRE, TXT_POST, OUTS, ...)                                                   \
    if (acc) asm volatile(TXT_PRE "1" TXT_POST : OUTS("+f") : __VA_ARGS__);                     \
    else asm volatile(TXT_PRE "0" TXT_POST : OUTS("=f") : __VA_ARGS__)
#define O8(c) F8(c, d, 0)
#define O16(c) F8(c, d, 0), F8(c, d, 8)
#define O32(c) O16(c), F8(c, d, 16), F8(c, d, 24)
#define O40(c) O32(c), F8(c, d, 32)
#define WGM(n) "wgmma.mma_async.sync.aligned.m64n" #n "k16.f32.bf16.bf16 "
__device__ __forceinline__ void wg_rs16(float* d, const uint32_t* a, uint64_t db, bool acc) {
    WG_BOTH(WGM(16) "{" R8L "}, {%8,%9,%10,%11}, %12, ", ", 1, 1, 1;", O8, "r"(a[0]), "r"(a[1]), "r"(a[2]), "r"(a[3]), "l"(db));
}
__device__ __forceinline__ void wg_ss16(float* d, uint64_t da, uint64_t db, bool acc) {
    WG_BOTH(WGM(16) "{" R8L "}, %8, %9, ", ", 1, 1, 1, 1;", O8, "l"(da), "l"(db));
}
__device__ __forceinline__ void wg_rs8(float* d, const uint32_t* a, uint64_t db, bool acc) {
#define O4(c) c(d[0]), c(d[1]), c(d[2]), c(d[3])
    WG_BOTH(WGM(8) "{%0,%1,%2,%3}, {%4,%5,%6,%7}, %8, ", ", 1, 1, 0;", O4, "r"(a[0]), "r"(a[1]), "r"(a[2]), "r"(a[3]), "l"(db));
}
__device__ __forceinline__ void wg_rs32(float* d, const uint32_t* a, uint64_t db, bool acc) {
    WG_BOTH(WGM(32) "{" R16L "}, {%16,%17,%18,%19}, %20, ", ", 1, 1, 0;", O16, "r"(a[0]), "r"(a[1]), "r"(a[2]), "r"(a[3]), "l"(db));
}
template <int TB> __device__ __forceinline__ void wg_rs64(float* d, const uint32_t* a, uint64_t db, bool acc) {
    WG_BOTH(WGM(64) "{" R32L "}, {%32,%33,%34,%35}, %36, ", ", 1, 1, %37;", O32, "r"(a[0]), "r"(a[1]), "r"(a[2]), "r"(a[3]), "l"(db), "n"(TB));
}
template <int TB> __device__ __forceinline__ void wg_ss64(float* d, uint64_t da, uint64_t db, bool acc) {
    WG_BOTH(WGM(64) "{" R32L "}, %32, %33, ", ", 1, 1, 1, %34;", O32, "l"(da), "l"(db), "n"(TB));
}
__device__ __forceinline__ void wg_ss80(float* d, uint64_t da, uint64_t db, bool acc) {
    WG_BOTH(WGM(80) "{" R40L "}, %40, %41, ", ", 1, 1, 1, 1;", O40, "l"(da), "l"(db));
}

constexpr float SM_SCALE = 0.08838834764831845f;
constexpr float LOG2E = 1.4426950408889634f;

#define WO_DELAY 3000
#define D_DELAY 7000
#define F1_DELAY 7000
#define W2_DELAY 16500
#define F1_DEPTH 30
#define PF_DELAY 6000
#define PF_PACE 400
__device__ __forceinline__ void hold_back(uint32_t ns) {
    const uint32_t t0 = timer_lo();
    while (timer_lo() - t0 < ns) __nanosleep(50);
}

__device__ __forceinline__ uint32_t* flag_ptr(int stage, int b) { return &g_flag[stage][b][0]; }
__device__ __forceinline__ uint32_t this_launch() { return ld_rlx(&g_epoch[fresh_bid()][0]) + 1; }
__device__ __forceinline__ bool flag_up(int stage, int b, uint32_t target) { return (int)(ld_rlx(flag_ptr(stage, b)) - target) >= 0; }
__device__ __forceinline__ void flag_wait(int stage, int b, uint32_t target) {
    [[maybe_unused]] int n = 0;
    while (!flag_up(stage, b, target)) {
        __nanosleep(20);
        SPIN_CHECK(n, 10 + stage);
    }
    fence_acq_gpu();
    fence_async_glb();
}
__device__ __forceinline__ void publish(int stage, int b) {
    fence_async_glb();
    fence_rel_gpu();
    red_add_u32(flag_ptr(stage, b), 1);
}
__device__ __forceinline__ uint32_t unit_frag_addr(int tid) {
    const int lane = tid & 31, w = (tid >> 5) & 3, i = lane & 7, j = lane >> 3;
    return ((j >> 1) * 8 + i) * 128 + ((((w << 1) + (j & 1)) ^ i) << 4);
}

#define V_BURST1 2
#define V_BURST2 1
#define V_PRE 8
#define SX_BF16 0
#define WO_MODE 0
#define V_LEAD 9
static_assert(V_BURST1 + V_BURST2 >= 2 && V_LEAD > V_BURST1 + V_BURST2, "q and k rely on v for the arrival of the blocks");
#define K_LEAD 0
#define Q_LEAD 36
#define V_FIRST 12
#define SX_GATE 1
#define PVX_LATE 1
#define V_EARLY 0
#define VM_EARLY 0
__host__ __device__ constexpr int x_order(int mat, int j) {
    return mat == 2 ? j : j < 2 ? j + 2 : j == 2 ? 8 : j == 3 ? 6 : j < 6 ? j : j == 6 ? 7 : 8 - j;
}
#define SS0Q 0
#define SS0K 0
#define SS0V 22
#define SSLQ 36
#define SSLK 36
#define SSLV 14
__host__ __device__ constexpr uint64_t ss_mask(int mat) {
    const int ns = 36 - (mat == 0 ? NRQ : mat == 1 ? NRK : NRV);
    const int j0 = mat == 0 ? SS0Q : mat == 1 ? SS0K : SS0V, len = mat == 0 ? SSLQ : mat == 1 ? SSLK : SSLV;
    uint64_t m = 0;
    for (int j = j0; j < j0 + len; j++)
        if ((j - j0) * ns / len != (j - j0 + 1) * ns / len) m |= 1ull << (x_order(mat, j >> 2) * 4 + (j & 3));
    return m;
}
__device__ __forceinline__ int popc_below(uint64_t m, int k) { return __popcll(m & ((1ull << k) - 1)); }
__host__ __device__ constexpr int x_slot(int f) {
    return f == 0 || f == 6 || f == 9 ? E_R0 : f == 1 || f == 7 ? E_R2 : f < 4 ? E_MEM + (f - 2) * 8192 : f == 4 ? E_QT : f == 5 ? E_KT : f == 8 ? E_VP : E_R1;
}
__host__ __device__ constexpr int x_empty(int blk) { return blk == 3 ? 0 : blk == 6 ? 1 : blk == 5 ? 2 : -1; }
__host__ __device__ constexpr int ar_tile(int j) { return WO_MODE == 2 ? (j == 8 ? 8 : (j & 1) * 4 + (j >> 1)) : j == 0 ? 8 : ((j - 1) & 1) * 4 + ((j - 1) & 2) + (j > 4); }
__host__ __device__ constexpr int sx_off(int u) { return u == 0 ? 0 : u == 1 ? 1536 : u == 2 ? 2560 : u == 3 ? 3072 : 5120; }

template <int MAT, int NR, int K0, int K1>
__device__ __forceinline__ void proj_mem(float* d, const uint32_t (&w)[NR][4]) {
    constexpr uint64_t M = ss_mask(MAT);
    const uint64_t db = mkdesc(E_MEM, 128, 9216, 0);
    const uint64_t da = mkdesc((MAT == 0 ? E_WQ : MAT == 1 ? E_WK : E_WV), 1024, 1024, 1);
#pragma unroll
    for (int ks = K0; ks < K1; ks++) {
        const int s = popc_below(M, ks);
        if ((M >> ks) & 1) wg_ss16(d, da + s * 128, db + ks * 16, ks > 0);
        else wg_rs16(d, w[ks - s], db + ks * 16, ks > 0);
    }
}
__device__ __forceinline__ uint32_t tl_lane(int tid, int group_bytes) {
    return ((tid >> 4) & 1) * group_bytes + (((tid >> 5) & 3) * 16 + (tid & 15)) * 16;
}
struct ArWords {
    uint32_t w[5];
    __device__ __forceinline__ ArWords(const float* y) {
        w[0] = pack2(y[0], y[1]); w[1] = pack2(y[2], y[3]); w[2] = pack2(y[4], y[5]); w[3] = pack2(y[6], 1.f); w[4] = pack2(y[7], 1.f);
    }
    __device__ __forceinline__ void force(uint32_t zero) {
        asm volatile("{.reg .pred p; setp.ne.u32 p, %0, 0; @p st.shared.v4.b32 [%5], {%1,%2,%3,%4};}" :: "r"(zero), "r"(w[0]), "r"(w[1]), "r"(w[2]), "r"(w[3]), "r"(w[4]) : "memory");
    }
    __device__ __forceinline__ void red(uint8_t* p, uint8_t* q) {
        asm volatile("red.relaxed.gpu.global.add.noftz.v4.bf16x2 [%0], {%1,%2,%3,%4};" :: "l"(p), "r"(w[0]), "r"(w[1]), "r"(w[2]), "r"(w[3]) : "memory");
        asm volatile("red.relaxed.gpu.global.add.noftz.bf16x2 [%0], %1;" :: "l"(q), "r"(w[4]) : "memory");
    }
};
__device__ __forceinline__ uint32_t ar_main(int tid) { return ((tid & 127) >> 3) * AR_STR + (tid & 7) * 16; }
__device__ __forceinline__ uint32_t ar_side(int tid) { return ((tid & 127) >> 5) * (4 * AR_STR) + AR_STR / 2 + (tid & 31) * 4; }

#define AR_LDQ 2
#define AR_LDK 2
#define AR_STQ 6
#define AR_STK 5
#define AR_VWAIT 1
#define AR_J1 3
#define AR_J2 5
template <int MAT> struct ArPart {
    static constexpr int J0 = MAT == 0 ? 0 : MAT == 1 ? AR_J1 : AR_J2, J1 = MAT == 0 ? AR_J1 : MAT == 1 ? AR_J2 : 9;
    uint4 av[J1 - J0];
    uint32_t as[J1 - J0];
    __device__ __forceinline__ void load(int i, int tid) {
        const uint8_t* pm = g_ar + ((i & 3) * AR_SLOT + ar_main(tid));
        const uint8_t* ps = g_ar + ((i & 3) * AR_SLOT + ar_side(tid));
#pragma unroll
        for (int j = J0; j < J1; j++) { av[j - J0] = ld_rlx128(pm + ar_tile(j) * (16 * AR_STR)); as[j - J0] = ld_rlx(ps + ar_tile(j) * (16 * AR_STR)); }
    }
    __device__ __forceinline__ void first_load(int i, int tid) {
        const uint8_t* pm = g_ar + ((i & 3) * AR_SLOT + ar_main(tid));
        const uint8_t* ps = g_ar + ((i & 3) * AR_SLOT + ar_side(tid));
#pragma unroll
        for (int j = 0; j < J1 - J0; j++) {
            av[j] = make_uint4(0, 0, 0, 0); as[j] = 0;
            asm volatile("{.reg .pred p; setp.ge.s32 p, %7, 0; @p ld.relaxed.gpu.global.v4.u32 {%0,%1,%2,%3}, [%5]; @p ld.relaxed.gpu.global.u32 %4, [%6];}"
                         : "+r"(av[j].x), "+r"(av[j].y), "+r"(av[j].z), "+r"(av[j].w), "+r"(as[j])
                         : "l"(pm + ar_tile(J0 + j) * (16 * AR_STR)), "l"(ps + ar_tile(J0 + j) * (16 * AR_STR)), "r"(i) : "memory");
        }
    }
    __device__ __forceinline__ bool complete(uint32_t one = 1) {
        bool ok = true;
#pragma unroll
        for (int j = J0; j < J1; j++) {
            ok &= __byte_perm(av[j - J0].w, as[j - J0], 0x7631 + one) == (ar_tile(j) == 8 ? 0x42804280u : 0x42004200u);
            av[j - J0].w = __byte_perm(av[j - J0].w, as[j - J0], 0x540f + one);
        }
        return __all_sync(~0u, ok);
    }
    __device__ __forceinline__ void store(const Params& P, int i, int tid) {
        [[maybe_unused]] int n = 0;
        const uint32_t one = MAT != 2 || !AR_VWAIT ? mbar_wait(bars + EB_EMPTY * 8, (i & 1) ^ 1) : 1;
        if (__builtin_expect(!complete(one) || i + 1 == LAG, 0)) {
            if (i >= 0) do { load(i, pin(tid << P.zero)); SPIN_CHECK(n, 2); PROF_INC(n, 1); } while (!complete());
            if (i < 0 || i + 1 == LAG) {
                const uint16_t* m = (const uint16_t*)P.mem0 + (tid & 3) * (2 * DM) + ((tid >> 5) & 3) * 16 + ((tid & 31) >> 2);
#pragma unroll
                for (int j = J0; j < J1; j++) {
                    const int f = ar_tile(j) * 64;
                    av[j - J0].z = (uint32_t)__ldg(m + f) | ((uint32_t)__ldg(m + f + DM) << 16);
                    av[j - J0].w = (uint32_t)__ldg(m + f + 8) | ((uint32_t)__ldg(m + f + DM + 8) << 16);
                    if (i < 0) { av[j - J0].x = av[j - J0].z; av[j - J0].y = av[j - J0].w; }
                }
            }
        }
        const uint32_t a = sb + E_MEM + tl_lane(tid, 9216);
#pragma unroll
        for (int j = J0; j < J1; j++) stsm4(a + ar_tile(j) * 1024, av[j - J0].x, av[j - J0].y, av[j - J0].z, av[j - J0].w);
    }
};

__device__ __forceinline__ void attn_mem(float* d, uint32_t par, int i, int tid) {
    const int lane = tid & 31, warp = tid >> 5, c = warp >> 1, hf = warp & 1;
    const int rank = cta_rank();
    const uint32_t peer = mapa(sb, rank ^ 1);
    const uint32_t l4 = (lane >> 4) * 1024 + (lane & 15) * 16;
    uint32_t kb[4][4];
    mbar_wait(bars + EB_WO * 8, 0);
    mbar_wait_cl(bars + EB_VX * 8, par);
    if (VM_EARLY) mbar_wait_cl(bars + EB_VM * 8, par);
    mbar_wait(bars + EB_STEP * 8, par);
    {
        const uint32_t aK = sb + E_KT + (c * 6 + hf * 2) * 1024 + l4;
#pragma unroll
        for (int ks = 0; ks < 4; ks++) ldsm4t(kb[ks], aK + ks * 256);
    }
    const uint32_t aQs = pin(sb + E_QM + tl_lane(tid, 1024));
    const uint32_t aQ = pin(sb + E_QM + c * 1024 + (((lane >> 3) & 1) * 16 + (lane >> 4) * 8 + (lane & 7)) * 16);
    const uint32_t aM = pin(sb + E_KT + (4 + c) * 1024 + lane * 16);
    const uint32_t oS = pin(tid * 16);
    const uint32_t aV = pin(sb + (hf == rank ? E_VT + c * 6144 : E_VP + c * 4096) + l4);
    wg_wait_acc<0, 8>(d);
    stsm4(aQs, pack2(d[0], d[1]), pack2(d[2], d[3]), pack2(d[4], d[5]), pack2(d[6], d[7]));
    nbar_sync(NB_QK, 256);
    TS(0, i, 1);
    float s[6];
    {
        uint32_t q[2][4], km[2][4];
        ldsm4t(q[0], aQ); ldsm4t(km[0], aM); ldsm4t(q[1], aQ + 512); ldsm4t(km[1], aM + 512);
        float a[6][4];
#pragma unroll
        for (int m = 0; m < 6; m++) a[m][0] = a[m][1] = a[m][2] = a[m][3] = 0.f;
#pragma unroll
        for (int j = 0; j < 2; j++) {
#pragma unroll
            for (int o = 0; o < 2; o++) {
                mma16816(a[o * 3], q[j], kb[2 * j + o][0], kb[2 * j + o][1]);
                mma16816(a[o * 3 + 1], q[j], kb[2 * j + o][2], kb[2 * j + o][3]);
            }
            mma16816(a[2], q[j], km[j][0], km[j][1]);
            mma16816(a[5], q[j], km[j][2], km[j][3]);
        }
        nbar_arrive(NB_S, 256);
        if (SX_GATE) nbar_arrive(NB_S2, 256);
#pragma unroll
        for (int m = 0; m < 3; m++) { s[2 * m] = a[m][0] + a[3 + m][2]; s[2 * m + 1] = a[m][1] + a[3 + m][3]; }
    }
    st_async128(peer + E_SR + oS, fu(s[0]), fu(s[1]), fu(s[2]), fu(s[3]), peer + SM_BAR + EB_SM * 8);
    const uint32_t oM = E_SR + 2048 + c * 256 + lane * 8;
    asm volatile("st.async.shared::cluster.mbarrier::complete_tx::bytes.b32 [%0], %1, [%2];"
                 :: "r"(peer + oM + hf * 4), "r"(fu(hf ? s[5] : s[4])), "r"(peer + SM_BAR + EB_SM * 8) : "memory");
    sts128(sb + E_SL + oS, fu(s[0]), fu(s[1]), fu(s[2]), fu(s[3]));
    mbar_arrive_warp(bars + EB_KF * 8);
    TS(0, i, 2);
#pragma unroll
    for (int T = 0; T < 4; T++) ldsm4(kb[T], aV + hf * 2048 + T * 256);
    nbar_sync(NB_G, 128);
    const uint32_t aO = sb + E_OM + c * OM_STR + (hf * 64 + lane) * 16;
    const uint32_t aR = sb + E_SR + oS, aR1 = sb + E_SR + (oS ^ 512), aRm = sb + oM, aV1 = aV + (hf ^ 1) * 2048;
    const uint4 l1 = lds128(aR1 + (E_SL - E_SR));
    mbar_wait_cl(bars + EB_SM * 8, par);
    TS(0, i, 3);
    float p[10];
    {
        const uint4 r0 = lds128(aR), r1 = lds128(aR1);
        const uint2 rm = lds64(aRm);
        p[0] = s[0] + uf(r0.x); p[1] = s[1] + uf(r0.y); p[2] = s[2] + uf(r0.z); p[3] = s[3] + uf(r0.w);
        p[4] = uf(l1.x) + uf(r1.x); p[5] = uf(l1.y) + uf(r1.y); p[6] = uf(l1.z) + uf(r1.z); p[7] = uf(l1.w) + uf(r1.w);
        p[8] = s[4] + uf(rm.x); p[9] = s[5] + uf(rm.y);
    }
    float mx = fmaxf(fmaxf(fmaxf(p[0], p[1]), fmaxf(p[2], p[3])), fmaxf(fmaxf(fmaxf(p[4], p[5]), fmaxf(p[6], p[7])), fmaxf(p[8], p[9])));
    mx = fmaxf(mx, __shfl_xor_sync(~0u, mx, 1));
    mx = fmaxf(mx, __shfl_xor_sync(~0u, mx, 2));
    const float mo = mx * (SM_SCALE * LOG2E);
    uint32_t pb[5];
    float o[5][4];
    const uint32_t ones[4] = {0x3f803f80u, 0x3f803f80u, 0x3f803f80u, 0x3f803f80u};
#pragma unroll
    for (int m = 0; m < 2; m++) pb[m] = pack2(ex2(fmaf(p[2 * m], SM_SCALE * LOG2E, -mo)), ex2(fmaf(p[2 * m + 1], SM_SCALE * LOG2E, -mo)));
#pragma unroll
    for (int T = 0; T < 5; T++) o[T][0] = o[T][1] = o[T][2] = o[T][3] = 0.f;
    mma16816(o[4], ones, pb[0], pb[1]);
#pragma unroll
    for (int T = 0; T < 4; T++) { mma16816(o[T], kb[T], pb[0], pb[1]); ldsm4(kb[T], aV1 + T * 256); }
#pragma unroll
    for (int m = 2; m < 5; m++) pb[m] = pack2(ex2(fmaf(p[2 * m], SM_SCALE * LOG2E, -mo)), ex2(fmaf(p[2 * m + 1], SM_SCALE * LOG2E, -mo)));
    if (!VM_EARLY) mbar_wait_cl(bars + EB_VM * 8, par);
    uint2 vm[4];
#pragma unroll
    for (int T = 0; T < 4; T++) vm[T] = lds64(sb + E_VF + hf * 2048 + lane * 16 + c * 8 + T * 512);
    mma16816(o[4], ones, pb[2], pb[3]);
#pragma unroll
    for (int T = 0; T < 4; T++) mma16816(o[T], kb[T], pb[2], pb[3]);
    mma1688(o[4], ones[0], ones[1], pb[4]);
#pragma unroll
    for (int T = 0; T < 4; T++) mma1688(o[T], vm[T].x, vm[T].y, pb[4]);
    nbar_arrive(NB_PV, 256);
    mbar_arrive_warp(bars + EB_CONS * 8);
    const float i0 = rcp(o[4][0]), i1 = rcp(o[4][1]);
#pragma unroll
    for (int j = 0; j < 2; j++)
        stsm4(aO + j * 512, pack2(o[2 * j][0] * i0, o[2 * j][1] * i1), pack2(o[2 * j][2] * i0, o[2 * j][3] * i1),
              pack2(o[2 * j + 1][0] * i0, o[2 * j + 1][1] * i1), pack2(o[2 * j + 1][2] * i0, o[2 * j + 1][3] * i1));
}

__device__ __forceinline__ void attn_x_scores(float (&p)[2][10], uint32_t par, int i, int tid) {
    {
        float s[40];
        const uint64_t da = mkdesc(E_QT, 128, 1024, 0), db = mkdesc(E_KT, 128, 1024, 0);
        wg_fence();
#pragma unroll
        for (int ks = 0; ks < 4; ks++) wg_ss80(s, da + ks * 16, db + ks * 16, ks > 0);
        wg_commit();
        const int dq = (tid >> 2) - 2 * (tid & 3);
        float mask[8];
#pragma unroll
        for (int j = 0; j < 8; j++) mask[j] = (j >> 1) * 8 + (j & 1) > dq ? -1e9f * LOG2E : 0.f;
        mbar_wait_cl(bars + EB_PRDY2 * 8, par);
        wg_wait_acc<0, 40>(s);
#pragma unroll
        for (int u = 0; u < 5; u++) {
            const int v = u < 4 ? 6 + u : 5;
            constexpr float C = SM_SCALE * LOG2E;
            const float m0 = u < 4 ? mask[2 * u & 7] : 0.f, m1 = u < 4 ? mask[(2 * u + 1) & 7] : 0.f;
            p[0][2 * u] = fmaf(s[4 * u], C, m0); p[0][2 * u + 1] = fmaf(s[4 * u + 1], C, m1); p[1][2 * u] = fmaf(s[4 * v + 2], C, m0); p[1][2 * u + 1] = fmaf(s[4 * v + 3], C, m1);
        }
    }
    mbar_arrive_warp(bars + EB_QF * 8);
    const int w = tid >> 5;
    if (!SX_BF16) {
        const uint32_t peer = mapa(sb, cta_rank() ^ 1);
#pragma unroll
        for (int u = 0; u < 5; u++)
            if (u == 0 || u <= w || u == 4) st_async128(peer + E_SX + sx_off(u) + tid * 16, fu(p[0][2 * u]), fu(p[0][2 * u + 1]), fu(p[1][2 * u]), fu(p[1][2 * u + 1]), peer + SM_BAR + EB_SX * 8);
    } else {
        const uint32_t peer = mapa(sb, cta_rank() ^ 1), a = peer + E_SX + tid * 16, mb = peer + SM_BAR + EB_SX * 8;
        st_async128(a, pack2(p[0][0], p[0][1]), pack2(p[1][0], p[1][1]), pack2(p[0][8], p[0][9]), pack2(p[1][8], p[1][9]), mb);
        if (w >= 1) st_async128(a + 2048, pack2(p[0][2], p[0][3]), pack2(p[1][2], p[1][3]), pack2(p[0][4], p[0][5]), pack2(p[1][4], p[1][5]), mb);
        if (w >= 3) st_async64(a + 4096, pack2(p[0][6], p[0][7]), pack2(p[1][6], p[1][7]), mb);
    }
    TS(128, i, 10);
}
__device__ __forceinline__ void attn_x_finish(float (&p)[2][10], uint32_t par, int i, int& tid, uint32_t zero) {
    const int w = tid >> 5;
    mbar_wait_cl(bars + EB_SX * 8, par);
    TS(128, i, 11);
    if (SX_BF16) {
        const uint32_t a = sb + E_SX + tid * 16;
        const uint4 r0 = lds128(a), r1 = lds128(a + (w >= 1 ? 2048 : 0));
        const uint2 r2 = lds64(a + (w >= 3 ? 4096 : 0));
        const uint32_t r[10] = {r0.x, r0.y, r1.x, r1.y, r1.z, r1.w, r2.x, r2.y, r0.z, r0.w};
#pragma unroll
        for (int j = 0; j < 10; j++) { p[j & 1][j & ~1] += bf_lo(r[j]); p[j & 1][j | 1] += bf_hi(r[j]); }
    } else
#pragma unroll
    for (int u = 0; u < 5; u++) {
        const uint4 r = lds128(pin(sb + tid * 16 + (u == 0 || u <= w ? sx_off(u) : sx_off(4))) + E_SX);
        p[0][2 * u] += uf(r.x); p[0][2 * u + 1] += uf(r.y); p[1][2 * u] += uf(r.z); p[1][2 * u + 1] += uf(r.w);
    }
    nbar_sync(NB_W, 128);
    uint32_t pa[5][4];
    float mx[2], inv[2];
#pragma unroll
    for (int h = 0; h < 2; h++) {
        const float* q = p[h];
        mx[h] = fmaxf(fmaxf(fmaxf(q[0], q[1]), fmaxf(q[2], q[3])), fmaxf(fmaxf(fmaxf(q[4], q[5]), fmaxf(q[6], q[7])), fmaxf(q[8], q[9])));
    }
#pragma unroll
    for (int o = 1; o < 4; o <<= 1) { mx[0] = fmaxf(mx[0], __shfl_xor_sync(~0u, mx[0], o)); mx[1] = fmaxf(mx[1], __shfl_xor_sync(~0u, mx[1], o)); }
#pragma unroll
    for (int h = 0; h < 2; h++) {
        float* q = p[h];
#pragma unroll
        for (int j = 0; j < 10; j++) q[j] = ex2(q[j] - mx[h]);
#pragma unroll
        for (int u = 0; u < 4; u++) {
            pa[h * 3 + (u >> 1)][(u & 1) * 2 + h] = pack2(q[2 * u], q[2 * u + 1]);
            pa[h * 3 + (u >> 1)][(u & 1) * 2 + (h ^ 1)] = zero << (h * 5 + u + 1);
        }
        pa[2][h * 3] = pack2(q[8], q[9]);
        pa[2][1 + h] = zero << (h * 5 + 5);
    }
    mbar_wait(bars + (PVX_LATE ? EB_CONS : EB_KF) * 8, par);
    fence_async_smem();
    tid = pin(tid << zero);
    const uint32_t aO = pin(sb + (((tid >> 4) & 1) * 8 + (tid & 7)) * 128 + (((((tid >> 3) & 1) * 4 + (tid >> 5)) ^ (tid & 7)) << 4)) + E_R1;
    TS(128, i, 12);
#pragma unroll
    for (int nh = 0; nh < 2; nh++) {
        float o[16], sum[4];
        const uint64_t db = mkdesc(E_VT + nh * 512, 1024, 128, 0);
        wg_fence();
#pragma unroll
        for (int kk = 0; kk < 5; kk++) {
            if (nh == 0) wg_rs8(sum, pa[kk], mkdesc(SM_ONES, 0, 0, 0), kk > 0);
            wg_rs32(o, pa[kk], db + kk * 128, kk > 0);
        }
        wg_commit();
        wg_wait_acc<0, 16>(o);
        if (nh == 0) { acc_ready<4>(sum); inv[0] = rcp(sum[0]); inv[1] = rcp(sum[2]); }
#pragma unroll
        for (int j = 0; j < 2; j++) {
            const float* y = &o[8 * j];
            stsm4t(aO + nh * 4096 + j * 2048, pack2(y[0] * inv[0], y[1] * inv[0]), pack2(y[2] * inv[1], y[3] * inv[1]), pack2(y[4] * inv[0], y[5] * inv[0]), pack2(y[6] * inv[1], y[7] * inv[1]));
        }
    }
    mbar_arrive_warp(bars + EB_OST * 8);
    TS(128, i, 13);
}

template <int MAT>
__device__ __forceinline__ void engine_main(const Params& P) {
    constexpr int NR = MAT == 0 ? NRQ : MAT == 1 ? NRK : NRV;
    constexpr uint64_t M = ss_mask(MAT);
    uint32_t w[NR][4];
    {
        const uint32_t a = sb + E_WO + (MAT == 0 ? 0 : MAT == 1 ? NRQ : NRQ + NRK) * 2048 + unit_frag_addr(fresh_tid());
        mbar_wait(bars + EB_WL * 8, 0);
        if (MAT == 0 && threadIdx.x == 0) TG(79, 2);
#pragma unroll
        for (int u = 0; u < NR; u++) ldsm4t(w[u], a + u * 2048);
    }
    nbar_arrive(NB_T, 448);
    int tid = fresh_tid() - MAT * 128;
#define TID (tid = pin(tid << P.zero))
    if (MAT == 0) { if (V_FIRST == 36) nbar_arrive(NB_S, 256); nbar_arrive(NB_PV, 256); nbar_arrive(NB_WO, 256); }
    auto project = [&](const int i) {
        const uint32_t par = i & 1;
        ArPart<MAT> ar;
        {
            float d[32];
            const uint64_t da = mkdesc((MAT == 0 ? E_WQ : MAT == 1 ? E_WK : E_WV), 1024, 1024, 1);
            constexpr int R1 = V_BURST1, R2 = V_BURST1 + V_BURST2;
#pragma unroll
            for (int n = 0; n < 9; n++) {
                const int blk = x_order(MAT, n), prev = n ? x_order(MAT, n - 1) : -1, f = MAT != 2 && blk < 2 ? 9 + blk : blk;
                if (MAT == 2) {
                    if (n == (R1 >= 2 ? R1 : R2)) { wg_wait<0>(); mbar_arrive_warp(bars + EB_V0 * 8); }
                    if ((n == 0 && (V_FIRST == 36 || i == 0)) || n == R1 || n == R2) {
#pragma unroll
                        for (int j = n; j < (n < R1 ? R1 : n < R2 ? R2 : V_PRE); j++) mbar_wait(bars + (EB_FULL + j) * 8, par);
                    }
                    if (n == 0 && V_FIRST == 36) nbar_sync(NB_S, 256);
                    if (n == R1) nbar_sync(NB_PV, 256);
                    if (n == R2) nbar_sync(NB_WO, 256);
                } else {
                    if (n == 0) nbar_sync(MAT ? NB_VL : NB_VL2, 256);
                }
                const bool wt = f >= (MAT == 2 || V_LEAD < V_PRE ? V_PRE : V_LEAD);
                if (wt) mbar_wait(bars + (EB_FULL + f) * 8, par);
                TX(MAT * 128, 1 + MAT * 9 + n);
                if (wt || n == 0 || (MAT == 2 ? n == R1 || n == R2 : n - 1 == (MAT ? AR_STK : AR_STQ))) wg_fence();
                if (n == 0) TS(MAT * 128, i, 20 + MAT);
                const uint64_t db = mkdesc(x_slot(f), 16, 1024, 1);
#pragma unroll
                for (int j = 0; j < 4; j++) {
                    const int ks = blk * 4 + j, s = popc_below(M, ks);
                    if ((M >> ks) & 1) wg_ss64<0>(d, da + s * 128, db + j * 2, n + j > 0);
                    else wg_rs64<0>(d, w[ks - s], db + j * 2, n + j > 0);
                }
                wg_commit();
                if (MAT == 2 && n + 1 == V_LEAD) { nbar_arrive(NB_VL, 256); if (!K_LEAD) nbar_arrive(NB_VL2, 256); }
                if (MAT == 1 && n + 1 == K_LEAD) nbar_arrive(NB_VL2, 256);
                if (MAT != 2 && n == (MAT ? AR_LDK : AR_LDQ)) { ar.first_load(i - 1, TID); }
                if (MAT != 2 && n == (MAT ? AR_STK : AR_STQ)) { ar.store(P, i - 1, TID); mbar_arrive_warp(bars + EB_MEM0 * 8); }
                if (MAT != 2 && x_empty(prev) >= 0) { wg_wait<1>(); mbar_arrive_warp(bars + (EB_EMPTY + x_empty(prev)) * 8); }
            }
            const uint32_t a = sb + (MAT == 0 ? E_QT : MAT == 1 ? E_KT : E_VT) + tl_lane(TID, MAT == 0 ? 2048 : 1024);
            if (MAT != 2) {
                mbar_wait(bars + (EB_EMPTY + 2) * 8, par);
                mbar_wait(bars + EB_MEM * 8, par);
            } else {
                mbar_wait(bars + EB_OST * 8, par ^ 1);
            }
            wg_wait_acc<0, 32>(d);
            TS(MAT * 128, i, 23 + MAT);
#pragma unroll
            for (int j = 0; j < 8; j += 2) {
                const int grp = MAT == 0 ? 2 * (j & 3) + (j >> 2) : j < 4 ? j : j + 2;
                stsm4(a + grp * 1024, pack2(d[4 * j], d[4 * j + 1]), pack2(d[4 * j + 2], d[4 * j + 3]), pack2(d[4 * j + 4], d[4 * j + 5]), pack2(d[4 * j + 6], d[4 * j + 7]));
            }
        }
        if (MAT != 2) {
            mbar_arrive_warp(bars + EB_STEP * 8);
        } else {
            __syncwarp();
            if ((TID & 31) < 3) mbar_arrive(bars + (EB_EMPTY + (tid & 31)) * 8);
            if (AR_VWAIT) mbar_wait(bars + EB_EMPTY * 8, par);
            ar.first_load(i - 1, TID);
            ar.store(P, i - 1, tid);
            TS(256, i, 19);
            mbar_wait(bars + EB_MEM0 * 8, par);
            fence_async_smem();
            mbar_arrive_warp(bars + EB_MEM * 8);
        }
    };
    auto step = [&](const int i) {
        const uint32_t par = i & 1;
        if (MAT == 2) {
            if (Q_LEAD) nbar_sync(NB_OM, 256);
            else mbar_wait(bars + EB_MEM * 8, par);
        }
        float d[8];
        TS(MAT * 128, i, MAT == 2 ? 26 : 14 + MAT);
        wg_fence();
        constexpr int MID = MAT == 0 ? Q_LEAD : MAT == 2 ? V_FIRST : 0;
        proj_mem<MAT, NR, 0, MID>(d, w);
        if (MAT == 0 && Q_LEAD) nbar_arrive(NB_OM, 256);
        if (MAT == 2 && V_FIRST < 36) {
#pragma unroll
            for (int j = 0; j < V_BURST1; j++) mbar_wait(bars + (EB_FULL + j) * 8, i == NSTEP - 1 ? par : par ^ 1);
            nbar_sync(NB_S, 256);
            wg_fence();
        }
        proj_mem<MAT, NR, MID, 36>(d, w);
        wg_commit();
        if (MAT == 0) {
            attn_mem(d, par, i, TID);
        } else if (MAT == 1) {
            tid *= mbar_wait(bars + EB_STEP * 8, par);
            const uint32_t a = pin(sb + E_KT + 4096 + tl_lane(tid, 1024));
            wg_wait_acc<0, 8>(d);
            stsm4(a, pack2(d[0], d[1]), pack2(d[2], d[3]), pack2(d[4], d[5]), pack2(d[6], d[7]));
            nbar_arrive(NB_QK, 256);
            TS(128, i, 18);
            fence_async_smem();
            nbar_sync(SX_GATE ? NB_S2 : NB_W, SX_GATE ? 256 : 128);
            float p[2][10];
            attn_x_scores(p, par, i, TID);
            attn_x_finish(p, par, i, TID, pin(P.zero));
        } else {
            const int rank = cta_rank();
            const uint32_t a = pin(sb + E_VT + 4096 + tl_lane(TID, 1024)), of = pin(E_VF + rank * 2048 + (tid & 127) * 16);
            const uint32_t peer = pin(mapa(sb, rank ^ 1));
            wg_wait_acc<0, 8>(d);
            const uint32_t v0 = pack2(d[0], d[1]), v1 = pack2(d[2], d[3]), v2 = pack2(d[4], d[5]), v3 = pack2(d[6], d[7]);
            st_async128(peer + of, v0, v1, v2, v3, peer + SM_BAR + EB_VM * 8);
            sts128(sb + of, v0, v1, v2, v3);
            stsm4(a, v0, v1, v2, v3);
            mbar_arrive_warp(bars + EB_VM * 8);
            mbar_arrive_warp(bars + EB_KF * 8);
            TS(256, i, 16);
        }
        if (MAT == 0) {
            const int rank = cta_rank();
            uint8_t* const ar = g_ar + (i & 3) * AR_SLOT;
            uint8_t* const pm = ar + pin(ar_main(TID) + rank * (64 * AR_STR));
            uint8_t* const ps = ar + pin(ar_side(tid) + rank * (64 * AR_STR));
            const uint32_t o8 = (128 - rank * 64) * AR_STR;
            const uint64_t db = mkdesc(E_OM, 128, OM_STR, 0), da = mkdesc(E_WO, 1024, 1024, 1);
            nbar_sync(NB_G, 128);
            fence_async_smem();
            TS(0, i, 6);
            if (i == NSTEP - 1) return;
            float y[4][8];
            wg_fence();
            if (WO_MODE == 2) {
#pragma unroll
                for (int T = 0; T < 4; T++) {
#pragma unroll
                    for (int ks = 0; ks < 8; ks++) wg_ss16(y[T], da + (T * 8 + ks) * 128, db + ks * 16, ks > 0);
                    wg_commit();
                }
                if (V_EARLY) nbar_arrive(NB_WO, 256);
                wg_wait_acc<2, 8>(y[0]); acc_ready<8>(y[1]);
                { ArWords z(y[0]); z.red(pm, ps); z.force(P.zero); }
                ArWords(y[1]).red(pm + 16 * AR_STR, ps + 16 * AR_STR);
                wg_wait_acc<1, 8>(y[2]);
                ArWords(y[2]).red(pm + 32 * AR_STR, ps + 32 * AR_STR);
                wg_fence();
#pragma unroll
                for (int ks = 0; ks < 4; ks++) wg_ss16(y[0], da + (32 + ks) * 128, db + (rank * 4 + ks) * 16, ks > 0);
                wg_commit();
                if (!V_EARLY) nbar_arrive(NB_WO, 256);
                wg_wait_acc<1, 8>(y[3]);
                ArWords(y[3]).red(pm + 48 * AR_STR, ps + 48 * AR_STR);
                wg_wait_acc<0, 8>(y[0]);
                ArWords(y[0]).red(pm + o8, ps + o8);
                return;
            }
#pragma unroll
            for (int ks = 0; ks < 4; ks++) wg_ss16(y[3], da + (32 + ks) * 128, db + (rank * 4 + ks) * 16, ks > 0);
            wg_commit();
#pragma unroll
            for (int ks = 0; ks < 8; ks++) wg_ss16(y[0], da + ks * 128, db + ks * 16, ks > 0);
            wg_commit();
            if (WO_MODE == 0) {
#pragma unroll
                for (int ks = 0; ks < 8; ks++) wg_ss16(y[2], da + (16 + ks) * 128, db + ks * 16, ks > 0);
                wg_commit();
                wg_wait_acc<2, 8>(y[3]);
                ArWords z(y[3]);
                z.force(P.zero);
                wg_fence();
#pragma unroll
                for (int ks = 0; ks < 8; ks++) wg_ss16(y[1], da + (8 + ks) * 128, db + ks * 16, ks > 0);
                wg_commit();
#pragma unroll
                for (int ks = 0; ks < 8; ks++) wg_ss16(y[3], da + (24 + ks) * 128, db + ks * 16, ks > 0);
                wg_commit();
                if (V_EARLY) nbar_arrive(NB_WO, 256);
                z.red(pm + o8, ps + o8);
                wg_wait_acc<2, 8>(y[2]); acc_ready<8>(y[0]);
                ArWords(y[0]).red(pm, ps);
                ArWords(y[2]).red(pm + 32 * AR_STR, ps + 32 * AR_STR);
            } else {
                wg_wait_acc<1, 8>(y[3]);
                { ArWords z(y[3]); z.red(pm + o8, ps + o8); z.force(P.zero); }
                wg_fence();
#pragma unroll
                for (int ks = 0; ks < 8; ks++) wg_ss16(y[2], da + (16 + ks) * 128, db + ks * 16, ks > 0);
                wg_commit();
                wg_wait_acc<1, 8>(y[0]);
                { ArWords z(y[0]); z.red(pm, ps); z.force(P.zero); }
                wg_fence();
#pragma unroll
                for (int ks = 0; ks < 8; ks++) wg_ss16(y[1], da + (8 + ks) * 128, db + ks * 16, ks > 0);
                wg_commit();
                wg_wait_acc<1, 8>(y[2]);
                { ArWords z(y[2]); z.red(pm + 32 * AR_STR, ps + 32 * AR_STR); z.force(P.zero); }
                wg_fence();
#pragma unroll
                for (int ks = 0; ks < 8; ks++) wg_ss16(y[3], da + (24 + ks) * 128, db + ks * 16, ks > 0);
                wg_commit();
                if (V_EARLY) nbar_arrive(NB_WO, 256);
            }
            wg_wait_acc<1, 8>(y[1]);
            ArWords(y[1]).red(pm + 16 * AR_STR, ps + 16 * AR_STR);
            wg_wait_acc<0, 8>(y[3]);
            ArWords(y[3]).red(pm + 48 * AR_STR, ps + 48 * AR_STR);
            if (!V_EARLY) nbar_arrive(NB_WO, 256);
            TS(0, i, 7);
        }
    };
    if (MAT != 2) {
#pragma unroll 1
        for (int i = 0; i < NSTEP; i++) { project(i); step(i); }
    } else {
#pragma unroll 1
        for (int i = -1; i < NSTEP; i++) {
            if (i >= 0) step(i);
            if (i < NSTEP - 1) project(i + 1);
        }
    }
    if (MAT == 2) { if (V_FIRST == 36) nbar_sync(NB_S, 256); nbar_sync(NB_PV, 256); }
}

__device__ __forceinline__ void engine_helper(const Params& P) {
    const int lane = threadIdx.x & 31, hw = warp_in_group(), e = blockIdx.x, rank = e & 1;
    if (hw < 3) {
        constexpr uint64_t M0 = ss_mask(0), M1 = ss_mask(1), M2 = ss_mask(2);
        const uint64_t m = hw == 0 ? M0 : hw == 1 ? M1 : M2;
        const uint32_t ws = sb + (hw == 0 ? E_WQ : hw == 1 ? E_WK : E_WV), wr = sb + E_WO + (hw == 0 ? 0 : hw == 1 ? NRQ : NRQ + NRK) * 2048;
        if (lane == 0) mbar_expect(bars + EB_WL * 8, 36 * 2048);
        __syncwarp();
        for (int ks = lane; ks < 36; ks += 32) {
            const int s = __popcll(m & ((1ull << ks) - 1));
            tma_unit(((m >> ks) & 1) ? ws + s * 2048 : wr + (ks - s) * 2048, hw == 0 ? &P.tmWq : hw == 1 ? &P.tmWk : &P.tmWv, ks, e, bars + EB_WL * 8);
        }
    }
    if (hw == 1) {
        hold_back(WO_DELAY);
        for (int u = lane; u < 36; u += 32)
            asm volatile("cp.async.bulk.prefetch.tensor.2d.L2.global [%0, {%1,%2}];"
                         :: "l"(&P.tmWo), "r"((u < 32 ? rank * 4 + (u >> 3) : 8) * 64), "r"(((e >> 1) * 8 + (u < 32 ? u & 7 : rank * 4 + (u & 3))) * 16) : "memory");
    }
    __syncwarp();
    if (hw < 2) nbar_sync(NB_T, 448);
    if (lane == 0) TG(79, 3);
    if (hw == 0) {
        if (lane == 0) {
            const uint32_t peer = mapa(sb, rank ^ 1);
#pragma unroll 1
            for (int n = 0; n < NSTEP; n++) {
                const uint32_t par = (n & 1) ^ 1;
                uint32_t rdy;
                do { asm volatile("ld.acquire.cta.shared.u32 %0, [%1];" : "=r"(rdy) : "r"(sb + SM_XRDY) : "memory"); } while (rdy <= n && (__nanosleep(20), true));
                fence_async_glb();
                TG(n, 30);
                const uint8_t* s0 = g_x0 + min(n, NSEG - 1) * XIMG;
                const uint8_t* s1 = n >= LAG ? g_x1 + (n - LAG) * XIMG : s0;
#pragma unroll
                for (int j = 0; j < 11; j++) {
                    const int f = j < 9 ? j : 19 - j, blk = f < 9 ? f : f - 9;
                    if (n > 0 && (f == 0 || f == 2 || f == 4 || f == 8 || f == 10))
                        mbar_wait(bars + (f == 0 ? EB_STEP : f == 2 ? EB_KF : f == 4 ? EB_QF : f == 8 ? EB_CONS : EB_OFREE) * 8, par);
                    if (f == 6 || f == 9) mbar_wait(bars + (f == 6 ? EB_V0 : EB_EMPTY + 1) * 8, par ^ 1);
                    const uint32_t fb = bars + (EB_FULL + f) * 8;
                    mbar_expect(fb, 8192);
                    bulk_g2s(sb + x_slot(f), s0 + blk * 4096, 4096, fb);
                    bulk_g2s(sb + x_slot(f) + 4096, s1 + blk * 4096, 4096, fb);
                }
                mbar_arrive_remote(peer + SM_BAR + EB_PRDY * 8);
            }
        }
    } else if (hw == 1) {
        if (lane == 0) mbar_expect(bars + EB_WO * 8, 36 * 2048);
        __syncwarp();
        for (int u = lane; u < 36; u += 32)
            tma_unit(sb + E_WO + u * 2048, &P.tmWo, (e >> 1) * 8 + (u < 32 ? u & 7 : rank * 4 + (u & 3)), u < 32 ? rank * 4 + (u >> 3) : 8, bars + EB_WO * 8);
        __syncwarp();
        if (lane == 0) {
#pragma unroll 1
            for (int i = 0; i < NSTEP; i++) {
                mbar_wait(bars + EB_STEP * 8, i & 1);
                mbar_arrive_remote(mapa(sb, rank ^ 1) + SM_BAR + EB_PRDY2 * 8);
                mbar_wait(bars + EB_OST * 8, i & 1);
                fence_async_smem();
                bulk_s2g(g_o + (i & (RING - 1)) * O_BYTES + e * 8192, sb + E_R1, 8192);
                asm volatile("cp.async.bulk.commit_group;" ::: "memory");
                asm volatile("cp.async.bulk.wait_group.read 0;" ::: "memory");
                mbar_arrive(bars + EB_OFREE * 8);
                asm volatile("cp.async.bulk.wait_group 0;" ::: "memory");
                publish(F_O, i);
                TG(i, 31);
            }
        }
    } else if (hw == 2) {
        const uint32_t peer = mapa(sb, rank ^ 1);
        const int idx = e * 23 + lane, line = idx >> 3;
        uint8_t* z = g_ar + (line < 144 ? line * AR_STR : (line - 144) * (4 * AR_STR) + AR_STR / 2) + (idx & 7) * 16;
        if (lane < 23 && idx < 1440) { stg128(z, make_uint4(0, 0, 0, 0)); stg128(z + AR_SLOT, make_uint4(0, 0, 0, 0)); }
        __syncwarp();
        if (lane == 0) {
            publish(F_X0, B_ZERO);
            mbar_arrive(bars + EB_MEM * 8);
            flag_wait(F_X0, B_ZERO, NENG * this_launch());
            mbar_arrive(bars + EB_WO * 8);
            TG(79, 5);
        }
        __syncwarp();
#pragma unroll 1
        for (int i = 0; i < NSTEP; i++) {
            mbar_wait(bars + EB_EMPTY * 8, i & 1);
            if (lane == 0) {
                mbar_wait_cl(bars + EB_PRDY * 8, i & 1);
                fence_async_smem();
                bulk_s2peer(peer + E_VP, sb + E_VT, 4096, peer + SM_BAR + EB_VX * 8);
                bulk_s2peer(peer + E_VP + 4096, sb + E_VT + 6144, 4096, peer + SM_BAR + EB_VX * 8);
                mbar_expect(bars + EB_VX * 8, 8192);
                mbar_expect(bars + EB_SX * 8, SX_BF16 ? 3840 : 7168);
                mbar_expect(bars + EB_SM * 8, 2560);
                mbar_expect(bars + EB_VM * 8, 2048);
            }
            __syncwarp();
            mbar_wait(bars + EB_MEM * 8, i & 1);
            if (lane < 23 && idx < 1440) stg128(z + ((i + 2) & 3) * AR_SLOT, make_uint4(0, 0, 0, 0));
            __syncwarp();
            if (lane == 0) { fence_gpu(); mbar_arrive(bars + EB_MEM * 8); }
            __syncwarp();
        }
    } else {
        for (int j = lane; j < 72; j += 32) asm volatile("prefetch.global.L2 [%0];" :: "l"(P.mem0 + j * 64));
        const uint32_t ep = this_launch(), t0 = timer_lo();
        if (lane == 0) {
#pragma unroll 1
            for (int n = 0; n < NSTEP; n++) {
                while ((n < NSEG && !flag_up(F_X0, n, 16 * ep)) || (n >= LAG && !flag_up(F_X1, n - LAG, 16 * ep))) {
                    __nanosleep(20);
                    if (timer_lo() - t0 > TIME_LIMIT) break;
                }
                fence_acq_gpu();
                asm volatile("st.release.cta.shared.u32 [%0], %1;" :: "r"(sb + SM_XRDY), "r"(n + 1) : "memory");
            }
        }
    }
    __syncwarp();
}

__device__ __forceinline__ void f1_fetch(const Params& P, uint32_t dst, int f0, int ks0, int n) {
    const int tid = threadIdx.x & 127, r = tid >> 3, c = (tid & 3) * 2 + ((tid >> 2) & 1);
    const bf16* src = ((c & 1) ? P.w3 : P.w1) + (size_t)(ks0 * 16 + r) * FF + f0 + (c >> 1) * 8;
    dst += r * 128 + ((c ^ (r & 7)) << 4);
#pragma unroll 1
    for (int u = 0; u < n; u++) {
        asm volatile("cp.async.cg.shared.global [%0], [%1], 16;" :: "r"(dst + u * 2048), "l"(src + (size_t)u * 16 * FF) : "memory");
        asm volatile("cp.async.commit_group; cp.async.wait_group %0;" :: "n"(F1_DEPTH) : "memory");
    }
}
constexpr int R_BACKLOG = 6;
static_assert(R_BACKLOG <= RING, "the partial sums would be overwritten");
#define F1_LEAD 0
template <int a, bool second>
__device__ __forceinline__ void f1_tile(const uint32_t (&w)[NRF][4], uint32_t ws, int b) {
    constexpr bool RF = (a == 1) == second;
    const uint32_t par = b & 1;
    float d[32];
    const uint64_t da = mkdesc(ws, 1024, 1024, 1), db = mkdesc(F_X, 16, 1024, 1);
#pragma unroll
    for (int blk = 0; blk < 9; blk++) {
        if (a == 1 && !second && blk == 0 && F1_LEAD) nbar_sync(NB_QK, 256);
        const bool wt = blk == 0 || (!second && (a == 0 || blk >= F1_LEAD));
        if (wt) { mbar_wait(bars + (FB_FULL + blk) * 8, par); wg_fence(); }
#pragma unroll
        for (int j = 0; j < 4; j++) {
            const int ks = blk * 4 + j;
            if (RF && ks < NRF) wg_rs64<0>(d, w[ks < NRF ? ks : 0], db + blk * 512 + j * 2, ks > 0);
            else wg_ss64<0>(d, da + (RF ? ks - NRF : 36 - NRF + ks) * 128, db + blk * 512 + j * 2, ks > 0);
        }
        wg_commit();
        if (a == 0 && !second && blk + 1 == F1_LEAD) nbar_arrive(NB_QK, 256);
        if (blk > 0 && second) { wg_wait<1>(); mbar_arrive_warp(bars + (FB_EMPTY + blk - 1) * 8); }
    }
    const int tid = fresh_tid(), g = (tid & 31) >> 2;
    uint8_t* dst = g_h + (b & (RING - 1)) * H_BYTES + ((fresh_bid() - NENG + (second ? 37 : 0)) * 64 + a * 32 + ((tid >> 5) & 3) * 8 + g) * 128;
    if (!second) mbar_wait(bars + FB_RACK * 8, par ^ 1);
    wg_wait_acc<0, 32>(d);
    if (second) mbar_arrive_warp(bars + (FB_EMPTY + 8) * 8);
    uint32_t h[8];
#pragma unroll
    for (int j = 0; j < 8; j++) {
        const float g0 = d[4 * j], g1 = d[4 * j + 1];
        const float e0 = 1.f + ex2(fminf(-LOG2E * g0, 60.f)), e1 = 1.f + ex2(fminf(-LOG2E * g1, 60.f));
        const float r = rcp(e0 * e1);
        h[j] = pack2(g0 * d[4 * j + 2] * (e1 * r), g1 * d[4 * j + 3] * (e0 * r));
    }
    stg128(dst + (((tid & 3) ^ g) << 4), make_uint4(h[0], h[1], h[2], h[3]));
    stg128(dst + ((((tid & 3) + 4) ^ g) << 4), make_uint4(h[4], h[5], h[6], h[7]));
    mbar_arrive_warp(bars + (second ? FB_H2 : FB_H) * 8);
}
template <int a>
__device__ __forceinline__ void f1_main(const Params& P) {
    constexpr uint32_t ws = F_W + a * (72 - NRF) * 2048;
    const int f0 = (blockIdx.x - NENG) * 128 + a * 96;
    uint32_t w[NRF][4];
    hold_back(F1_DELAY);
    f1_fetch(P, sb + ws, f0, 0, NRF);
    asm volatile("cp.async.wait_all;" ::: "memory");
    nbar_sync(NB_G + a, 128);
    {
        const uint32_t fa = sb + ws + unit_frag_addr(threadIdx.x);
#pragma unroll
        for (int u = 0; u < NRF; u++) ldsm4t(w[u], fa + u * 2048);
    }
    nbar_sync(NB_G + a, 128);
    f1_fetch(P, sb + ws, f0, NRF, 36 - NRF);
    f1_fetch(P, sb + ws + (36 - NRF) * 2048, f0 + (a ? -64 : 64), 0, 36);
    asm volatile("cp.async.wait_all;" ::: "memory");
    fence_async_smem();
    nbar_sync(NB_G + a, 128);
    if (threadIdx.x == 0) TG(79, 2);
#pragma unroll 1
    for (int b = 0; b < NSTEP; b++) {
        f1_tile<a, false>(w, ws, b);
        f1_tile<a, true>(w, ws, b);
    }
}
__device__ __forceinline__ uint32_t n_pairs(int b) { return (b < NSEG ? 16 : 0) + (b >= LAG ? 16 : 0); }
__device__ __forceinline__ void publisher(uint32_t done, uint32_t ack, int stage) {
#pragma unroll 1
    for (int b = 0; b < NSTEP; b++) {
        if (stage == F_H2) { mbar_wait(done - 8, b & 1); publish(F_H, b); }
        mbar_wait(done, b & 1);
        mbar_arrive(ack);
        TG(b, 30);
        publish(stage, b);
        TG(b, 31);
    }
}
__device__ __forceinline__ void f1_helper(const Params& P) {
    const int hw = warp_in_group();
    if ((threadIdx.x & 31) == 0) {
        const bool chain = blockIdx.x >= NENG + 16;
        if (hw == 0) {
            const uint32_t ep = this_launch();
#pragma unroll 1
            for (int b = 0; b < NSTEP; b++) {
                flag_wait(F_XF, b, n_pairs(b) * ep);
                TG(b, 29);
                const uint8_t* src = g_xf + (b & (RING - 1)) * (9 * 8192);
#pragma unroll 1
                for (int blk = 0; blk < 9; blk++) {
                    mbar_wait(bars + (FB_EMPTY + blk) * 8, (b & 1) ^ 1);
                    mbar_expect(bars + (FB_FULL + blk) * 8, 8192);
                    bulk_g2s(sb + F_X + blk * 8192, src + blk * 8192, 8192, bars + (FB_FULL + blk) * 8);
                }
            }
        } else if (hw == 1) {
            const uint32_t ep = this_launch();
            int b1 = chain ? LAG : 0, b2 = b1;
            const int bend = b1 + NSEG;
            bool second = true;
#pragma unroll 1
            for (int j = blockIdx.x < NENG + 32 ? 0 : 2 * NSEG; j < 2 * NSEG; j++) {
                [[maybe_unused]] int n = 0;
                const bool may1 = b1 < bend && b1 < b2 + R_BACKLOG;
                bool may2 = !chain || !second || !may1, any;
                do {
                    const bool r1 = flag_up(F_P1, b1, 15 * ep) & may1, r2 = flag_up(F_P2, b2, 17 * ep) & may2;
                    second = chain ? !r1 : r2;
                    any = r1 | r2;
                    may2 = !chain || !may1;
                    SPIN_CHECK(n, 20);
                } while (!any);
                fence_acq_gpu();
                TG(second ? b2 : b1, 25 + 2 * second);
                sts32(sb + F_RED + 192 + (j & 1) * 4, second ? b2 + 256 : b1);
                mbar_arrive(bars + FB_JOB * 8);
                if (second) b2++; else b1++;
                mbar_wait(bars + FB_JOB * 8, j & 1);
            }
        } else if (hw == 2) {
#pragma unroll 1
            for (int j = blockIdx.x < NENG + 32 ? 0 : 2 * NSEG; j < 2 * NSEG; j++) {
                if (j == 0) mbar_arrive(bars + FB_JOB * 8);
                mbar_wait(bars + FB_RDONE * 8, j & 1);
                const int job = lds32(sb + F_RED + 192 + (j & 1) * 4);
                mbar_arrive(bars + FB_JOB * 8);
                TG(job & 255, 23 + (job >> 8));
                if (job < 256 || !chain) publish(job < 256 ? F_XF : F_X1, job & 255);
                TG(job & 255, 26 + 2 * (job >> 8));
            }
        } else {
            hold_back(PF_DELAY);
#pragma unroll 1
            for (int j = 0; j < 24; j++) {
                const bf16* w = j >= 16 ? P.w2 : (j & 1) ? P.w3 : P.w1;
                asm volatile("cp.async.bulk.prefetch.L2.global [%0], %1;" :: "l"(w + (size_t)((j >= 16 ? j - 16 : j >> 1) * NF1 + blockIdx.x - NENG) * (2 * FF)), "r"(4 * FF) : "memory");
                hold_back(PF_PACE);
            }
            publisher(bars + FB_H2 * 8, bars + FB_RACK * 8, F_H2);
        }
    }
    __syncwarp();
}

__device__ __forceinline__ void add8(float* f, uint4 a) {
    f[0] += bf_lo(a.x); f[1] += bf_hi(a.x); f[2] += bf_lo(a.y); f[3] += bf_hi(a.y);
    f[4] += bf_lo(a.z); f[5] += bf_hi(a.z); f[6] += bf_lo(a.w); f[7] += bf_hi(a.w);
}
__device__ __forceinline__ void set8(float* f, uint4 a) {
    f[0] = bf_lo(a.x); f[1] = bf_hi(a.x); f[2] = bf_lo(a.y); f[3] = bf_hi(a.y);
    f[4] = bf_lo(a.z); f[5] = bf_hi(a.z); f[6] = bf_lo(a.w); f[7] = bf_hi(a.w);
}
__device__ __forceinline__ void ln0_rows(const Params& P, int r) {
    const int lane = threadIdx.x & 31, l = lane < 24 ? lane : 0;
    const uint4* xrow = (const uint4*)(P.x + r * DM) + l;
    uint4 xw[3];
#pragma unroll
    for (int k = 0; k < 3; k++) xw[k] = __ldg(xrow + 24 * k);
    asm volatile("prefetch.global.L2 [%0];" :: "l"(P.x + (r + 16) * DM + (lane < 9 ? lane : 0) * 64));
#pragma unroll 1
    for (int seg = 0; seg < NSEG; seg++) {
#pragma unroll 1
        for (int h = 0; h < 2; h++) {
            float f[24];
#pragma unroll
            for (int k = 0; k < 3; k++) set8(&f[k * 8], xw[k]);
            if (2 * seg + h + 1 < 2 * NSEG) {
#pragma unroll
                for (int k = 0; k < 3; k++) xw[k] = __ldg(xrow + (2 * seg + h + 1) * (16 * DM / 8) + 24 * k);
            }
            float s = 0.f, q = 0.f;
#pragma unroll
            for (int j = 0; j < 24; j++) s += f[j];
            if (lane >= 24) s = 0.f;
#pragma unroll
            for (int o = 16; o; o >>= 1) s += __shfl_xor_sync(~0u, s, o);
            const float mean = s * (1.f / DM);
#pragma unroll
            for (int j = 0; j < 24; j++) { f[j] -= mean; q += f[j] * f[j]; }
            if (lane >= 24) q = 0.f;
#pragma unroll
            for (int o = 16; o; o >>= 1) q += __shfl_xor_sync(~0u, q, o);
            const float rstd = rsqrtf(q * (1.f / DM) + 1e-5f);
            if (lane < 24) {
                uint8_t* d = g_x0 + seg * XIMG + (l >> 3) * 4096 + (r + 16 * h) * 128 + (((l & 7) ^ (r & 7)) << 4);
#pragma unroll
                for (int k = 0; k < 3; k++) {
                    const float* y = &f[8 * k];
                    stg128(d + k * 12288, make_uint4(pack2(y[0] * rstd, y[1] * rstd), pack2(y[2] * rstd, y[3] * rstd), pack2(y[4] * rstd, y[5] * rstd), pack2(y[6] * rstd, y[7] * rstd)));
                }
            }
        }
        __syncwarp();
        if (lane == 0 && seg == 0) TG(79, 4);
        if (lane == 0) publish(F_X0, seg);
        if (lane == 0 && seg == 0) TG(79, 5);
        __syncwarp();
    }
}

template <bool SECOND, bool CHAIN>
__device__ __forceinline__ void reduce_job(const Params& P, int b, int p, int t) {
    constexpr int NP = SECOND ? NP2 : NP1;
    const int seg = CHAIN ? b - LAG : b, lane = t & 31;
    const bool act = !(t & 1);
    const uint32_t ro = (b & (RING - 1)), po = p * (DM * 4) + t * 16, so = 2048 - t * 16 + (t >> 1) * 4;
    const int fa = (t >> 2) * 16 + (t & 3) * 2, fs = 512 + (t >> 5) * 16 + ((t >> 2) & 7) + (t & 2) * 4;
    const uint32_t row = (seg * 32 + (p & 15) * 2) * DM;
    uint8_t* const r1 = g_r1 + ro * PART + po;
    uint8_t* const r2 = g_r2 + seg * (PART / 2) + po - (CHAIN ? PART / 2 : 0);
    float f[10];
    uint4 x;
    uint32_t y;
    {
        const uint8_t* src = (SECOND ? g_p2 : g_p1) + ro * (NP * PART) + po;
        uint4 a[NP];
        uint32_t c[NP];
#pragma unroll
        for (int k = 0; k < NP; k++) { a[k] = ld_rlx128(src + k * PART); c[k] = ld_rlx(src + so + k * PART); }
        if (SECOND || CHAIN) {
            x = ld_rlx128(SECOND ? r1 : r2); y = ld_rlx((SECOND ? r1 : r2) + so);
        } else {
            const bf16* xr = P.x + row;
            const uint32_t a0 = ld_rlx(xr + fa), b0 = ld_rlx(xr + fa + 8), a1 = ld_rlx(xr + fa + DM), b1 = ld_rlx(xr + fa + DM + 8);
            const uint32_t s0 = ld_rlx(xr + (fs & ~1)), s1 = ld_rlx(xr + (fs & ~1) + DM);
            x = make_uint4(__byte_perm(a0, a1, 0x5410), __byte_perm(b0, b1, 0x5410), __byte_perm(a0, a1, 0x7632), __byte_perm(b0, b1, 0x7632));
            y = __byte_perm(s0, s1, (fs & 1) ? 0x7632 : 0x5410);
        }
        set8(f, a[0]); f[8] = bf_lo(c[0]); f[9] = bf_hi(c[0]);
#pragma unroll
        for (int k = 1; k < NP; k++) { add8(f, a[k]); f[8] += bf_lo(c[k]); f[9] += bf_hi(c[k]); }
    }
    add8(f, x);
    x = make_uint4(pack2(f[0], f[1]), pack2(f[2], f[3]), pack2(f[4], f[5]), pack2(f[6], f[7]));
    y = pack2(f[8] + bf_lo(y), f[9] + bf_hi(y));
    if (SECOND && CHAIN) {
        bf16* o = P.out + row;
        stg32(o + fa, __byte_perm(x.x, x.z, 0x5410));
        stg32(o + fa + 8, __byte_perm(x.y, x.w, 0x5410));
        stg32(o + fa + DM, __byte_perm(x.x, x.z, 0x7632));
        stg32(o + fa + DM + 8, __byte_perm(x.y, x.w, 0x7632));
        stg16(o + fs + (act ? 0 : DM), act ? y : y >> 16);
        return;
    }
    set8(f, x);
    f[8] = act ? bf_lo(y) : 0.f; f[9] = act ? 0.f : bf_hi(y);
    float st[4];
    st[0] = (f[0] + f[2]) + (f[4] + f[6]) + f[8]; st[2] = (f[0] * f[0] + f[2] * f[2]) + (f[4] * f[4] + f[6] * f[6]) + f[8] * f[8];
    st[1] = (f[1] + f[3]) + (f[5] + f[7]) + f[9]; st[3] = (f[1] * f[1] + f[3] * f[3]) + (f[5] * f[5] + f[7] * f[7]) + f[9] * f[9];
    {
        const bool u = lane & 1, v = lane & 2;
        st[0] = (u ? st[1] : st[0]) + __shfl_xor_sync(~0u, u ? st[0] : st[1], 1);
        st[2] = (u ? st[3] : st[2]) + __shfl_xor_sync(~0u, u ? st[2] : st[3], 1);
        st[0] = (v ? st[2] : st[0]) + __shfl_xor_sync(~0u, v ? st[0] : st[2], 2);
        st[0] = (st[0] + __shfl_xor_sync(~0u, st[0], 4)) + (__shfl_xor_sync(~0u, st[0], 8) + __shfl_xor_sync(~0u, st[0], 12));
        if (!(lane & 12)) sts32(sb + F_RED + (t >> 4) * 16 + (lane & 3) * 4, fu(st[0]));
    }
    nbar_sync(NB_R, 128);
#pragma unroll
    for (int k = 0; k < 8; k++) {
        const uint4 q = lds128(sb + F_RED + k * 16);
        if (k == 0) { st[0] = uf(q.x); st[1] = uf(q.y); st[2] = uf(q.z); st[3] = uf(q.w); }
        else { st[0] += uf(q.x); st[1] += uf(q.y); st[2] += uf(q.z); st[3] += uf(q.w); }
    }
    stg128(SECOND ? r2 : r1, x);
    if (act) stg32((SECOND ? r2 : r1) + so, y);
    const float m0 = st[0] * (1.f / DM), m1 = st[1] * (1.f / DM);
    const float q0 = rsqrtf(fmaxf(st[2] * (1.f / DM) - m0 * m0, 0.f) + 1e-5f), q1 = rsqrtf(fmaxf(st[3] * (1.f / DM) - m1 * m1, 0.f) + 1e-5f);
    constexpr int KB = SECOND ? 4096 : 8192;
    uint8_t* d = (SECOND ? g_x1 + seg * XIMG : g_xf + ro * (9 * 8192)) + p * 256;
#pragma unroll
    for (int e = 0; e < 2; e++) {
        const float m = e ? m1 : m0, q = e ? q1 : q0;
#pragma unroll
        for (int h = 0; h < 2; h++)
            stg32(d + (fa >> 6) * KB + (t & 3) * 4 + e * 128 + (((((fa >> 3) & 6) + h) ^ ((2 * p + e) & 7)) << 4), pack2((f[2 * h + e] - m) * q, (f[4 + 2 * h + e] - m) * q));
    }
    stg16(d + 8 * KB + (t & 1) * 128 + ((((fs >> 3) & 7) ^ ((2 * p + (t & 1)) & 7)) << 4) + (fs & 7) * 2, pack2(act ? (f[8] - m0) * q0 : (f[9] - m1) * q1, 0.f));
}
template <bool CHAIN>
__device__ __forceinline__ void reducer(const Params& P) {
#pragma unroll 1
    for (int j = 0; j < 2 * NSEG; j++) {
        const int t = fresh_tid() - 256, p = fresh_bid() - NENG;
        mbar_wait(bars + FB_JOB * 8, j & 1);
        const int job = lds32(sb + F_RED + 192 + (j & 1) * 4);
        if (job >= 256) reduce_job<true, CHAIN>(P, job - 256, p, t);
        else reduce_job<false, CHAIN>(P, job, p, t);
        mbar_arrive_warp(bars + FB_RDONE * 8);
    }
}

__host__ __device__ constexpr int d_rf(int u) { return u < 48 ? ((u & 3) < 2 ? (u >> 2) * 2 + (u & 1) : -1) : u == 48 ? 24 : -1; }
__host__ __device__ constexpr int d_ss(int u) { return u < 48 ? (u >> 2) * 2 + (u & 1) : u - 25; }
template <bool WIDE, int wg>
__device__ __forceinline__ void d_main() {
    constexpr int NR = WIDE ? 24 : NRD;
    uint32_t w[NR][4];
    {
        const uint32_t fa = sb + wg * (NRD * 2048) + unit_frag_addr(threadIdx.x);
        mbar_wait(bars + DB_WL * 8, 0);
#pragma unroll
        for (int u = 0; u < NR; u++) ldsm4t(w[u], fa + u * 2048);
        nbar_arrive(NB_W, 416);
        mbar_wait(bars + DB_WL * 8, 1);
        if (threadIdx.x == 0) TG(79, 2);
    }
    const uint64_t da = mkdesc(wg * ((52 - NRD) * 2048), 1024, 1024, 1);
#pragma unroll 1
    for (int b = 0; b < NSTEP; b++) {
#pragma unroll
        for (int T = 0; T < (WIDE ? 3 : 1); T++) {
            float d[32];
            constexpr int NB = WIDE ? 4 : 13;
#pragma unroll
            for (int blk = 0; blk < NB; blk++) {
                const int c = blk;
                if (T == 0 || blk == 0) mbar_wait(bars + (DB_FULL + (c & 7)) * 8, WIDE || (c & 7) >= 5 ? b & 1 : c >> 3);
                if (T == 0 || blk == 0) wg_fence();
                const uint64_t db = mkdesc(D_B + (c & 7) * 8192, 8192, 1024, 1);
#pragma unroll
                for (int j = 0; j < 4; j++) {
                    const int u = T * 16 + blk * 4 + j;
                    if (d_rf(u) >= 0) wg_rs64<1>(d, w[d_rf(u) >= 0 ? d_rf(u) : 0], db + j * 128, blk + j > 0);
                    else wg_ss64<1>(d, da + d_ss(u) * 128, db + j * 128, blk + j > 0);
                }
                wg_commit();
                if (!WIDE && blk > 0) { wg_wait<1>(); mbar_arrive_warp(bars + (DB_EMPTY + ((c - 1) & 7)) * 8); }
            }
            const int tid = fresh_tid(), t = tid & 3, ds = fresh_bid() - NENG - NF1;
            const bool w2 = ds >= 15;
            const int tile = WIDE ? wg * 3 + T : (ds % 3) * 3 + wg;
            uint8_t* dst = (w2 ? g_p2 + ((b & (RING - 1)) * NP2 + (WIDE ? ds - 25 : (ds - 15) / 3)) * PART : g_p1 + ((b & (RING - 1)) * NP1 + ds / 3) * PART)
                         + (tile * 64 + ((tid >> 5) & 3) * 16 + ((tid & 31) >> 2) * 2) * 4 + (w2 ? 4 * t : t) * (DM * 4);
            const uint32_t js = w2 ? DM * 4 : DM * 16;
            if (T == 0) mbar_wait(bars + (DB_P + 1) * 8, (b & 1) ^ 1);
            wg_wait_acc<0, 32>(d);
            if (!WIDE) mbar_arrive_warp(bars + (DB_EMPTY + ((NB - 1) & 7)) * 8);
            else if (T == 2) {
#pragma unroll
                for (int blk = 0; blk < 4; blk++) mbar_arrive_warp(bars + (DB_EMPTY + blk) * 8);
            }
#pragma unroll
            for (int j = 0; j < 8; j++) stg64(dst + (j >> 2) * (DM * 64) + (j & 3) * js, pack2(d[4 * j], d[4 * j + 1]), pack2(d[4 * j + 2], d[4 * j + 3]));
        }
        mbar_arrive_warp(bars + DB_P * 8);
    }
}
__device__ __forceinline__ void d_helper(const Params& P, int ds) {
    const int lane = threadIdx.x & 31, hw = warp_in_group();
    const bool w2 = ds >= 15, wide = ds >= 30;
    const int kr = (w2 ? ds - 15 : ds) / 3, nb = wide ? 4 : 13;
    const int blk0 = wide ? 29 + (ds - 30) * 4 : kr * (w2 ? 6 : 13), n1 = w2 ? (kr == 4 ? 5 : 6) : 13, blk1 = 37 + kr * 7 - n1;
    if (hw == 0) {
        const int nu = wide ? 48 : 52;
        hold_back(w2 ? W2_DELAY : D_DELAY);
#pragma unroll 1
        for (int ph = 0; ph < 2; ph++) {
            if (ph) nbar_sync(NB_W, 416);
            if (lane == 0) mbar_expect(bars + DB_WL * 8, (wide ? 72 : ph ? 3 * (52 - NRD) : 3 * NRD) * 2048);
            __syncwarp();
#pragma unroll 1
            for (int x = lane; x < 3 * nu; x += 32) {
                const int wg = x / nu, u = x - wg * nu, j = (wide ? u & 15 : u) >> 2;
                const int kb = !w2 ? blk0 + j : j < n1 ? (blk0 + j) * 2 : (blk1 + j - 37) * 2 + 1;
                if ((d_rf(u) < 0) == (ph != 0))
                    tma_unit(sb + (ph ? wg * (52 - NRD) + d_ss(u) : wg * NRD + d_rf(u)) * 2048, w2 ? &P.tmW2 : &P.tmWo,
                             kb * 4 + (u & 3), wide ? wg * 3 + (u >> 4) : (ds % 3) * 3 + wg, bars + DB_WL * 8);
            }
        }
        __syncwarp();
        if (lane == 0) {
            const uint32_t target = (w2 ? NF1 : NENG) * this_launch();
#pragma unroll 1
            for (int b = 0; b < NSTEP; b++) {
                flag_wait(w2 ? F_H : F_O, b, target);
                TG(b, 29);
                const uint8_t* src = (w2 ? g_h + (b & (RING - 1)) * H_BYTES : g_o + (b & (RING - 1)) * O_BYTES);
#pragma unroll 1
                for (int blk = 0; blk < nb; blk++) {
                    const int c = blk;
                    if (blk == n1) flag_wait(F_H2, b, target);
                    mbar_wait(bars + (DB_EMPTY + (c & 7)) * 8, (wide || (c & 7) >= 5 ? b & 1 : c >> 3) ^ 1);
                    mbar_expect(bars + (DB_FULL + (c & 7)) * 8, 8192);
                    bulk_g2s(sb + D_B + (c & 7) * 8192, src + (blk + (blk < n1 ? blk0 : blk1)) * 8192, 8192, bars + (DB_FULL + (c & 7)) * 8);
                }
            }
        }
    } else if (hw == 1 && lane == 0) {
        publisher(bars + DB_P * 8, bars + (DB_P + 1) * 8, w2 ? F_P2 : F_P1);
    }
    __syncwarp();
}

__device__ __forceinline__ void sign_off() { mbar_arrive_warp(sb + SM_DONE); }
__device__ __forceinline__ void sign_off_helper() {
    if (warp_in_group() < 3) { sign_off(); return; }
    uint32_t ok;
    const uint32_t t0 = timer_lo(), ep = this_launch();
    do {
        __nanosleep(100);
        asm volatile("{.reg .pred p; mbarrier.test_wait.parity.shared::cta.b64 p, [%1], 0; selp.u32 %0, 1, 0, p;}" : "=r"(ok) : "r"(sb + SM_DONE) : "memory");
    } while (!ok && timer_lo() - t0 < TIME_LIMIT);
    if (!ok || (sb & 0x3ffff) != SM_ORG) __trap();
    if (fresh_tid() == NTHREADS - 32) { g_epoch[fresh_bid()][0] = ep; TG(79, 1); }
    __syncwarp();
}

__global__ void __cluster_dims__(2, 1, 1) __launch_bounds__(NTHREADS, 1) fused_kernel(const __grid_constant__ Params P) {
    const int wg = __shfl_sync(~0u, threadIdx.x >> 7, 0);
    const int bid = blockIdx.x;
    if (threadIdx.x >= NTHREADS - 32) sts32(sb + SM_ONES + (threadIdx.x & 31) * 4, 0x3f803f80u);
    if (threadIdx.x == 0) {
        TG(79, 0);
        mbar_init(sb + SM_DONE, 15);
        sts32(sb + SM_XRDY, 0);
        if (bid < NENG) {
            for (int i = 0; i < 11; i++) mbar_init(bars + (EB_FULL + i) * 8, 1);
            mbar_init(bars + EB_V0 * 8, 4);
            for (int i = 0; i < 3; i++) mbar_init(bars + (EB_EMPTY + i) * 8, 12);
            mbar_init(bars + EB_PRDY2 * 8, 1);
            mbar_init(bars + EB_WL * 8, 3); mbar_init(bars + EB_WO * 8, 2); mbar_init(bars + EB_STEP * 8, 8);
            mbar_init(bars + EB_VX * 8, 1); mbar_init(bars + EB_SM * 8, 1); mbar_init(bars + EB_SX * 8, 1); mbar_init(bars + EB_VM * 8, 5);
            mbar_init(bars + EB_QF * 8, 4); mbar_init(bars + EB_KF * 8, 8); mbar_init(bars + EB_MEM * 8, 5); mbar_init(bars + EB_MEM0 * 8, 8); mbar_init(bars + EB_PRDY * 8, 1);
            mbar_init(bars + EB_CONS * 8, 4); mbar_init(bars + EB_OST * 8, 4); mbar_init(bars + EB_OFREE * 8, 1);
        } else if (bid < NENG + NF1) {
            for (int i = 0; i < 9; i++) { mbar_init(bars + (FB_FULL + i) * 8, 1); mbar_init(bars + (FB_EMPTY + i) * 8, 8); }
            mbar_init(bars + FB_H * 8, 8); mbar_init(bars + FB_H2 * 8, 8); mbar_init(bars + FB_RACK * 8, 1); mbar_init(bars + FB_JOB * 8, 2); mbar_init(bars + FB_RDONE * 8, 4);
        } else {
            for (int i = 0; i < 8; i++) { mbar_init(bars + (DB_FULL + i) * 8, 1); mbar_init(bars + (DB_EMPTY + i) * 8, 12); }
            mbar_init(bars + DB_WL * 8, 1); mbar_init(bars + DB_P * 8, 12); mbar_init(bars + (DB_P + 1) * 8, 1);
        }
        asm volatile("fence.mbarrier_init.release.cluster;" ::: "memory");
    }
    __syncthreads();
    asm volatile("barrier.cluster.arrive.relaxed.aligned; barrier.cluster.wait.aligned;" ::: "memory");
    if (bid < NENG) {
        if (wg == 0) { reg_inc<REGQ>(); engine_main<0>(P); sign_off(); cluster_sync_all(); }
        else if (wg == 1) { reg_inc<REGK>(); engine_main<1>(P); sign_off(); cluster_sync_all(); }
        else if (wg == 2) { reg_inc<REGV>(); engine_main<2>(P); sign_off(); cluster_sync_all(); }
        else { reg_dec<24>(); engine_helper(P); sign_off_helper(); cluster_sync_all(); }
    } else if (bid < NENG + NF1) {
        if (wg < 2) {
            reg_inc<REGF>();
            if (wg == 0) f1_main<0>(P); else f1_main<1>(P);
            sign_off();
        } else if (wg == 2) {
            reg_dec<488 - 2 * REGF>();
            if (bid >= NENG + 32) ln0_rows(P, (bid - NENG - 32) * 4 + warp_in_group());
            else if (bid < NENG + 16) reducer<false>(P);
            else reducer<true>(P);
            sign_off();
        } else {
            reg_dec<24>();
            f1_helper(P);
            sign_off_helper();
        }
    } else {
        const int ds = bid - NENG - NF1;
        if (wg < 3) {
            reg_inc<160>();
            if (ds < 30) { if (wg == 0) d_main<false, 0>(); else if (wg == 1) d_main<false, 1>(); else d_main<false, 2>(); }
            else { if (wg == 0) d_main<true, 0>(); else if (wg == 1) d_main<true, 1>(); else d_main<true, 2>(); }
            sign_off();
        } else {
            reg_dec<32>();
            d_helper(P, ds);
            sign_off_helper();
        }
    }
}

typedef CUresult (*EncodeFn)(CUtensorMap*, CUtensorMapDataType, cuuint32_t, void*, const cuuint64_t*, const cuuint64_t*,
                             const cuuint32_t*, const cuuint32_t*, CUtensorMapInterleave, CUtensorMapSwizzle,
                             CUtensorMapL2promotion, CUtensorMapFloatOOBfill);

void make_map(EncodeFn enc, CUtensorMap* m, const void* p, int rows, int cols) {
    cuuint64_t dims[2] = {(cuuint64_t)cols, (cuuint64_t)rows};
    cuuint64_t strides[1] = {(cuuint64_t)cols * 2};
    cuuint32_t box[2] = {64, 16};
    cuuint32_t es[2] = {1, 1};
    enc(m, CU_TENSOR_MAP_DATA_TYPE_BFLOAT16, 2, (void*)p, dims, strides, box, es, CU_TENSOR_MAP_INTERLEAVE_NONE,
        CU_TENSOR_MAP_SWIZZLE_128B, CU_TENSOR_MAP_L2_PROMOTION_L2_128B, CU_TENSOR_MAP_FLOAT_OOB_FILL_NONE);
}

}

extern "C" void kernel_launch(void* const* d_in, const int* in_sizes, int n_in, void* d_out, int out_size) {
    (void)in_sizes; (void)n_in; (void)out_size;
    static EncodeFn enc = nullptr;
    if (!enc) {
        void* fn = nullptr;
        cudaDriverEntryPointQueryResult qr;
        cudaGetDriverEntryPoint("cuTensorMapEncodeTiled", &fn, cudaEnableDefault, &qr);
        enc = (EncodeFn)fn;
        cudaFuncSetAttribute(fused_kernel, cudaFuncAttributeMaxDynamicSharedMemorySize, SM_TOTAL);
    }
    Params P;
    make_map(enc, &P.tmWq, d_in[2], DM, 4096);
    make_map(enc, &P.tmWk, d_in[3], DM, 4096);
    make_map(enc, &P.tmWv, d_in[4], DM, 4096);
    make_map(enc, &P.tmWo, d_in[5], 4096, DM);
    make_map(enc, &P.tmW2, d_in[10], FF, DM);
    P.x = (const bf16*)d_in[0];
    P.mem0 = (const bf16*)d_in[1];
    P.w1 = (const bf16*)d_in[8];
    P.w3 = (const bf16*)d_in[9];
    P.w2 = (const bf16*)d_in[10];
    P.out = (bf16*)d_out;
    P.zero = 0;
    fused_kernel<<<NCTA, NTHREADS, SM_TOTAL>>>(P);
}
```

```cpp
#include <cuda_runtime.h>
#include <cuda_bf16.h>
#include <cuda.h>
#include <stdint.h>

typedef __nv_bfloat16 bf16;

namespace {

constexpr int DM = 576, FF = 4608, NSEG = 64;
constexpr int NENG = 64, NF1 = 36, ND = 32, NCTA = NENG + NF1 + ND;
constexpr int NTHREADS = 512;
#define LAG 8
#define RING 16
static_assert(RING > LAG, "ring too short");
#define USE_ONE 1
constexpr int NSTEP = NSEG + LAG;

enum { F_X0 = 0, F_X1, F_O, F_P1, F_XF, F_H, F_P2, F_H2, F_COUNT };
constexpr int B_ZERO = 95;
__device__ uint32_t g_flag[F_COUNT][96][8];
__device__ uint32_t g_epoch[NCTA][8];
constexpr int XIMG = 9 * 8192;
constexpr int O_BYTES = 65 * 8192;
constexpr int H_BYTES = 73 * 8192;
constexpr int PART = 32 * DM * 4;
constexpr int NP1 = 5, NP2 = 7;
__device__ __align__(1024) uint8_t g_x[NSTEP * XIMG];
__device__ __align__(1024) uint8_t g_xf[RING * XIMG];
__device__ __align__(1024) uint8_t g_o[RING * O_BYTES];
__device__ __align__(1024) uint8_t g_h[RING * H_BYTES];
__device__ __align__(1024) uint8_t g_p1[RING * NP1 * PART];
__device__ __align__(1024) uint8_t g_p2[RING * NP2 * PART];
__device__ __align__(1024) uint8_t g_r1[RING * PART];
__device__ __align__(1024) uint8_t g_r2[NSEG * PART / 2];
#define AR_STR 4352
constexpr int AR_SLOT = 144 * AR_STR;
__device__ __align__(1024) uint8_t g_ar[4 * AR_SLOT];

struct Params {
    CUtensorMap tmWq, tmWk, tmWv, tmWo, tmW2;
    const bf16 *x, *mem0, *w1, *w3, *w2;
    bf16* out;
    uint32_t zero;
};

constexpr uint32_t SM_ORG = 1024;
extern __shared__ __align__(1024) uint8_t smem_raw[];
#define sb ((uint32_t)__cvta_generic_to_shared(smem_raw))
#define bars (sb + SM_BAR)
constexpr int SM_BAR = 231936;
constexpr int SM_TOTAL = SM_BAR + 512;
#define NRQ 25
#define NRK 25
#define NRV 25
#define REGQ 160
#define REGK 168
#define REGV 160
constexpr int E_WQ = 0;
constexpr int E_WK = E_WQ + (36 - NRQ) * 2048;
constexpr int E_WV = E_WK + (36 - NRK) * 2048;
constexpr int E_WO = E_WV + (36 - NRV) * 2048;
constexpr int E_MEM = E_WO + 36 * 2048;
constexpr int E_R0 = E_MEM + 18432;
constexpr int E_R2 = E_R0 + 8192, E_R3 = E_R2 + 8192, E_R1 = E_R3 + 8192;
constexpr int E_SX = E_R1;
constexpr int E_QT = E_R1 + 8192;
constexpr int E_KT = E_QT + 8192;
constexpr int E_VT = E_KT + 10240;
constexpr int E_OM = E_VT + 10240;
constexpr int E_QM = E_OM + 4096;
constexpr int E_SR = E_QM + 2048;
constexpr int E_SL = E_SR + 2560;
constexpr int E_END = E_SL + 2048;
static_assert(E_END <= SM_BAR, "engine smem overflow");
static_assert(E_WO + (NRQ + NRK + NRV) * 2048 <= E_OM, "weight staging: the peer writes there without asking");
enum {
    EB_FULL = 0  , EB_EMPTY = 6  , EB_V0 = 9, EB_WL, EB_WO, EB_STEP, EB_SM, EB_SX, EB_OX,
    EB_QF, EB_KF, EB_CONS, EB_OST, EB_OFREE, EB_MEM, EB_PRDY
};
enum { NB_G = 1, NB_LEAD, NB_QK, NB_S, NB_OM, NB_W, NB_R, NB_T, NB_PV, NB_WO, NB_V, NB_KT, NB_S2, NB_VL };
constexpr int NB_VL2 = NB_LEAD;
#define REGF 208
constexpr int NRF = REGF == 200 ? 35 : 36;
constexpr int F_W = 0;
constexpr int F_X = 2 * (72 - NRF) * 2048;
constexpr int F_RED = F_X + 9 * 8192;
static_assert(F_RED + 512 <= SM_BAR, "F1 smem overflow");
enum { FB_FULL = 0, FB_EMPTY = 9, FB_H = 18, FB_H2, FB_RACK, FB_JOB, FB_RDONE };
constexpr int NRD = 25;
constexpr int D_B = 3 * (52 - NRD) * 2048;
static_assert(D_B + 8 * 8192 <= SM_BAR, "D smem overflow");
enum { DB_FULL = 0, DB_EMPTY = 8, DB_WL = 16, DB_P };
constexpr int SM_DONE = SM_BAR + 248, SM_XRDY = SM_BAR + 376, SM_ONES = SM_BAR + 384;
constexpr uint32_t TIME_LIMIT = 2000000000u;

#define SPIN_CHECK(n, code)

#define TS(thr, step, k)
#define TX(thr, k)
#define TG(step, k)
#define PROF_INC(n, k)

__device__ __forceinline__ uint32_t mapa(uint32_t a, uint32_t r) {
    uint32_t o; asm("mapa.shared::cluster.u32 %0, %1, %2;" : "=r"(o) : "r"(a), "r"(r)); return o;
}
__device__ __forceinline__ void mbar_init(uint32_t b, uint32_t cnt) {
    asm volatile("mbarrier.init.shared::cta.b64 [%0], %1;" :: "r"(b), "r"(cnt) : "memory");
}
__device__ __forceinline__ void mbar_arrive(uint32_t b) {
    asm volatile("mbarrier.arrive.shared::cta.b64 _, [%0];" :: "r"(b) : "memory");
}
__device__ __forceinline__ void mbar_arrive_warp(uint32_t b) {
    asm volatile("{.reg .pred p; bar.warp.sync -1; elect.sync _|p, -1; @p mbarrier.arrive.shared::cta.b64 _, [%0];}" :: "r"(b) : "memory");
}
__device__ __forceinline__ void mbar_arrive_remote(uint32_t b) {
    asm volatile("fence.release.sync_restrict::shared::cta.cluster; mbarrier.arrive.relaxed.cluster.shared::cluster.b64 _, [%0];" :: "r"(b) : "memory");
}
__device__ __forceinline__ void mbar_expect(uint32_t b, uint32_t bytes) {
    asm volatile("mbarrier.arrive.expect_tx.shared::cta.b64 _, [%0], %1;" :: "r"(b), "r"(bytes) : "memory");
}
__device__ __forceinline__ uint32_t mbar_wait(uint32_t b, uint32_t par) {
    uint32_t ok; [[maybe_unused]] int n = 0;
    while (true) {
        asm volatile("{.reg .pred p; mbarrier.try_wait.parity.shared::cta.b64 p, [%1], %2; selp.u32 %0, 1, 0, p;}"
                     : "=r"(ok) : "r"(b), "r"(par) : "memory");
        if (ok) break;
        SPIN_CHECK(n, 1000 + ((b & 511) >> 3));
    }
    return ok;
}
__device__ __forceinline__ bool mbar_test(uint32_t b, uint32_t par) {
    uint32_t ok;
    asm volatile("{.reg .pred p; mbarrier.test_wait.parity.shared::cta.b64 p, [%1], %2; selp.u32 %0, 1, 0, p;}" : "=r"(ok) : "r"(b), "r"(par) : "memory");
    return ok;
}
__device__ __forceinline__ void mbar_wait_cl(uint32_t b, uint32_t par) {
    uint32_t ok; [[maybe_unused]] int n = 0;
    while (true) {
        asm volatile("{.reg .pred p; mbarrier.try_wait.parity.relaxed.cluster.shared::cta.b64 p, [%1], %2; selp.u32 %0, 1, 0, p;}"
                     : "=r"(ok) : "r"(b), "r"(par) : "memory");
        if (ok) break;
        SPIN_CHECK(n, 1000 + ((b & 511) >> 3));
    }
    asm volatile("fence.acquire.sync_restrict::shared::cluster.cluster;" ::: "memory");
}
__device__ __forceinline__ void nbar_sync(int id, int n) { asm volatile("bar.sync %0, %1;" :: "r"(id), "r"(n) : "memory"); }
__device__ __forceinline__ void nbar_arrive(int id, int n) { asm volatile("bar.arrive %0, %1;" :: "r"(id), "r"(n) : "memory"); }
__device__ __forceinline__ void cluster_sync_all() {
    asm volatile("barrier.cluster.arrive.release.aligned; barrier.cluster.wait.acquire.aligned;" ::: "memory");
}
__device__ __forceinline__ void fence_async_smem() { asm volatile("fence.proxy.async.shared::cta;" ::: "memory"); }
__device__ __forceinline__ void fence_async_glb() { asm volatile("fence.proxy.async.global;" ::: "memory"); }
__device__ __forceinline__ void fence_rel_gpu() { asm volatile("fence.release.gpu;" ::: "memory"); }
__device__ __forceinline__ void fence_acq_gpu() { asm volatile("fence.acquire.gpu;" ::: "memory"); }
__device__ __forceinline__ void fence_gpu() { asm volatile("fence.acq_rel.gpu;" ::: "memory"); }
__device__ __forceinline__ int fresh_tid() { int t; asm volatile("mov.u32 %0, %%tid.x;" : "=r"(t)); return t; }
__device__ __forceinline__ int fresh_bid() { int t; asm volatile("mov.u32 %0, %%ctaid.x;" : "=r"(t)); return t; }
__device__ __forceinline__ uint32_t pin(uint32_t v) { asm volatile("" : "+r"(v)); return v; }
__device__ __forceinline__ int warp_in_group() { return __shfl_sync(~0u, (fresh_tid() >> 5) & 3, 0); }
__device__ __forceinline__ int cta_rank() { int t; asm volatile("mov.u32 %0, %%cluster_ctarank;" : "=r"(t)); return t; }
__device__ __forceinline__ uint32_t timer_lo() { uint32_t t; asm volatile("mov.u32 %0, %%globaltimer_lo;" : "=r"(t)); return t; }
__device__ __forceinline__ uint32_t keep(uint32_t v) { return __shfl_xor_sync(~0u, v, 0); }
__device__ __forceinline__ void red_add_u32(uint32_t* p, uint32_t v) {
    asm volatile("red.relaxed.gpu.global.add.u32 [%0], %1;" :: "l"(p), "r"(v) : "memory");
}
__device__ __forceinline__ uint32_t ld_rlx(const void* p) {
    uint32_t v; asm volatile("ld.relaxed.gpu.global.u32 %0, [%1];" : "=r"(v) : "l"(p) : "memory"); return v;
}
__device__ __forceinline__ uint2 ld_rlx64(const void* p) {
    uint2 v; asm volatile("ld.relaxed.gpu.global.v2.u32 {%0,%1}, [%2];" : "=r"(v.x), "=r"(v.y) : "l"(p) : "memory"); return v;
}
__device__ __forceinline__ uint4 ld_rlx128(const void* p) {
    uint4 v;
    asm volatile("ld.relaxed.gpu.global.v4.u32 {%0,%1,%2,%3}, [%4];" : "=r"(v.x), "=r"(v.y), "=r"(v.z), "=r"(v.w) : "l"(p) : "memory");
    return v;
}
__device__ __forceinline__ void stg128(void* p, uint4 v) {
    asm volatile("st.global.v4.b32 [%0], {%1,%2,%3,%4};" :: "l"(p), "r"(v.x), "r"(v.y), "r"(v.z), "r"(v.w) : "memory");
}
__device__ __forceinline__ void stg64(void* p, uint32_t a, uint32_t b) {
    asm volatile("st.global.v2.b32 [%0], {%1,%2};" :: "l"(p), "r"(a), "r"(b) : "memory");
}
__device__ __forceinline__ void stg16(void* p, uint32_t a) { asm volatile("st.global.b16 [%0], %1;" :: "l"(p), "h"((uint16_t)a) : "memory"); }
__device__ __forceinline__ void stg32(void* p, uint32_t a) { asm volatile("st.global.b32 [%0], %1;" :: "l"(p), "r"(a) : "memory"); }
__device__ __forceinline__ void st_async128(uint32_t a, uint32_t x, uint32_t y, uint32_t z, uint32_t w, uint32_t mb) {
    asm volatile("st.async.shared::cluster.mbarrier::complete_tx::bytes.v4.b32 [%0], {%1,%2,%3,%4}, [%5];"
                 :: "r"(a), "r"(x), "r"(y), "r"(z), "r"(w), "r"(mb) : "memory");
}
__device__ __forceinline__ void st_async64(uint32_t a, uint32_t x, uint32_t y, uint32_t mb) {
    asm volatile("st.async.shared::cluster.mbarrier::complete_tx::bytes.v2.b32 [%0], {%1,%2}, [%3];"
                 :: "r"(a), "r"(x), "r"(y), "r"(mb) : "memory");
}
__device__ __forceinline__ void sts128(uint32_t a, uint32_t x, uint32_t y, uint32_t z, uint32_t w) {
    asm volatile("st.shared.v4.b32 [%0], {%1,%2,%3,%4};" :: "r"(a), "r"(x), "r"(y), "r"(z), "r"(w) : "memory");
}
__device__ __forceinline__ void sts32(uint32_t a, uint32_t v) { asm volatile("st.shared.b32 [%0], %1;" :: "r"(a), "r"(v) : "memory"); }
__device__ __forceinline__ uint4 lds128(uint32_t a) {
    uint4 v; asm volatile("ld.shared.v4.b32 {%0,%1,%2,%3}, [%4];" : "=r"(v.x), "=r"(v.y), "=r"(v.z), "=r"(v.w) : "r"(a) : "memory"); return v;
}
__device__ __forceinline__ uint2 lds64(uint32_t a) {
    uint2 v; asm volatile("ld.shared.v2.b32 {%0,%1}, [%2];" : "=r"(v.x), "=r"(v.y) : "r"(a) : "memory"); return v;
}
__device__ __forceinline__ uint32_t lds32(uint32_t a) {
    uint32_t v; asm volatile("ld.shared.b32 %0, [%1];" : "=r"(v) : "r"(a) : "memory"); return v;
}
__device__ __forceinline__ void bulk_g2s(uint32_t dst, const void* src, uint32_t bytes, uint32_t mb) {
    asm volatile("cp.async.bulk.shared::cluster.global.mbarrier::complete_tx::bytes [%0], [%1], %2, [%3];"
                 :: "r"(dst), "l"(src), "r"(bytes), "r"(mb) : "memory");
}
__device__ __forceinline__ void bulk_s2g(void* dst, uint32_t src, uint32_t bytes) {
    asm volatile("cp.async.bulk.global.shared::cta.bulk_group [%0], [%1], %2;" :: "l"(dst), "r"(src), "r"(bytes) : "memory");
}
__device__ __forceinline__ void bulk_s2peer(uint32_t dst, uint32_t src, uint32_t bytes, uint32_t mb) {
    asm volatile("cp.async.bulk.shared::cluster.shared::cta.mbarrier::complete_tx::bytes [%0], [%1], %2, [%3];"
                 :: "r"(dst), "r"(src), "r"(bytes), "r"(mb) : "memory");
}
__device__ __forceinline__ void tma_unit(uint32_t dst, const CUtensorMap* tm, int kstep, int mgroup, uint32_t mb) {
    asm volatile("cp.async.bulk.tensor.2d.shared::cluster.global.mbarrier::complete_tx::bytes [%0], [%1, {%2,%3}], [%4];"
                 :: "r"(dst), "l"(tm), "r"(mgroup * 64), "r"(kstep * 16), "r"(mb) : "memory");
}
__device__ __forceinline__ void ldsm4(uint32_t* r, uint32_t a) {
    asm volatile("ldmatrix.sync.aligned.m8n8.x4.shared.b16 {%0,%1,%2,%3}, [%4];"
                 : "=r"(r[0]), "=r"(r[1]), "=r"(r[2]), "=r"(r[3]) : "r"(a) : "memory");
}
__device__ __forceinline__ void ldsm4t(uint32_t* r, uint32_t a) {
    asm volatile("ldmatrix.sync.aligned.m8n8.x4.trans.shared.b16 {%0,%1,%2,%3}, [%4];"
                 : "=r"(r[0]), "=r"(r[1]), "=r"(r[2]), "=r"(r[3]) : "r"(a) : "memory");
}
__device__ __forceinline__ void stsm4(uint32_t a, uint32_t r0, uint32_t r1, uint32_t r2, uint32_t r3) {
    asm volatile("stmatrix.sync.aligned.m8n8.x4.shared.b16 [%0], {%1,%2,%3,%4};" :: "r"(a), "r"(r0), "r"(r1), "r"(r2), "r"(r3) : "memory");
}
__device__ __forceinline__ void stsm4t(uint32_t a, uint32_t r0, uint32_t r1, uint32_t r2, uint32_t r3) {
    asm volatile("stmatrix.sync.aligned.m8n8.x4.trans.shared.b16 [%0], {%1,%2,%3,%4};" :: "r"(a), "r"(r0), "r"(r1), "r"(r2), "r"(r3) : "memory");
}
__device__ __forceinline__ uint32_t pack2(float lo, float hi) {
    uint32_t d; asm("cvt.rn.bf16x2.f32 %0, %1, %2;" : "=r"(d) : "f"(hi), "f"(lo)); return d;
}
__device__ __forceinline__ float bf_lo(uint32_t w) { return __uint_as_float(w << 16); }
__device__ __forceinline__ float bf_hi(uint32_t w) { return __uint_as_float(w & 0xffff0000u); }
__device__ __forceinline__ float ex2(float x) { float y; asm("ex2.approx.ftz.f32 %0, %1;" : "=f"(y) : "f"(x)); return y; }
__device__ __forceinline__ float rcp(float x) { float y; asm("rcp.approx.ftz.f32 %0, %1;" : "=f"(y) : "f"(x)); return y; }
__device__ __forceinline__ uint32_t fu(float x) { return __float_as_uint(x); }
__device__ __forceinline__ float uf(uint32_t x) { return __uint_as_float(x); }
__device__ __forceinline__ void mma16816(float* d, const uint32_t* a, uint32_t b0, uint32_t b1) {
    asm volatile("mma.sync.aligned.m16n8k16.row.col.f32.bf16.bf16.f32 {%0,%1,%2,%3}, {%4,%5,%6,%7}, {%8,%9}, {%0,%1,%2,%3};"
                 : "+f"(d[0]), "+f"(d[1]), "+f"(d[2]), "+f"(d[3]) : "r"(a[0]), "r"(a[1]), "r"(a[2]), "r"(a[3]), "r"(b0), "r"(b1));
}
__device__ __forceinline__ void mma1688(float* d, uint32_t a0, uint32_t a1, uint32_t b0) {
    asm volatile("mma.sync.aligned.m16n8k8.row.col.f32.bf16.bf16.f32 {%0,%1,%2,%3}, {%4,%5}, {%6}, {%0,%1,%2,%3};"
                 : "+f"(d[0]), "+f"(d[1]), "+f"(d[2]), "+f"(d[3]) : "r"(a0), "r"(a1), "r"(b0));
}
template <int N> __device__ __forceinline__ void reg_inc() { asm volatile("setmaxnreg.inc.sync.aligned.u32 %0;" :: "n"(N)); }
template <int N> __device__ __forceinline__ void reg_dec() { asm volatile("setmaxnreg.dec.sync.aligned.u32 %0;" :: "n"(N)); }

__device__ __forceinline__ uint64_t mkdesc(uint32_t addr, uint32_t lbo, uint32_t sbo, uint32_t swz) {
    return (uint64_t)((addr + SM_ORG) >> 4) | ((uint64_t)(lbo >> 4) << 16) | ((uint64_t)(sbo >> 4) << 32) | ((uint64_t)swz << 62);
}
__device__ __forceinline__ void wg_fence() { asm volatile("wgmma.fence.sync.aligned;" ::: "memory"); }
__device__ __forceinline__ void wg_commit() { asm volatile("wgmma.commit_group.sync.aligned;" ::: "memory"); }
template <int N> __device__ __forceinline__ void wg_wait() { asm volatile("wgmma.wait_group.sync.aligned %0;" :: "n"(N) : "memory"); }
template <int M> __device__ __forceinline__ void acc_ready(float* d) {
#pragma unroll
    for (int j = 0; j < M; j++) asm volatile("" : "+f"(d[j]) :: "memory");
}
template <int N, int M> __device__ __forceinline__ void wg_wait_acc(float* d) { wg_wait<N>(); acc_ready<M>(d); }

#define F8(c, d, o) c(d[o]), c(d[o + 1]), c(d[o + 2]), c(d[o + 3]), c(d[o + 4]), c(d[o + 5]), c(d[o + 6]), c(d[o + 7])
#define R8L "%0,%1,%2,%3,%4,%5,%6,%7"
#define R16L R8L ",%8,%9,%10,%11,%12,%13,%14,%15"
#define R32L R16L ",%16,%17,%18,%19,%20,%21,%22,%23,%24,%25,%26,%27,%28,%29,%30,%31"
#define R40L R32L ",%32,%33,%34,%35,%36,%37,%38,%39"
#define WG_BOTH(TXT_PRE, TXT_POST, OUTS, ...)                                                   \
    if (acc) asm volatile(TXT_PRE "1" TXT_POST : OUTS("+f") : __VA_ARGS__);                     \
    else asm volatile(TXT_PRE "0" TXT_POST : OUTS("=f") : __VA_ARGS__)
#define O8(c) F8(c, d, 0)
#define O16(c) F8(c, d, 0), F8(c, d, 8)
#define O32(c) O16(c), F8(c, d, 16), F8(c, d, 24)
#define O40(c) O32(c), F8(c, d, 32)
#define WGM(n) "wgmma.mma_async.sync.aligned.m64n" #n "k16.f32.bf16.bf16 "
__device__ __forceinline__ void wg_rs16(float* d, const uint32_t* a, uint64_t db, bool acc) {
    WG_BOTH(WGM(16) "{" R8L "}, {%8,%9,%10,%11}, %12, ", ", 1, 1, 1;", O8, "r"(a[0]), "r"(a[1]), "r"(a[2]), "r"(a[3]), "l"(db));
}
__device__ __forceinline__ void wg_ss16(float* d, uint64_t da, uint64_t db, bool acc) {
    WG_BOTH(WGM(16) "{" R8L "}, %8, %9, ", ", 1, 1, 1, 1;", O8, "l"(da), "l"(db));
}
__device__ __forceinline__ void wg_rs8(float* d, const uint32_t* a, uint64_t db, bool acc) {
#define O4(c) c(d[0]), c(d[1]), c(d[2]), c(d[3])
    WG_BOTH(WGM(8) "{%0,%1,%2,%3}, {%4,%5,%6,%7}, %8, ", ", 1, 1, 0;", O4, "r"(a[0]), "r"(a[1]), "r"(a[2]), "r"(a[3]), "l"(db));
}
__device__ __forceinline__ void wg_rs32(float* d, const uint32_t* a, uint64_t db, bool acc) {
    WG_BOTH(WGM(32) "{" R16L "}, {%16,%17,%18,%19}, %20, ", ", 1, 1, 0;", O16, "r"(a[0]), "r"(a[1]), "r"(a[2]), "r"(a[3]), "l"(db));
}
__device__ __forceinline__ void wg_ss32(float* d, uint64_t da, uint64_t db, bool acc) {
    WG_BOTH(WGM(32) "{" R16L "}, %16, %17, ", ", 1, 1, 1, 0;", O16, "l"(da), "l"(db));
}
template <int TB> __device__ __forceinline__ void wg_rs64(float* d, const uint32_t* a, uint64_t db, bool acc) {
    WG_BOTH(WGM(64) "{" R32L "}, {%32,%33,%34,%35}, %36, ", ", 1, 1, %37;", O32, "r"(a[0]), "r"(a[1]), "r"(a[2]), "r"(a[3]), "l"(db), "n"(TB));
}
template <int TB> __device__ __forceinline__ void wg_ss64(float* d, uint64_t da, uint64_t db, bool acc) {
    WG_BOTH(WGM(64) "{" R32L "}, %32, %33, ", ", 1, 1, 1, %34;", O32, "l"(da), "l"(db), "n"(TB));
}
__device__ __forceinline__ void wg_ss80(float* d, uint64_t da, uint64_t db, bool acc) {
    WG_BOTH(WGM(80) "{" R40L "}, %40, %41, ", ", 1, 1, 1, 1;", O40, "l"(da), "l"(db));
}

constexpr float SM_SCALE = 0.08838834764831845f;
constexpr float LOG2E = 1.4426950408889634f;

#define WO_DELAY 3000
#define D_DELAY 7000
#define F1_DELAY 7000
#define W2_DELAY 16500
#define F1_DEPTH 30
#define PF_DELAY 6000
#define PF_PACE 400
__device__ __forceinline__ void hold_back(uint32_t ns) {
    const uint32_t t0 = timer_lo();
    while (timer_lo() - t0 < ns) __nanosleep(50);
}

__device__ __forceinline__ uint32_t* flag_ptr(int stage, int b) { return &g_flag[stage][b][0]; }
__device__ __forceinline__ uint32_t this_launch() { return ld_rlx(&g_epoch[fresh_bid()][0]) + 1; }
__device__ __forceinline__ bool flag_up(int stage, int b, uint32_t target) { return (int)(ld_rlx(flag_ptr(stage, b)) - target) >= 0; }
__device__ __forceinline__ void flag_wait(int stage, int b, uint32_t target) {
    [[maybe_unused]] int n = 0;
    while (!flag_up(stage, b, target)) {
        __nanosleep(20);
        SPIN_CHECK(n, 10 + stage);
    }
    fence_acq_gpu();
    fence_async_glb();
}
__device__ __forceinline__ void publish(int stage, int b) {
    fence_async_glb();
    fence_rel_gpu();
    red_add_u32(flag_ptr(stage, b), 1);
}
__device__ __forceinline__ uint32_t unit_frag_addr(int tid) {
    const int lane = tid & 31, w = (tid >> 5) & 3, i = lane & 7, j = lane >> 3;
    return ((j >> 1) * 8 + i) * 128 + ((((w << 1) + (j & 1)) ^ i) << 4);
}

#define V_BURST1 3
#define V_BURST2 1
#define V_PRE 9
#define SX_BF16 0
#define V_REV 1
#define K_GATE 1
#define WO_R8 0
#define OX_V4 0
#define V_LEAD 8
static_assert((V_BURST1 + V_BURST2 >= 2 || V_PRE == 7) && V_BURST1 <= 3 && V_LEAD > V_BURST1 + V_BURST2, "q and k rely on v for the arrival of the blocks");
#define K_LEAD 0
#define Q_LEAD 36
#define V_FIRST 8
#define SX_GATE 1
static_assert(SX_GATE, "EB_QF also stands for the K tile");
#define V_EARLY 0
__host__ __device__ constexpr int x_order(int mat, int j) {
    return mat == 2 ? j : j < 3 ? j + 5 : j < 5 ? j : j == 5 ? 2 : j == 6 ? 8 : 8 - j;
}
#define SS0Q 0
#define SS0K 0
#define SS0V 22
#define SSLQ 36
#define SSLK 36
#define SSLV 14
__host__ __device__ constexpr uint64_t ss_mask(int mat) {
    const int ns = 36 - (mat == 0 ? NRQ : mat == 1 ? NRK : NRV);
    const int j0 = mat == 0 ? SS0Q : mat == 1 ? SS0K : SS0V, len = mat == 0 ? SSLQ : mat == 1 ? SSLK : SSLV;
    uint64_t m = 0;
    for (int j = j0; j < j0 + len; j++)
        if ((j - j0) * ns / len != (j - j0 + 1) * ns / len) m |= 1ull << (x_order(mat, j >> 2) * 4 + (j & 3));
    return m;
}
__device__ __forceinline__ int popc_below(uint64_t m, int k) { return __popcll(m & ((1ull << k) - 1)); }
__host__ __device__ constexpr int x_slot(int f) {
    return f < 3 ? E_R0 + f * 8192 : f == 3 ? E_QT : f == 4 ? E_KT : f < 7 ? E_MEM + (f - 5) * 8192 : f == 8 ? E_R2 : f == 10 ? E_R1 : E_R0;
}
__host__ __device__ constexpr int x_full(int f) { return f < 3 ? 0 : f < 9 ? (f - 1) / 2 : 14 - f; }
__host__ __device__ constexpr bool x_first(int f) { return f == 0 || x_full(f) != x_full(f - 1); }
__host__ __device__ constexpr int x_empty(int blk) { return blk == 6 ? 0 : blk == 7 ? 1 : blk == 4 ? 2 : -1; }
__host__ __device__ constexpr int ar_tile(int j) { return j == 0 ? 8 : ((j - 1) & 1) * 4 + ((j - 1) >> 1); }
__host__ __device__ constexpr int sx_off(int u) { return u == 0 ? 0 : u == 1 ? 1536 : u == 2 ? 2560 : u == 3 ? 3072 : 5120; }

template <int MAT, int NR, int K0, int K1>
__device__ __forceinline__ void proj_mem(float* d, const uint32_t (&w)[NR][4]) {
    constexpr uint64_t M = ss_mask(MAT);
    const uint64_t db = mkdesc(E_MEM, 128, 9216, 0);
    const uint64_t da = mkdesc((MAT == 0 ? E_WQ : MAT == 1 ? E_WK : E_WV), 1024, 1024, 1);
#pragma unroll
    for (int j = K0; j < K1; j++) {
        const int ks = MAT == 2 && V_REV ? 35 - j : j, s = popc_below(M, ks);
        if ((M >> ks) & 1) wg_ss16(d, da + s * 128, db + ks * 16, j > 0);
        else wg_rs16(d, w[ks - s], db + ks * 16, j > 0);
    }
}
__device__ __forceinline__ uint32_t tl_lane(int tid, int group_bytes) {
    return ((tid >> 4) & 1) * group_bytes + (((tid >> 5) & 3) * 16 + (tid & 15)) * 16;
}
struct ArWords {
    uint32_t w[5];
    __device__ __forceinline__ ArWords(const float* y) {
        w[0] = pack2(y[0], y[1]); w[1] = pack2(y[2], y[3]); w[2] = pack2(y[4], y[5]); w[3] = pack2(y[6], 1.f); w[4] = pack2(y[7], 1.f);
    }
    __device__ __forceinline__ void force(uint32_t zero) {
        asm volatile("{.reg .pred p; setp.ne.u32 p, %0, 0; @p st.shared.v4.b32 [%5], {%1,%2,%3,%4};}" :: "r"(zero), "r"(w[0]), "r"(w[1]), "r"(w[2]), "r"(w[3]), "r"(w[4]) : "memory");
    }
    __device__ __forceinline__ void red(uint8_t* p, uint8_t* q) {
        asm volatile("red.relaxed.gpu.global.add.noftz.v4.bf16x2 [%0], {%1,%2,%3,%4};" :: "l"(p), "r"(w[0]), "r"(w[1]), "r"(w[2]), "r"(w[3]) : "memory");
        asm volatile("red.relaxed.gpu.global.add.noftz.bf16x2 [%0], %1;" :: "l"(q), "r"(w[4]) : "memory");
    }
};
__device__ __forceinline__ uint32_t ar_main(int tid) { return ((tid & 127) >> 3) * AR_STR + (tid & 7) * 16; }
__device__ __forceinline__ uint32_t ar_side(int tid) { return ((tid & 127) >> 5) * (4 * AR_STR) + AR_STR / 2 + (tid & 31) * 4; }

#define AR_VA -1
#define AR_VA1 0
#define AR_SPLIT 5
template <bool B> struct Bool { static constexpr bool value = B; };
template <int J0, int J1>
__device__ __forceinline__ void ar_fetch(const uint8_t* pm, const uint8_t* ps, uint32_t a, bool& bad0, bool& bad1, uint32_t gate = 0, uint32_t par = 0) {
    uint4 av[9];
    uint32_t as[9];
#pragma unroll
    for (int j = J0; j < J1; j++) { av[j] = ld_rlx128(pm + ar_tile(j) * (16 * AR_STR)); as[j] = ld_rlx(ps + ar_tile(j) * (16 * AR_STR)); }
    if (gate) mbar_wait(gate, par);
    if (J0 == 0) bad0 = false;
    if (J1 == 9) bad1 = false;
#pragma unroll
    for (int j = J0; j < J1; j++) {
        (j < AR_SPLIT ? bad0 : bad1) |= __byte_perm(av[j].w, as[j], 0x7632) != (ar_tile(j) == 8 ? 0x42804280u : 0x42004200u);
        stsm4(a + ar_tile(j) * 1024, av[j].x, av[j].y, av[j].z, __byte_perm(av[j].w, as[j], 0x5410));
    }
}

__device__ __forceinline__ void attn_mem(float* d, uint32_t par, int i, int tid) {
    const int lane = tid & 31, warp = tid >> 5, c = warp >> 1, hf = warp & 1;
    const int rank = cta_rank();
    const uint32_t peer = mapa(sb, rank ^ 1);
    const uint32_t l4 = (lane >> 4) * 1024 + (lane & 15) * 16;
    uint32_t kb[4][4];
    {
        const uint32_t aK = sb + E_KT + (c * 6 + hf * 2) * 1024 + l4;
#pragma unroll
        for (int ks = 0; ks < 4; ks++) ldsm4t(kb[ks], aK + ks * 256);
    }
    const uint32_t aQs = pin(sb + E_QM + tl_lane(tid, 1024));
    const uint32_t aQ = pin(sb + E_QM + c * 1024 + (((lane >> 3) & 1) * 16 + (lane >> 4) * 8 + (lane & 7)) * 16);
    const uint32_t aM = pin(sb + E_KT + (4 + c) * 1024 + lane * 16);
    const uint32_t oS = pin(tid * 16);
    wg_wait_acc<0, 8>(d);
    stsm4(aQs, pack2(d[0], d[1]), pack2(d[2], d[3]), pack2(d[4], d[5]), pack2(d[6], d[7]));
    nbar_sync(NB_QK, 256);
    TS(0, i, 1);
    float s[6];
    {
        uint32_t q[2][4], km[2][4];
        ldsm4t(q[0], aQ); ldsm4t(km[0], aM); ldsm4t(q[1], aQ + 512); ldsm4t(km[1], aM + 512);
        float a[6][4];
#pragma unroll
        for (int m = 0; m < 6; m++) a[m][0] = a[m][1] = a[m][2] = a[m][3] = 0.f;
#pragma unroll
        for (int j = 0; j < 2; j++) {
#pragma unroll
            for (int o = 0; o < 2; o++) {
                mma16816(a[o * 3], q[j], kb[2 * j + o][0], kb[2 * j + o][1]);
                mma16816(a[o * 3 + 1], q[j], kb[2 * j + o][2], kb[2 * j + o][3]);
            }
            mma16816(a[2], q[j], km[j][0], km[j][1]);
            mma16816(a[5], q[j], km[j][2], km[j][3]);
        }
        nbar_arrive(NB_S, 256);
        if (SX_GATE) nbar_arrive(NB_S2, 256);
#pragma unroll
        for (int m = 0; m < 3; m++) { s[2 * m] = a[m][0] + a[3 + m][2]; s[2 * m + 1] = a[m][1] + a[3 + m][3]; }
    }
    st_async128(peer + E_SR + oS, fu(s[0]), fu(s[1]), fu(s[2]), fu(s[3]), peer + SM_BAR + EB_SM * 8);
    const uint32_t oM = E_SR + 2048 + c * 256 + lane * 8;
    asm volatile("st.async.shared::cluster.mbarrier::complete_tx::bytes.b32 [%0], %1, [%2];"
                 :: "r"(peer + oM + hf * 4), "r"(fu(hf ? s[5] : s[4])), "r"(peer + SM_BAR + EB_SM * 8) : "memory");
    sts128(sb + E_SL + oS, fu(s[0]), fu(s[1]), fu(s[2]), fu(s[3]));
    mbar_arrive_warp(bars + EB_KF * 8);
    TS(0, i, 2);
#pragma unroll
    for (int j = 0; j < 4; j++) ldsm4(kb[j], sb + E_VT + c * 6144 + l4 + hf * 512 + ((j >> 1) ^ hf) * 2048 + (j & 1) * 256);
    nbar_sync(NB_G, 128);
    const uint32_t aR = sb + E_SR + oS, aR1 = sb + E_SR + (oS ^ 512), aRm = sb + oM;
    const uint4 l1 = lds128(aR1 + (E_SL - E_SR));
    mbar_wait_cl(bars + EB_SM * 8, par);
    TS(0, i, 3);
    float p[10];
    {
        const uint4 r0 = lds128(aR), r1 = lds128(aR1);
        const uint2 rm = lds64(aRm);
        p[0] = s[0] + uf(r0.x); p[1] = s[1] + uf(r0.y); p[2] = s[2] + uf(r0.z); p[3] = s[3] + uf(r0.w);
        p[4] = uf(l1.x) + uf(r1.x); p[5] = uf(l1.y) + uf(r1.y); p[6] = uf(l1.z) + uf(r1.z); p[7] = uf(l1.w) + uf(r1.w);
        p[8] = s[4] + uf(rm.x); p[9] = s[5] + uf(rm.y);
    }
    float mx = fmaxf(fmaxf(fmaxf(p[0], p[1]), fmaxf(p[2], p[3])), fmaxf(fmaxf(fmaxf(p[4], p[5]), fmaxf(p[6], p[7])), fmaxf(p[8], p[9])));
    mx = fmaxf(mx, __shfl_xor_sync(~0u, mx, 1));
    mx = fmaxf(mx, __shfl_xor_sync(~0u, mx, 2));
    const float mo = mx * (SM_SCALE * LOG2E);
    mbar_wait(bars + EB_KF * 8, par);
    uint32_t vm[4], pb[5];
    ldsm4(vm, aM + (E_VT - E_KT) + hf * 512);
    float o[3][4];
    const uint32_t ones[4] = {0x3f803f80u, 0x3f803f80u, 0x3f803f80u, 0x3f803f80u};
#pragma unroll
    for (int T = 0; T < 3; T++) o[T][0] = o[T][1] = o[T][2] = o[T][3] = 0.f;
#pragma unroll
    for (int j = 0; j < 2; j++) {
#pragma unroll
        for (int m = 2 * j; m < 2 * j + 2; m++) pb[m] = pack2(ex2(fmaf(p[2 * m], SM_SCALE * LOG2E, -mo)), ex2(fmaf(p[2 * m + 1], SM_SCALE * LOG2E, -mo)));
        mma16816(o[2], ones, pb[2 * j], pb[2 * j + 1]);
#pragma unroll
        for (int T = 0; T < 2; T++) mma16816(o[T], kb[2 * j + T], pb[2 * j], pb[2 * j + 1]);
    }
    pb[4] = pack2(ex2(fmaf(p[8], SM_SCALE * LOG2E, -mo)), ex2(fmaf(p[9], SM_SCALE * LOG2E, -mo)));
    mma1688(o[2], ones[0], ones[1], pb[4]);
#pragma unroll
    for (int T = 0; T < 2; T++) mma1688(o[T], vm[2 * T], vm[2 * T + 1], pb[4]);
    nbar_arrive(NB_PV, 256);
    mbar_arrive_warp(bars + EB_CONS * 8);
    const float i0 = rcp(o[2][0]), i1 = rcp(o[2][1]);
    uint32_t ow[4];
#pragma unroll
    for (int j = 0; j < 4; j++) ow[j] = pack2(o[j >> 1][2 * (j & 1)] * i0, o[j >> 1][2 * (j & 1) + 1] * i1);
    const uint32_t oO = E_OM + c * 2048 + hf * 512;
    stsm4(sb + oO + lane * 16, ow[0], ow[1], ow[2], ow[3]);
    if (OX_V4) {
        __syncwarp();
        const uint4 r = lds128(sb + oO + lane * 16);
        nbar_sync(NB_G, 128);
        st_async128(peer + oO + 1024 + lane * 16, r.x, r.y, r.z, r.w, peer + SM_BAR + EB_OX * 8);
    } else {
#pragma unroll
        for (int j = 0; j < 4; j++)
            asm volatile("st.async.shared::cluster.mbarrier::complete_tx::bytes.b32 [%0], %1, [%2];"
                         :: "r"(peer + oO + 1024 + j * 128 + lane * 4), "r"(ow[j]), "r"(peer + SM_BAR + EB_OX * 8) : "memory");
    }
}

__device__ __forceinline__ void attn_x_scores(float (&p)[2][10], uint32_t par, int i, int tid) {
    {
        float s[40];
        const uint64_t da = mkdesc(E_QT, 128, 1024, 0), db = mkdesc(E_KT, 128, 1024, 0);
        wg_fence();
#pragma unroll
        for (int ks = 0; ks < 4; ks++) wg_ss80(s, da + ks * 16, db + ks * 16, ks > 0);
        wg_commit();
        const int dq = (tid >> 2) - 2 * (tid & 3);
        float mask[8];
#pragma unroll
        for (int j = 0; j < 8; j++) mask[j] = (j >> 1) * 8 + (j & 1) > dq ? -1e9f * LOG2E : 0.f;
        mbar_wait_cl(bars + EB_PRDY * 8, par);
        wg_wait_acc<0, 40>(s);
#pragma unroll
        for (int u = 0; u < 5; u++) {
            const int v = u < 4 ? 6 + u : 5;
            constexpr float C = SM_SCALE * LOG2E;
            const float m0 = u < 4 ? mask[2 * u & 7] : 0.f, m1 = u < 4 ? mask[(2 * u + 1) & 7] : 0.f;
            p[0][2 * u] = fmaf(s[4 * u], C, m0); p[0][2 * u + 1] = fmaf(s[4 * u + 1], C, m1); p[1][2 * u] = fmaf(s[4 * v + 2], C, m0); p[1][2 * u + 1] = fmaf(s[4 * v + 3], C, m1);
        }
    }
    mbar_arrive_warp(bars + EB_QF * 8);
    const int w = tid >> 5;
    if (!SX_BF16) {
        const uint32_t peer = mapa(sb, cta_rank() ^ 1);
#pragma unroll
        for (int u = 0; u < 5; u++)
            if (u == 0 || u <= w || u == 4) st_async128(peer + E_SX + sx_off(u) + tid * 16, fu(p[0][2 * u]), fu(p[0][2 * u + 1]), fu(p[1][2 * u]), fu(p[1][2 * u + 1]), peer + SM_BAR + EB_SX * 8);
    } else {
        const uint32_t peer = mapa(sb, cta_rank() ^ 1), a = peer + E_SX + tid * 16, mb = peer + SM_BAR + EB_SX * 8;
        st_async128(a, pack2(p[0][0], p[0][1]), pack2(p[1][0], p[1][1]), pack2(p[0][8], p[0][9]), pack2(p[1][8], p[1][9]), mb);
        if (w >= 1) st_async128(a + 2048, pack2(p[0][2], p[0][3]), pack2(p[1][2], p[1][3]), pack2(p[0][4], p[0][5]), pack2(p[1][4], p[1][5]), mb);
        if (w >= 3) st_async64(a + 4096, pack2(p[0][6], p[0][7]), pack2(p[1][6], p[1][7]), mb);
    }
    TS(128, i, 10);
}
__device__ __forceinline__ void attn_x_finish(float (&p)[2][10], uint32_t par, int i, int& tid, uint32_t zero) {
    const int w = tid >> 5;
    mbar_wait_cl(bars + EB_SX * 8, par);
    TS(128, i, 11);
    if (SX_BF16) {
        const uint32_t a = sb + E_SX + tid * 16;
        const uint4 r0 = lds128(a), r1 = lds128(a + (w >= 1 ? 2048 : 0));
        const uint2 r2 = lds64(a + (w >= 3 ? 4096 : 0));
        const uint32_t r[10] = {r0.x, r0.y, r1.x, r1.y, r1.z, r1.w, r2.x, r2.y, r0.z, r0.w};
#pragma unroll
        for (int j = 0; j < 10; j++) { p[j & 1][j & ~1] += bf_lo(r[j]); p[j & 1][j | 1] += bf_hi(r[j]); }
    } else
#pragma unroll
    for (int u = 0; u < 5; u++) {
        const uint4 r = lds128(pin(sb + tid * 16 + (u == 0 || u <= w ? sx_off(u) : sx_off(4))) + E_SX);
        p[0][2 * u] += uf(r.x); p[0][2 * u + 1] += uf(r.y); p[1][2 * u] += uf(r.z); p[1][2 * u + 1] += uf(r.w);
    }
    nbar_sync(NB_W, 128);
    uint32_t pa[5][4];
    float mx[2], inv[2];
#pragma unroll
    for (int h = 0; h < 2; h++) {
        const float* q = p[h];
        mx[h] = fmaxf(fmaxf(fmaxf(q[0], q[1]), fmaxf(q[2], q[3])), fmaxf(fmaxf(fmaxf(q[4], q[5]), fmaxf(q[6], q[7])), fmaxf(q[8], q[9])));
    }
#pragma unroll
    for (int o = 1; o < 4; o <<= 1) { mx[0] = fmaxf(mx[0], __shfl_xor_sync(~0u, mx[0], o)); mx[1] = fmaxf(mx[1], __shfl_xor_sync(~0u, mx[1], o)); }
#pragma unroll
    for (int h = 0; h < 2; h++) {
        float* q = p[h];
#pragma unroll
        for (int j = 0; j < 10; j++) q[j] = ex2(q[j] - mx[h]);
#pragma unroll
        for (int u = 0; u < 4; u++) {
            pa[h * 3 + (u >> 1)][(u & 1) * 2 + h] = pack2(q[2 * u], q[2 * u + 1]);
            pa[h * 3 + (u >> 1)][(u & 1) * 2 + (h ^ 1)] = zero << (h * 5 + u + 1);
        }
        pa[2][h * 3] = pack2(q[8], q[9]);
        pa[2][1 + h] = zero << (h * 5 + 5);
    }
    mbar_wait(bars + EB_CONS * 8, par);
    fence_async_smem();
    tid = pin(tid << zero);
    const uint32_t aO = pin(sb + (((tid >> 4) & 1) * 8 + (tid & 7)) * 128 + (((((tid >> 3) & 1) * 4 + (tid >> 5)) ^ (tid & 7)) << 4)) + E_R1;
    TS(128, i, 12);
#pragma unroll
    for (int nh = 0; nh < 2; nh++) {
        float o[16], sum[4];
        const uint64_t db = mkdesc(E_VT + nh * 512, 1024, 128, 0);
        wg_fence();
#pragma unroll
        for (int kk = 0; kk < 5; kk++) {
            if (nh == 0) wg_rs8(sum, pa[kk], mkdesc(SM_ONES, 0, 0, 0), kk > 0);
            wg_rs32(o, pa[kk], db + kk * 128, kk > 0);
        }
        wg_commit();
        wg_wait_acc<0, 16>(o);
        if (nh == 0) { acc_ready<4>(sum); inv[0] = rcp(sum[0]); inv[1] = rcp(sum[2]); }
#pragma unroll
        for (int j = 0; j < 2; j++) {
            const float* y = &o[8 * j];
            stsm4t(aO + nh * 4096 + j * 2048, pack2(y[0] * inv[0], y[1] * inv[0]), pack2(y[2] * inv[1], y[3] * inv[1]), pack2(y[4] * inv[0], y[5] * inv[0]), pack2(y[6] * inv[1], y[7] * inv[1]));
        }
    }
    mbar_arrive_warp(bars + EB_OST * 8);
    TS(128, i, 13);
}

template <int MAT>
__device__ __forceinline__ void engine_main(const Params& P) {
    constexpr int NR = MAT == 0 ? NRQ : MAT == 1 ? NRK : NRV;
    constexpr uint64_t M = ss_mask(MAT);
    uint32_t w[NR][4];
    {
        const uint32_t a = sb + E_WO + (MAT == 0 ? 0 : MAT == 1 ? NRQ : NRQ + NRK) * 2048 + unit_frag_addr(fresh_tid());
        mbar_wait(bars + EB_WL * 8, 0);
        if (MAT == 0 && threadIdx.x == 0) TG(79, 2);
#pragma unroll
        for (int u = 0; u < NR; u++) ldsm4t(w[u], a + u * 2048);
    }
    nbar_arrive(NB_T, 448);
    int tid = fresh_tid() - MAT * 128;
#define TID (tid = pin(tid << P.zero))
    if (MAT == 0) { if (V_FIRST == 36) nbar_arrive(NB_S, 256); nbar_arrive(NB_PV, 256); nbar_arrive(NB_WO, 256); }
    auto project = [&](auto one, const int i) {
        constexpr bool ONE = decltype(one)::value;
        const uint32_t par = i & 1;
        {
            float d[ONE ? 16 : 32];
            const uint64_t da = mkdesc((MAT == 0 ? E_WQ : MAT == 1 ? E_WK : E_WV), 1024, 1024, 1);
            constexpr int R1 = V_BURST1, R2 = V_BURST1 + V_BURST2;
#pragma unroll
            for (int n = 0; n < 9; n++) {
                const int blk = x_order(MAT, n), prev = n ? x_order(MAT, n - 1) : -1, f = MAT != 2 && blk < 2 ? 9 + blk : blk;
                if (MAT == 2) {
                    if (R2 >= 2 && n == (R1 >= 2 ? R1 : R2)) { wg_wait<0>(); mbar_arrive_warp(bars + EB_V0 * 8); }
                    if ((n == 0 && (V_FIRST == 36 || i == 0)) || n == R1 || n == R2) {
#pragma unroll
                        for (int j = n; j < (n < R1 ? R1 : n < R2 ? R2 : V_PRE); j++) if (x_first(j)) mbar_wait(bars + (EB_FULL + x_full(j)) * 8, par);
                    }
                    if (n == 0 && V_FIRST == 36) nbar_sync(NB_S, 256);
                    if (n == R1) nbar_sync(NB_PV, 256);
                    if (n == R2) nbar_sync(NB_WO, 256);
                } else {
                    if (n == 0) nbar_sync(MAT ? NB_VL : NB_VL2, 256);
                }
                static_assert(V_PRE == 9 || (V_PRE == 7 && V_LEAD > 7), "see the barriers");
                const bool wt = MAT == 2 ? f == V_PRE : f >= 9;
                if (wt) mbar_wait(bars + (EB_FULL + x_full(f)) * 8, par);
                TX(MAT * 128, 1 + MAT * 9 + n);
                if (wt || n == 0 || (MAT == 2 && (n == R1 || n == R2))) wg_fence();
                if (n == 0) TS(MAT * 128, i, 20 + MAT);
                const uint64_t db = mkdesc(x_slot(f), 16, 1024, 1);
#pragma unroll
                for (int j = 0; j < 4; j++) {
                    const int ks = blk * 4 + j, s = popc_below(M, ks);
                    if constexpr (ONE) {
                        if ((M >> ks) & 1) wg_ss32(d, da + s * 128, db + j * 2, n + j > 0);
                        else wg_rs32(d, w[ks - s], db + j * 2, n + j > 0);
                    } else {
                        if ((M >> ks) & 1) wg_ss64<0>(d, da + s * 128, db + j * 2, n + j > 0);
                        else wg_rs64<0>(d, w[ks - s], db + j * 2, n + j > 0);
                    }
                }
                wg_commit();
                if (MAT == 2 && n + 1 == V_LEAD) { nbar_arrive(NB_VL, 256); if (!K_LEAD) nbar_arrive(NB_VL2, 256); }
                if (MAT == 1 && n + 1 == K_LEAD) nbar_arrive(NB_VL2, 256);
                if (MAT == 2 && R2 < 2 && n == 3) { wg_wait<2>(); mbar_arrive_warp(bars + EB_V0 * 8); }
                if (MAT != 2 && x_empty(prev) >= 0) { wg_wait<1>(); mbar_arrive_warp(bars + (EB_EMPTY + x_empty(prev)) * 8); }
            }
            const uint32_t a = sb + (MAT == 0 ? E_QT : MAT == 1 ? E_KT : E_VT) + tl_lane(TID, MAT == 0 ? 2048 : 1024) + (ONE && i >= NSEG ? (MAT == 0 ? 1024 : 6144) : 0);
            if (MAT != 2) {
                mbar_wait(bars + (EB_EMPTY + 2) * 8, par);
                if (!ONE) mbar_wait(bars + EB_MEM * 8, par);
            } else {
                mbar_wait(bars + EB_OST * 8, par ^ 1);
            }
            wg_wait_acc<0, ONE ? 16 : 32>(d);
            TS(MAT * 128, i, 23 + MAT);
#pragma unroll
            for (int j = 0; j < (ONE ? 4 : 8); j += 2) {
                const int grp = MAT == 0 ? 2 * (j & 3) + (j >> 2) : j < 4 ? j : j + 2;
                stsm4(a + grp * 1024, pack2(d[4 * j], d[4 * j + 1]), pack2(d[4 * j + 2], d[4 * j + 3]), pack2(d[4 * j + 4], d[4 * j + 5]), pack2(d[4 * j + 6], d[4 * j + 7]));
            }
        }
        if (MAT != 2) {
            if (ONE) mbar_arrive_warp(bars + EB_STEP * 8);
            if (ONE) mbar_wait(bars + EB_MEM * 8, par);
        } else {
            __syncwarp();
            if ((TID & 31) < 3) mbar_arrive(bars + (EB_EMPTY + (tid & 31)) * 8);
        }
    };
    auto step = [&](const int i) {
        const uint32_t par = i & 1;
        if (MAT == 2) {
            if (Q_LEAD) nbar_sync(NB_OM, K_GATE ? 384 : 256);
            else mbar_wait(bars + EB_MEM * 8, par);
        }
        float d[8];
        TS(MAT * 128, i, MAT == 2 ? 26 : 14 + MAT);
        wg_fence();
        constexpr int MID = MAT == 2 ? V_FIRST : Q_LEAD;
        proj_mem<MAT, NR, 0, MID>(d, w);
        if ((MAT == 0 || (MAT == 1 && K_GATE)) && Q_LEAD) nbar_arrive(NB_OM, K_GATE ? 384 : 256);
        if (MAT == 2 && V_FIRST < 36) {
            if (V_BURST1) mbar_wait(bars + EB_FULL * 8, i == NSTEP - 1 ? par : par ^ 1);
            nbar_sync(NB_S, 256);
            wg_fence();
        }
        proj_mem<MAT, NR, MID, 36>(d, w);
        wg_commit();
        if (MAT == 0) {
            mbar_wait(bars + EB_WO * 8, 0);
            tid *= mbar_wait(bars + EB_STEP * 8, par);
            attn_mem(d, par, i, tid);
        } else if (MAT == 1) {
            tid *= mbar_wait(bars + EB_STEP * 8, par);
            const uint32_t a = pin(sb + E_KT + 4096 + tl_lane(tid, 1024));
            wg_wait_acc<0, 8>(d);
            stsm4(a, pack2(d[0], d[1]), pack2(d[2], d[3]), pack2(d[4], d[5]), pack2(d[6], d[7]));
            nbar_arrive(NB_QK, 256);
            TS(128, i, 18);
            fence_async_smem();
            nbar_sync(SX_GATE ? NB_S2 : NB_W, SX_GATE ? 256 : 128);
            float p[2][10];
            attn_x_scores(p, par, i, TID);
            attn_x_finish(p, par, i, TID, pin(P.zero));
        } else {
            const uint32_t a = pin(sb + E_VT + 4096 + tl_lane(TID, 1024));
            wg_wait_acc<0, 8>(d);
            stsm4(a, pack2(d[0], d[1]), pack2(d[2], d[3]), pack2(d[4], d[5]), pack2(d[6], d[7]));
            mbar_arrive_warp(bars + EB_KF * 8);
            TS(256, i, 16);
        }
        if (MAT == 0) {
            const int rank = cta_rank();
            uint8_t* const ar = g_ar + (i & 3) * AR_SLOT;
            uint8_t* const pm = ar + pin(ar_main(TID) + rank * (64 * AR_STR));
            uint8_t* const ps = ar + pin(ar_side(tid) + rank * (64 * AR_STR));
            const uint32_t o8 = (128 - rank * 64) * AR_STR;
            const uint64_t db = mkdesc(E_OM, 128, 2048, 0), da = mkdesc(E_WO, 1024, 1024, 1);
            if (!OX_V4) nbar_sync(NB_G, 128);
            fence_async_smem();
            TS(0, i, 6);
            if (i == NSTEP - 1) { mbar_wait_cl(bars + EB_OX * 8, par); return; }
            float y[4][8];
            wg_fence();
#pragma unroll
            for (int ks = 0; ks < 4; ks++) wg_ss16(y[3], da + (32 + ks) * 128, db + ks * 16, ks > 0);
            wg_commit();
#pragma unroll
            for (int j = 0; j < 12; j++) wg_ss16(y[j % 3], da + ((j % 3) * 8 + j / 3) * 128, db + (j / 3) * 16, j >= 3);
            wg_commit();
            wg_wait_acc<1, 8>(y[3]);
            ArWords z(y[3]);
            if (WO_R8) z.red(pm + o8, ps + o8); else z.force(P.zero);
            mbar_wait_cl(bars + EB_OX * 8, par);
            fence_async_smem();
            wg_fence();
#pragma unroll
            for (int T = 0; T < 4; T++) {
#pragma unroll
                for (int ks = T < 3 ? 4 : 0; ks < 8; ks++) wg_ss16(y[T], da + (T * 8 + ks) * 128, db + ks * 16, ks > 0);
                wg_commit();
            }
            if (V_EARLY) nbar_arrive(NB_WO, 256);
            if (!WO_R8) z.red(pm + o8, ps + o8);
            wg_wait_acc<1, 8>(y[0]); acc_ready<8>(y[1]); acc_ready<8>(y[2]);
#pragma unroll
            for (int T = 0; T < 3; T++) ArWords(y[T]).red(pm + T * 16 * AR_STR, ps + T * 16 * AR_STR);
            wg_wait_acc<0, 8>(y[3]);
            ArWords(y[3]).red(pm + 48 * AR_STR, ps + 48 * AR_STR);
            if (!V_EARLY) nbar_arrive(NB_WO, 256);
            TS(0, i, 7);
        }
    };
    auto either = [&](const int i) {
        if (__builtin_expect(USE_ONE == 2 || (USE_ONE && (i < LAG || i >= NSEG)), MAT != 2)) project(Bool<true>(), i);
        else project(Bool<false>(), i);
    };
    if (MAT != 2) {
#pragma unroll 1
        for (int i = 0; i < NSTEP; i++) {
            either(i);
            if (!USE_ONE || (USE_ONE == 1 && i >= LAG && i < NSEG)) mbar_arrive_warp(bars + EB_STEP * 8);
            step(i);
        }
    } else {
#pragma unroll 1
        for (int i = -1; i < NSTEP; i++) {
            if (i >= 0) step(i);
            if (i < NSTEP - 1) {
                either(i + 1);
                const uint32_t par = (i & 1) ^ 1, slot = max(i, 0) & 3;
                const uint8_t* pm = g_ar + (slot * AR_SLOT + ar_main(TID));
                const uint8_t* ps = g_ar + (slot * AR_SLOT + ar_side(tid));
                const uint32_t a = sb + E_MEM + tl_lane(tid, 9216);
                asm volatile("{.reg .pred p; setp.ne.u32 p, %0, 0; @p st.shared.v2.b64 [%3], {%1,%2};}" :: "r"(P.zero), "l"(pm), "l"(ps), "r"(a) : "memory");
                const bool one = USE_ONE == 2 || (USE_ONE && (i + 1 < LAG || i + 1 >= NSEG));
                bool bad0, bad1;
                if (AR_VA >= 0 || one) mbar_wait(bars + (EB_EMPTY + (one ? AR_VA1 : AR_VA)) * 8, par);
                ar_fetch<0, AR_SPLIT>(pm, ps, a, bad0, bad1, bars + EB_EMPTY * 8, par);
                ar_fetch<AR_SPLIT, 9>(pm, ps, a, bad0, bad1);
                [[maybe_unused]] int n = 0;
                if (__any_sync(~0u, bad0 | bad1) || i < 0 || i + 1 == LAG) {
                    while (__any_sync(~0u, bad0) && i >= 0) { ar_fetch<0, AR_SPLIT>(pm, ps, a, bad0, bad1); SPIN_CHECK(n, 2); PROF_INC(n, 1); }
                    while (__any_sync(~0u, bad1) && i >= 0) { ar_fetch<AR_SPLIT, 9>(pm, ps, a, bad0, bad1); SPIN_CHECK(n, 2); PROF_INC(n, 0x10000); }
                    if (i < 0 || i + 1 == LAG) {
                        const uint16_t* m = (const uint16_t*)P.mem0 + (tid & 3) * (2 * DM) + (tid >> 5) * 16 + ((tid & 31) >> 2);
                        const uint32_t a2 = sb + E_MEM + (tid >> 5) * 256 + (tid & 31) * 4;
                        uint32_t v[18];
#pragma unroll
                        for (int T = 0; T < 18; T++) v[T] = (uint32_t)__ldg(m + (T >> 1) * 64 + (T & 1) * 8) | ((uint32_t)__ldg(m + (T >> 1) * 64 + (T & 1) * 8 + DM) << 16);
                        __syncwarp();
#pragma unroll
                        for (int T = 0; T < 18; T++) {
                            sts32(a2 + 9216 + (T >> 1) * 1024 + (T & 1) * 128, v[T]);
                            if (i < 0) sts32(a2 + (T >> 1) * 1024 + (T & 1) * 128, v[T]);
                        }
                    }
                }
                fence_async_smem();
                mbar_arrive_warp(bars + EB_MEM * 8);
            }
        }
    }
    if (MAT == 2) { if (V_FIRST == 36) nbar_sync(NB_S, 256); nbar_sync(NB_PV, 256); }
}

__device__ __forceinline__ void engine_helper(const Params& P) {
    const int lane = threadIdx.x & 31, hw = warp_in_group(), e = blockIdx.x, rank = e & 1;
    if (hw < 3) {
        constexpr uint64_t M0 = ss_mask(0), M1 = ss_mask(1), M2 = ss_mask(2);
        const uint64_t m = hw == 0 ? M0 : hw == 1 ? M1 : M2;
        const uint32_t ws = sb + (hw == 0 ? E_WQ : hw == 1 ? E_WK : E_WV), wr = sb + E_WO + (hw == 0 ? 0 : hw == 1 ? NRQ : NRQ + NRK) * 2048;
        if (lane == 0) mbar_expect(bars + EB_WL * 8, 36 * 2048);
        __syncwarp();
        for (int ks = lane; ks < 36; ks += 32) {
            const int s = __popcll(m & ((1ull << ks) - 1));
            tma_unit(((m >> ks) & 1) ? ws + s * 2048 : wr + (ks - s) * 2048, hw == 0 ? &P.tmWq : hw == 1 ? &P.tmWk : &P.tmWv, ks, e, bars + EB_WL * 8);
        }
    }
    if (hw == 1) {
        hold_back(WO_DELAY);
        for (int u = lane; u < 36; u += 32)
            asm volatile("cp.async.bulk.prefetch.tensor.2d.L2.global [%0, {%1,%2}];"
                         :: "l"(&P.tmWo), "r"((u < 32 ? rank * 4 + (u >> 3) : 8) * 64), "r"(((e >> 1) * 8 + (u < 32 ? u & 7 : rank * 4 + (u & 3))) * 16) : "memory");
    }
    __syncwarp();
    if (hw < 2) nbar_sync(NB_T, 448);
    if (lane == 0) TG(79, 3);
    if (hw == 0) {
        if (lane == 0) {
#pragma unroll 1
            for (int n = 0; n < NSTEP; n++) {
                const uint32_t par = (n & 1) ^ 1;
                uint32_t rdy;
                do { asm volatile("ld.acquire.cta.shared.u32 %0, [%1];" : "=r"(rdy) : "r"(sb + SM_XRDY) : "memory"); } while (rdy <= n && (__nanosleep(20), true));
                fence_async_glb();
                TG(n, 30);
                const uint8_t* src = g_x + n * XIMG;
#pragma unroll
                for (int j = 0; j < 6; j++) {
                    const int f = j == 0 ? 0 : j < 4 ? 2 * j + 1 : 14 - j, blk = f < 9 ? f : f - 9, bytes = j == 0 ? 24576 : j < 4 ? 16384 : 8192;
                    if (j == 3 || j == 5) mbar_wait(bars + (j == 3 ? EB_V0 : EB_EMPTY + 1) * 8, par ^ 1);
                    else mbar_wait(bars + (j == 0 ? EB_STEP : j == 1 ? EB_QF : j == 2 ? EB_KF : EB_OFREE) * 8, par);
                    const uint32_t fb = bars + (EB_FULL + j) * 8;
                    mbar_expect(fb, bytes);
                    bulk_g2s(sb + x_slot(f), src + blk * 8192, bytes, fb);
                }
            }
        }
    } else if (hw == 1) {
        if (lane == 0) mbar_expect(bars + EB_WO * 8, 36 * 2048);
        __syncwarp();
        for (int u = lane; u < 36; u += 32)
            tma_unit(sb + E_WO + u * 2048, &P.tmWo, (e >> 1) * 8 + ((u & 7) ^ (rank * 4)), u < 32 ? rank * 4 + (u >> 3) : 8, bars + EB_WO * 8);
        __syncwarp();
        if (lane == 0) {
#pragma unroll 1
            for (int i = 0; i < NSTEP; i++) {
                mbar_wait(bars + EB_STEP * 8, i & 1);
                mbar_arrive_remote(mapa(sb, rank ^ 1) + SM_BAR + EB_PRDY * 8);
                mbar_wait(bars + EB_OST * 8, i & 1);
                fence_async_smem();
                bulk_s2g(g_o + (i & (RING - 1)) * O_BYTES + e * 8192, sb + E_R1, 8192);
                asm volatile("cp.async.bulk.commit_group;" ::: "memory");
                asm volatile("cp.async.bulk.wait_group.read 0;" ::: "memory");
                mbar_arrive(bars + EB_OFREE * 8);
                asm volatile("cp.async.bulk.wait_group 0;" ::: "memory");
                publish(F_O, i);
                TG(i, 31);
            }
        }
    } else if (hw == 2) {
        const int idx = e * 23 + lane, line = idx >> 3;
        uint8_t* z = g_ar + (line < 144 ? line * AR_STR : (line - 144) * (4 * AR_STR) + AR_STR / 2) + (idx & 7) * 16;
        if (lane < 23 && idx < 1440) { stg128(z, make_uint4(0, 0, 0, 0)); stg128(z + AR_SLOT, make_uint4(0, 0, 0, 0)); }
        __syncwarp();
        if (lane == 0) {
            publish(F_X0, B_ZERO);
            mbar_arrive(bars + EB_MEM * 8);
            flag_wait(F_X0, B_ZERO, NENG * this_launch());
            mbar_arrive(bars + EB_WO * 8);
            TG(79, 5);
        }
        __syncwarp();
#pragma unroll 1
        for (int i = 0; i < NSTEP; i++) {
            mbar_wait(bars + EB_MEM * 8, i & 1);
            if (lane < 3) mbar_expect(bars + (EB_SM + lane) * 8, lane == 0 ? 2560 : lane == 1 ? (SX_BF16 ? 3840 : 7168) : 2048);
            if (lane < 23 && idx < 1440) stg128(z + ((i + 2) & 3) * AR_SLOT, make_uint4(0, 0, 0, 0));
            __syncwarp();
            if (lane == 0) { fence_gpu(); mbar_arrive(bars + EB_MEM * 8); }
            __syncwarp();
        }
    } else {
        for (int j = lane; j < 72; j += 32) asm volatile("prefetch.global.L2 [%0];" :: "l"(P.mem0 + j * 64));
        const uint32_t ep = this_launch(), t0 = timer_lo();
        if (lane == 0) {
#pragma unroll 1
            for (int n = 0; n < NSTEP; n++) {
                while ((n < NSEG && !flag_up(F_X0, n, 16 * ep)) || (n >= LAG && !flag_up(F_X1, n - LAG, 16 * ep))) {
                    __nanosleep(20);
                    if (timer_lo() - t0 > TIME_LIMIT) break;
                }
                fence_acq_gpu();
                asm volatile("st.release.cta.shared.u32 [%0], %1;" :: "r"(sb + SM_XRDY), "r"(n + 1) : "memory");
            }
        }
    }
    __syncwarp();
}

__device__ __forceinline__ void f1_fetch(const Params& P, uint32_t dst, int f0, int ks0, int n) {
    const int tid = threadIdx.x & 127, r = tid >> 3, c = (tid & 3) * 2 + ((tid >> 2) & 1);
    const bf16* src = ((c & 1) ? P.w3 : P.w1) + (size_t)(ks0 * 16 + r) * FF + f0 + (c >> 1) * 8;
    dst += r * 128 + ((c ^ (r & 7)) << 4);
#pragma unroll 1
    for (int u = 0; u < n; u++) {
        asm volatile("cp.async.cg.shared.global [%0], [%1], 16;" :: "r"(dst + u * 2048), "l"(src + (size_t)u * 16 * FF) : "memory");
        asm volatile("cp.async.commit_group; cp.async.wait_group %0;" :: "n"(F1_DEPTH) : "memory");
    }
}
constexpr int R_BACKLOG = 6;
static_assert(R_BACKLOG <= RING, "the partial sums would be overwritten");
#define F1_LEAD 0
template <int a, bool second>
__device__ __forceinline__ void f1_tile(const uint32_t (&w)[NRF][4], uint32_t ws, int b) {
    constexpr bool RF = (a == 1) == second;
    const uint32_t par = b & 1;
    float d[32];
    const uint64_t da = mkdesc(ws, 1024, 1024, 1), db = mkdesc(F_X, 16, 1024, 1);
#pragma unroll
    for (int blk = 0; blk < 9; blk++) {
        if (a == 1 && !second && blk == 0 && F1_LEAD) nbar_sync(NB_QK, 256);
        const bool wt = blk == 0 || (!second && (a == 0 || blk >= F1_LEAD));
        if (wt) { mbar_wait(bars + (FB_FULL + blk) * 8, par); wg_fence(); }
#pragma unroll
        for (int j = 0; j < 4; j++) {
            const int ks = blk * 4 + j;
            if (RF && ks < NRF) wg_rs64<0>(d, w[ks < NRF ? ks : 0], db + blk * 512 + j * 2, ks > 0);
            else wg_ss64<0>(d, da + (RF ? ks - NRF : 36 - NRF + ks) * 128, db + blk * 512 + j * 2, ks > 0);
        }
        wg_commit();
        if (a == 0 && !second && blk + 1 == F1_LEAD) nbar_arrive(NB_QK, 256);
        if (blk > 0 && second) { wg_wait<1>(); mbar_arrive_warp(bars + (FB_EMPTY + blk - 1) * 8); }
    }
    const int tid = fresh_tid(), g = (tid & 31) >> 2;
    uint8_t* dst = g_h + (b & (RING - 1)) * H_BYTES + ((fresh_bid() - NENG + (second ? 37 : 0)) * 64 + a * 32 + ((tid >> 5) & 3) * 8 + g) * 128;
    if (!second) mbar_wait(bars + FB_RACK * 8, par ^ 1);
    wg_wait_acc<0, 32>(d);
    if (second) mbar_arrive_warp(bars + (FB_EMPTY + 8) * 8);
    uint32_t h[8];
#pragma unroll
    for (int j = 0; j < 8; j++) {
        const float g0 = d[4 * j], g1 = d[4 * j + 1];
        const float e0 = 1.f + ex2(fminf(-LOG2E * g0, 60.f)), e1 = 1.f + ex2(fminf(-LOG2E * g1, 60.f));
        const float r = rcp(e0 * e1);
        h[j] = pack2(g0 * d[4 * j + 2] * (e1 * r), g1 * d[4 * j + 3] * (e0 * r));
    }
    stg128(dst + (((tid & 3) ^ g) << 4), make_uint4(h[0], h[1], h[2], h[3]));
    stg128(dst + ((((tid & 3) + 4) ^ g) << 4), make_uint4(h[4], h[5], h[6], h[7]));
    mbar_arrive_warp(bars + (second ? FB_H2 : FB_H) * 8);
}
template <int a>
__device__ __forceinline__ void f1_main(const Params& P) {
    constexpr uint32_t ws = F_W + a * (72 - NRF) * 2048;
    const int f0 = (blockIdx.x - NENG) * 128 + a * 96;
    uint32_t w[NRF][4];
    hold_back(F1_DELAY);
    f1_fetch(P, sb + ws, f0, 0, NRF);
    asm volatile("cp.async.wait_all;" ::: "memory");
    nbar_sync(NB_G + a, 128);
    {
        const uint32_t fa = sb + ws + unit_frag_addr(threadIdx.x);
#pragma unroll
        for (int u = 0; u < NRF; u++) ldsm4t(w[u], fa + u * 2048);
    }
    nbar_sync(NB_G + a, 128);
    f1_fetch(P, sb + ws, f0, NRF, 36 - NRF);
    f1_fetch(P, sb + ws + (36 - NRF) * 2048, f0 + (a ? -64 : 64), 0, 36);
    asm volatile("cp.async.wait_all;" ::: "memory");
    fence_async_smem();
    nbar_sync(NB_G + a, 128);
    if (threadIdx.x == 0) TG(79, 2);
#pragma unroll 1
    for (int b = 0; b < NSTEP; b++) {
        f1_tile<a, false>(w, ws, b);
        f1_tile<a, true>(w, ws, b);
    }
}
__device__ __forceinline__ uint32_t n_pairs(int b) { return (b < NSEG ? 16 : 0) + (b >= LAG ? 16 : 0); }
__device__ __forceinline__ void publisher(uint32_t done, uint32_t ack, int stage) {
#pragma unroll 1
    for (int b = 0; b < NSTEP; b++) {
        if (stage == F_H2) { mbar_wait(done - 8, b & 1); publish(F_H, b); }
        mbar_wait(done, b & 1);
        mbar_arrive(ack);
        TG(b, 30);
        publish(stage, b);
        TG(b, 31);
    }
}
__device__ __forceinline__ void f1_helper(const Params& P) {
    const int hw = warp_in_group();
    if ((threadIdx.x & 31) == 0) {
        const bool chain = blockIdx.x >= NENG + 16;
        if (hw == 0) {
            const uint32_t ep = this_launch();
#pragma unroll 1
            for (int b = 0; b < NSTEP; b++) {
                flag_wait(F_XF, b, n_pairs(b) * ep);
                TG(b, 29);
                const uint8_t* src = g_xf + (b & (RING - 1)) * (9 * 8192);
#pragma unroll 1
                for (int blk = 0; blk < 9; blk++) {
                    mbar_wait(bars + (FB_EMPTY + blk) * 8, (b & 1) ^ 1);
                    mbar_expect(bars + (FB_FULL + blk) * 8, 8192);
                    bulk_g2s(sb + F_X + blk * 8192, src + blk * 8192, 8192, bars + (FB_FULL + blk) * 8);
                }
            }
        } else if (hw == 1) {
            const uint32_t ep = this_launch();
            int b1 = chain ? LAG : 0, b2 = b1;
            const int bend = b1 + NSEG;
            bool second = true;
#pragma unroll 1
            for (int j = blockIdx.x < NENG + 32 ? 0 : 2 * NSEG; j < 2 * NSEG; j++) {
                [[maybe_unused]] int n = 0;
                const bool may1 = b1 < bend && b1 < b2 + R_BACKLOG;
                bool may2 = !chain || !second || !may1, any;
                do {
                    const bool r1 = flag_up(F_P1, b1, 15 * ep) & may1, r2 = flag_up(F_P2, b2, 17 * ep) & may2;
                    second = chain ? !r1 : r2;
                    any = r1 | r2;
                    may2 = !chain || !may1;
                    SPIN_CHECK(n, 20);
                } while (!any);
                fence_acq_gpu();
                TG(second ? b2 : b1, 25 + 2 * second);
                sts32(sb + F_RED + 192 + (j & 1) * 4, second ? b2 + 256 : b1);
                mbar_arrive(bars + FB_JOB * 8);
                if (second) b2++; else b1++;
                mbar_wait(bars + FB_JOB * 8, j & 1);
            }
        } else if (hw == 2) {
#pragma unroll 1
            for (int j = blockIdx.x < NENG + 32 ? 0 : 2 * NSEG; j < 2 * NSEG; j++) {
                if (j == 0) mbar_arrive(bars + FB_JOB * 8);
                mbar_wait(bars + FB_RDONE * 8, j & 1);
                const int job = lds32(sb + F_RED + 192 + (j & 1) * 4);
                mbar_arrive(bars + FB_JOB * 8);
                TG(job & 255, 23 + (job >> 8));
                if (job < 256 || !chain) publish(job < 256 ? F_XF : F_X1, job & 255);
                TG(job & 255, 26 + 2 * (job >> 8));
            }
        } else {
            hold_back(PF_DELAY);
#pragma unroll 1
            for (int j = 0; j < 24; j++) {
                const bf16* w = j >= 16 ? P.w2 : (j & 1) ? P.w3 : P.w1;
                asm volatile("cp.async.bulk.prefetch.L2.global [%0], %1;" :: "l"(w + (size_t)((j >= 16 ? j - 16 : j >> 1) * NF1 + blockIdx.x - NENG) * (2 * FF)), "r"(4 * FF) : "memory");
                hold_back(PF_PACE);
            }
            publisher(bars + FB_H2 * 8, bars + FB_RACK * 8, F_H2);
        }
    }
    __syncwarp();
}

__device__ __forceinline__ void add8(float* f, uint4 a) {
    f[0] += bf_lo(a.x); f[1] += bf_hi(a.x); f[2] += bf_lo(a.y); f[3] += bf_hi(a.y);
    f[4] += bf_lo(a.z); f[5] += bf_hi(a.z); f[6] += bf_lo(a.w); f[7] += bf_hi(a.w);
}
__device__ __forceinline__ void set8(float* f, uint4 a) {
    f[0] = bf_lo(a.x); f[1] = bf_hi(a.x); f[2] = bf_lo(a.y); f[3] = bf_hi(a.y);
    f[4] = bf_lo(a.z); f[5] = bf_hi(a.z); f[6] = bf_lo(a.w); f[7] = bf_hi(a.w);
}
__device__ __forceinline__ void ln0_rows(const Params& P, int r) {
    const int lane = threadIdx.x & 31, l = lane < 24 ? lane : 0;
    const uint4* xrow = (const uint4*)(P.x + r * DM) + l;
    uint4 xw[3];
#pragma unroll
    for (int k = 0; k < 3; k++) xw[k] = __ldg(xrow + 24 * k);
    asm volatile("prefetch.global.L2 [%0];" :: "l"(P.x + (r + 16) * DM + (lane < 9 ? lane : 0) * 64));
#pragma unroll 1
    for (int seg = 0; seg < NSEG; seg++) {
#pragma unroll 1
        for (int h = 0; h < 2; h++) {
            float f[24];
#pragma unroll
            for (int k = 0; k < 3; k++) set8(&f[k * 8], xw[k]);
            if (2 * seg + h + 1 < 2 * NSEG) {
#pragma unroll
                for (int k = 0; k < 3; k++) xw[k] = __ldg(xrow + (2 * seg + h + 1) * (16 * DM / 8) + 24 * k);
            }
            float s = 0.f, q = 0.f;
#pragma unroll
            for (int j = 0; j < 24; j++) s += f[j];
            if (lane >= 24) s = 0.f;
#pragma unroll
            for (int o = 16; o; o >>= 1) s += __shfl_xor_sync(~0u, s, o);
            const float mean = s * (1.f / DM);
#pragma unroll
            for (int j = 0; j < 24; j++) { f[j] -= mean; q += f[j] * f[j]; }
            if (lane >= 24) q = 0.f;
#pragma unroll
            for (int o = 16; o; o >>= 1) q += __shfl_xor_sync(~0u, q, o);
            const float rstd = rsqrtf(q * (1.f / DM) + 1e-5f);
            if (lane < 24) {
                uint8_t* d = g_x + seg * XIMG + (l >> 3) * 8192 + (r + 16 * h) * 128 + (((l & 7) ^ (r & 7)) << 4);
#pragma unroll
                for (int k = 0; k < 3; k++) {
                    const float* y = &f[8 * k];
                    stg128(d + k * 24576, make_uint4(pack2(y[0] * rstd, y[1] * rstd), pack2(y[2] * rstd, y[3] * rstd), pack2(y[4] * rstd, y[5] * rstd), pack2(y[6] * rstd, y[7] * rstd)));
                }
            }
        }
        __syncwarp();
        if (lane == 0 && seg == 0) TG(79, 4);
        if (lane == 0) publish(F_X0, seg);
        if (lane == 0 && seg == 0) TG(79, 5);
        __syncwarp();
    }
}

template <bool SECOND, bool CHAIN>
__device__ __forceinline__ void reduce_job(const Params& P, int b, int p, int t) {
    constexpr int NP = SECOND ? NP2 : NP1;
    const int seg = CHAIN ? b - LAG : b, lane = t & 31;
    const bool act = !(t & 1);
    const uint32_t ro = (b & (RING - 1)), po = p * (DM * 4) + t * 16, so = 2048 - t * 16 + (t >> 1) * 4;
    const int fa = (t >> 2) * 16 + (t & 3) * 2, fs = 512 + (t >> 5) * 16 + ((t >> 2) & 7) + (t & 2) * 4;
    const uint32_t row = (seg * 32 + (p & 15) * 2) * DM;
    uint8_t* const r1 = g_r1 + ro * PART + po;
    uint8_t* const r2 = g_r2 + seg * (PART / 2) + po - (CHAIN ? PART / 2 : 0);
    float f[10];
    uint4 x;
    uint32_t y;
    {
        const uint8_t* src = (SECOND ? g_p2 : g_p1) + ro * (NP * PART) + po;
        uint4 a[NP];
        uint32_t c[NP];
#pragma unroll
        for (int k = 0; k < NP; k++) { a[k] = ld_rlx128(src + k * PART); c[k] = ld_rlx(src + so + k * PART); }
        if (SECOND || CHAIN) {
            x = ld_rlx128(SECOND ? r1 : r2); y = ld_rlx((SECOND ? r1 : r2) + so);
        } else {
            const bf16* xr = P.x + row;
            const uint32_t a0 = ld_rlx(xr + fa), b0 = ld_rlx(xr + fa + 8), a1 = ld_rlx(xr + fa + DM), b1 = ld_rlx(xr + fa + DM + 8);
            const uint32_t s0 = ld_rlx(xr + (fs & ~1)), s1 = ld_rlx(xr + (fs & ~1) + DM);
            x = make_uint4(__byte_perm(a0, a1, 0x5410), __byte_perm(b0, b1, 0x5410), __byte_perm(a0, a1, 0x7632), __byte_perm(b0, b1, 0x7632));
            y = __byte_perm(s0, s1, (fs & 1) ? 0x7632 : 0x5410);
        }
        set8(f, a[0]); f[8] = bf_lo(c[0]); f[9] = bf_hi(c[0]);
#pragma unroll
        for (int k = 1; k < NP; k++) { add8(f, a[k]); f[8] += bf_lo(c[k]); f[9] += bf_hi(c[k]); }
    }
    add8(f, x);
    x = make_uint4(pack2(f[0], f[1]), pack2(f[2], f[3]), pack2(f[4], f[5]), pack2(f[6], f[7]));
    y = pack2(f[8] + bf_lo(y), f[9] + bf_hi(y));
    if (SECOND && CHAIN) {
        bf16* o = P.out + row;
        stg32(o + fa, __byte_perm(x.x, x.z, 0x5410));
        stg32(o + fa + 8, __byte_perm(x.y, x.w, 0x5410));
        stg32(o + fa + DM, __byte_perm(x.x, x.z, 0x7632));
        stg32(o + fa + DM + 8, __byte_perm(x.y, x.w, 0x7632));
        stg16(o + fs + (act ? 0 : DM), act ? y : y >> 16);
        return;
    }
    set8(f, x);
    f[8] = act ? bf_lo(y) : 0.f; f[9] = act ? 0.f : bf_hi(y);
    float st[4];
    st[0] = (f[0] + f[2]) + (f[4] + f[6]) + f[8]; st[2] = (f[0] * f[0] + f[2] * f[2]) + (f[4] * f[4] + f[6] * f[6]) + f[8] * f[8];
    st[1] = (f[1] + f[3]) + (f[5] + f[7]) + f[9]; st[3] = (f[1] * f[1] + f[3] * f[3]) + (f[5] * f[5] + f[7] * f[7]) + f[9] * f[9];
    {
        const bool u = lane & 1, v = lane & 2;
        st[0] = (u ? st[1] : st[0]) + __shfl_xor_sync(~0u, u ? st[0] : st[1], 1);
        st[2] = (u ? st[3] : st[2]) + __shfl_xor_sync(~0u, u ? st[2] : st[3], 1);
        st[0] = (v ? st[2] : st[0]) + __shfl_xor_sync(~0u, v ? st[0] : st[2], 2);
        st[0] = (st[0] + __shfl_xor_sync(~0u, st[0], 4)) + (__shfl_xor_sync(~0u, st[0], 8) + __shfl_xor_sync(~0u, st[0], 12));
        if (!(lane & 12)) sts32(sb + F_RED + (t >> 4) * 16 + (lane & 3) * 4, fu(st[0]));
    }
    nbar_sync(NB_R, 128);
#pragma unroll
    for (int k = 0; k < 8; k++) {
        const uint4 q = lds128(sb + F_RED + k * 16);
        if (k == 0) { st[0] = uf(q.x); st[1] = uf(q.y); st[2] = uf(q.z); st[3] = uf(q.w); }
        else { st[0] += uf(q.x); st[1] += uf(q.y); st[2] += uf(q.z); st[3] += uf(q.w); }
    }
    stg128(SECOND ? r2 : r1, x);
    if (act) stg32((SECOND ? r2 : r1) + so, y);
    const float m0 = st[0] * (1.f / DM), m1 = st[1] * (1.f / DM);
    const float q0 = rsqrtf(fmaxf(st[2] * (1.f / DM) - m0 * m0, 0.f) + 1e-5f), q1 = rsqrtf(fmaxf(st[3] * (1.f / DM) - m1 * m1, 0.f) + 1e-5f);
    constexpr int KB = 8192;
    uint8_t* d = (SECOND ? g_x + (b + LAG) * XIMG + (USE_ONE && b + LAG >= NSEG ? 0 : 4096) : g_xf + ro * XIMG) + p * 256;
#pragma unroll
    for (int e = 0; e < 2; e++) {
        const float m = e ? m1 : m0, q = e ? q1 : q0;
#pragma unroll
        for (int h = 0; h < 2; h++)
            stg32(d + (fa >> 6) * KB + (t & 3) * 4 + e * 128 + (((((fa >> 3) & 6) + h) ^ ((2 * p + e) & 7)) << 4), pack2((f[2 * h + e] - m) * q, (f[4 + 2 * h + e] - m) * q));
    }
    stg16(d + 8 * KB + (t & 1) * 128 + ((((fs >> 3) & 7) ^ ((2 * p + (t & 1)) & 7)) << 4) + (fs & 7) * 2, pack2(act ? (f[8] - m0) * q0 : (f[9] - m1) * q1, 0.f));
}
template <bool CHAIN>
__device__ __forceinline__ void reducer(const Params& P) {
#pragma unroll 1
    for (int j = 0; j < 2 * NSEG; j++) {
        const int t = fresh_tid() - 256, p = fresh_bid() - NENG;
        mbar_wait(bars + FB_JOB * 8, j & 1);
        const int job = lds32(sb + F_RED + 192 + (j & 1) * 4);
        if (job >= 256) reduce_job<true, CHAIN>(P, job - 256, p, t);
        else reduce_job<false, CHAIN>(P, job, p, t);
        mbar_arrive_warp(bars + FB_RDONE * 8);
    }
}

__host__ __device__ constexpr int d_rf(int u) { return u < 48 ? ((u & 3) < 2 ? (u >> 2) * 2 + (u & 1) : -1) : u == 48 ? 24 : -1; }
__host__ __device__ constexpr int d_ss(int u) { return u < 48 ? (u >> 2) * 2 + (u & 1) : u - 25; }
template <bool WIDE, int wg>
__device__ __forceinline__ void d_main() {
    constexpr int NR = WIDE ? 24 : NRD;
    uint32_t w[NR][4];
    {
        const uint32_t fa = sb + wg * (NRD * 2048) + unit_frag_addr(threadIdx.x);
        mbar_wait(bars + DB_WL * 8, 0);
#pragma unroll
        for (int u = 0; u < NR; u++) ldsm4t(w[u], fa + u * 2048);
        nbar_arrive(NB_W, 416);
        mbar_wait(bars + DB_WL * 8, 1);
        if (threadIdx.x == 0) TG(79, 2);
    }
    const uint64_t da = mkdesc(wg * ((52 - NRD) * 2048), 1024, 1024, 1);
#pragma unroll 1
    for (int b = 0; b < NSTEP; b++) {
#pragma unroll
        for (int T = 0; T < (WIDE ? 3 : 1); T++) {
            float d[32];
            constexpr int NB = WIDE ? 4 : 13;
#pragma unroll
            for (int blk = 0; blk < NB; blk++) {
                const int c = blk;
                if (T == 0 || blk == 0) mbar_wait(bars + (DB_FULL + (c & 7)) * 8, WIDE || (c & 7) >= 5 ? b & 1 : c >> 3);
                if (T == 0 || blk == 0) wg_fence();
                const uint64_t db = mkdesc(D_B + (c & 7) * 8192, 8192, 1024, 1);
#pragma unroll
                for (int j = 0; j < 4; j++) {
                    const int u = T * 16 + blk * 4 + j;
                    if (d_rf(u) >= 0) wg_rs64<1>(d, w[d_rf(u) >= 0 ? d_rf(u) : 0], db + j * 128, blk + j > 0);
                    else wg_ss64<1>(d, da + d_ss(u) * 128, db + j * 128, blk + j > 0);
                }
                wg_commit();
                if (!WIDE && blk > 0) { wg_wait<1>(); mbar_arrive_warp(bars + (DB_EMPTY + ((c - 1) & 7)) * 8); }
            }
            const int tid = fresh_tid(), t = tid & 3, ds = fresh_bid() - NENG - NF1;
            const bool w2 = ds >= 15;
            const int tile = WIDE ? wg * 3 + T : (ds % 3) * 3 + wg;
            uint8_t* dst = (w2 ? g_p2 + ((b & (RING - 1)) * NP2 + (WIDE ? ds - 25 : (ds - 15) / 3)) * PART : g_p1 + ((b & (RING - 1)) * NP1 + ds / 3) * PART)
                         + (tile * 64 + ((tid >> 5) & 3) * 16 + ((tid & 31) >> 2) * 2) * 4 + (w2 ? 4 * t : t) * (DM * 4);
            const uint32_t js = w2 ? DM * 4 : DM * 16;
            if (T == 0) mbar_wait(bars + (DB_P + 1) * 8, (b & 1) ^ 1);
            wg_wait_acc<0, 32>(d);
            if (!WIDE) mbar_arrive_warp(bars + (DB_EMPTY + ((NB - 1) & 7)) * 8);
            else if (T == 2) {
#pragma unroll
                for (int blk = 0; blk < 4; blk++) mbar_arrive_warp(bars + (DB_EMPTY + blk) * 8);
            }
#pragma unroll
            for (int j = 0; j < 8; j++) stg64(dst + (j >> 2) * (DM * 64) + (j & 3) * js, pack2(d[4 * j], d[4 * j + 1]), pack2(d[4 * j + 2], d[4 * j + 3]));
        }
        mbar_arrive_warp(bars + DB_P * 8);
    }
}
__device__ __forceinline__ void d_helper(const Params& P, int ds) {
    const int lane = threadIdx.x & 31, hw = warp_in_group();
    const bool w2 = ds >= 15, wide = ds >= 30;
    const int kr = (w2 ? ds - 15 : ds) / 3, nb = wide ? 4 : 13;
    const int blk0 = wide ? 29 + (ds - 30) * 4 : kr * (w2 ? 6 : 13), n1 = w2 ? (kr == 4 ? 5 : 6) : 13, blk1 = 37 + kr * 7 - n1;
    if (hw == 0) {
        const int nu = wide ? 48 : 52;
        hold_back(w2 ? W2_DELAY : D_DELAY);
#pragma unroll 1
        for (int ph = 0; ph < 2; ph++) {
            if (ph) nbar_sync(NB_W, 416);
            if (lane == 0) mbar_expect(bars + DB_WL * 8, (wide ? 72 : ph ? 3 * (52 - NRD) : 3 * NRD) * 2048);
            __syncwarp();
#pragma unroll 1
            for (int x = lane; x < 3 * nu; x += 32) {
                const int wg = x / nu, u = x - wg * nu, j = (wide ? u & 15 : u) >> 2;
                const int kb = !w2 ? blk0 + j : j < n1 ? (blk0 + j) * 2 : (blk1 + j - 37) * 2 + 1;
                if ((d_rf(u) < 0) == (ph != 0))
                    tma_unit(sb + (ph ? wg * (52 - NRD) + d_ss(u) : wg * NRD + d_rf(u)) * 2048, w2 ? &P.tmW2 : &P.tmWo,
                             kb * 4 + (u & 3), wide ? wg * 3 + (u >> 4) : (ds % 3) * 3 + wg, bars + DB_WL * 8);
            }
        }
        __syncwarp();
        if (lane == 0) {
            const uint32_t target = (w2 ? NF1 : NENG) * this_launch();
#pragma unroll 1
            for (int b = 0; b < NSTEP; b++) {
                flag_wait(w2 ? F_H : F_O, b, target);
                TG(b, 29);
                const uint8_t* src = (w2 ? g_h + (b & (RING - 1)) * H_BYTES : g_o + (b & (RING - 1)) * O_BYTES);
#pragma unroll 1
                for (int blk = 0; blk < nb; blk++) {
                    const int c = blk;
                    if (blk == n1) flag_wait(F_H2, b, target);
                    mbar_wait(bars + (DB_EMPTY + (c & 7)) * 8, (wide || (c & 7) >= 5 ? b & 1 : c >> 3) ^ 1);
                    mbar_expect(bars + (DB_FULL + (c & 7)) * 8, 8192);
                    bulk_g2s(sb + D_B + (c & 7) * 8192, src + (blk + (blk < n1 ? blk0 : blk1)) * 8192, 8192, bars + (DB_FULL + (c & 7)) * 8);
                }
            }
        }
    } else if (hw == 1 && lane == 0) {
        publisher(bars + DB_P * 8, bars + (DB_P + 1) * 8, w2 ? F_P2 : F_P1);
    }
    __syncwarp();
}

__device__ __forceinline__ void sign_off() { mbar_arrive_warp(sb + SM_DONE); }
__device__ __forceinline__ void sign_off_helper() {
    if (warp_in_group() < 3) { sign_off(); return; }
    uint32_t ok;
    const uint32_t t0 = timer_lo(), ep = this_launch();
    do {
        __nanosleep(100);
        asm volatile("{.reg .pred p; mbarrier.test_wait.parity.shared::cta.b64 p, [%1], 0; selp.u32 %0, 1, 0, p;}" : "=r"(ok) : "r"(sb + SM_DONE) : "memory");
    } while (!ok && timer_lo() - t0 < TIME_LIMIT);
    if (!ok || (sb & 0x3ffff) != SM_ORG) __trap();
    if (fresh_tid() == NTHREADS - 32) { g_epoch[fresh_bid()][0] = ep; TG(79, 1); }
    __syncwarp();
}

__global__ void __cluster_dims__(2, 1, 1) __launch_bounds__(NTHREADS, 1) fused_kernel(const __grid_constant__ Params P) {
    const int wg = __shfl_sync(~0u, threadIdx.x >> 7, 0);
    const int bid = blockIdx.x;
    if (threadIdx.x >= NTHREADS - 32) sts32(sb + SM_ONES + (threadIdx.x & 31) * 4, 0x3f803f80u);
    if (threadIdx.x == 0) {
        TG(79, 0);
        mbar_init(sb + SM_DONE, 15);
        sts32(sb + SM_XRDY, 0);
        if (bid < NENG) {
            for (int i = 0; i < 9; i++) mbar_init(bars + (EB_FULL + i) * 8, i < 6 ? 1 : 12);
            mbar_init(bars + EB_V0 * 8, 4); mbar_init(bars + EB_WL * 8, 3); mbar_init(bars + EB_WO * 8, 2); mbar_init(bars + EB_STEP * 8, 8);
            mbar_init(bars + EB_SM * 8, 1); mbar_init(bars + EB_SX * 8, 1); mbar_init(bars + EB_OX * 8, 1);
            mbar_init(bars + EB_QF * 8, 4); mbar_init(bars + EB_KF * 8, 8); mbar_init(bars + EB_CONS * 8, 4); mbar_init(bars + EB_OST * 8, 4);
            mbar_init(bars + EB_OFREE * 8, 1); mbar_init(bars + EB_MEM * 8, 5); mbar_init(bars + EB_PRDY * 8, 1);
        } else if (bid < NENG + NF1) {
            for (int i = 0; i < 9; i++) { mbar_init(bars + (FB_FULL + i) * 8, 1); mbar_init(bars + (FB_EMPTY + i) * 8, 8); }
            mbar_init(bars + FB_H * 8, 8); mbar_init(bars + FB_H2 * 8, 8); mbar_init(bars + FB_RACK * 8, 1); mbar_init(bars + FB_JOB * 8, 2); mbar_init(bars + FB_RDONE * 8, 4);
        } else {
            for (int i = 0; i < 8; i++) { mbar_init(bars + (DB_FULL + i) * 8, 1); mbar_init(bars + (DB_EMPTY + i) * 8, 12); }
            mbar_init(bars + DB_WL * 8, 1); mbar_init(bars + DB_P * 8, 12); mbar_init(bars + (DB_P + 1) * 8, 1);
        }
        asm volatile("fence.mbarrier_init.release.cluster;" ::: "memory");
    }
    __syncthreads();
    asm volatile("barrier.cluster.arrive.relaxed.aligned; barrier.cluster.wait.aligned;" ::: "memory");
    if (bid < NENG) {
        if (wg == 0) { reg_inc<REGQ>(); engine_main<0>(P); sign_off(); cluster_sync_all(); }
        else if (wg == 1) { reg_inc<REGK>(); engine_main<1>(P); sign_off(); cluster_sync_all(); }
        else if (wg == 2) { reg_inc<REGV>(); engine_main<2>(P); sign_off(); cluster_sync_all(); }
        else { reg_dec<24>(); engine_helper(P); sign_off_helper(); cluster_sync_all(); }
    } else if (bid < NENG + NF1) {
        if (wg < 2) {
            reg_inc<REGF>();
            if (wg == 0) f1_main<0>(P); else f1_main<1>(P);
            sign_off();
        } else if (wg == 2) {
            reg_dec<488 - 2 * REGF>();
            if (bid >= NENG + 32) ln0_rows(P, (bid - NENG - 32) * 4 + warp_in_group());
            else if (bid < NENG + 16) reducer<false>(P);
            else reducer<true>(P);
            sign_off();
        } else {
            reg_dec<24>();
            f1_helper(P);
            sign_off_helper();
        }
    } else {
        const int ds = bid - NENG - NF1;
        if (wg < 3) {
            reg_inc<160>();
            if (ds < 30) { if (wg == 0) d_main<false, 0>(); else if (wg == 1) d_main<false, 1>(); else d_main<false, 2>(); }
            else { if (wg == 0) d_main<true, 0>(); else if (wg == 1) d_main<true, 1>(); else d_main<true, 2>(); }
            sign_off();
        } else {
            reg_dec<32>();
            d_helper(P, ds);
            sign_off_helper();
        }
    }
}

typedef CUresult (*EncodeFn)(CUtensorMap*, CUtensorMapDataType, cuuint32_t, void*, const cuuint64_t*, const cuuint64_t*,
                             const cuuint32_t*, const cuuint32_t*, CUtensorMapInterleave, CUtensorMapSwizzle,
                             CUtensorMapL2promotion, CUtensorMapFloatOOBfill);

void make_map(EncodeFn enc, CUtensorMap* m, const void* p, int rows, int cols) {
    cuuint64_t dims[2] = {(cuuint64_t)cols, (cuuint64_t)rows};
    cuuint64_t strides[1] = {(cuuint64_t)cols * 2};
    cuuint32_t box[2] = {64, 16};
    cuuint32_t es[2] = {1, 1};
    enc(m, CU_TENSOR_MAP_DATA_TYPE_BFLOAT16, 2, (void*)p, dims, strides, box, es, CU_TENSOR_MAP_INTERLEAVE_NONE,
        CU_TENSOR_MAP_SWIZZLE_128B, CU_TENSOR_MAP_L2_PROMOTION_L2_128B, CU_TENSOR_MAP_FLOAT_OOB_FILL_NONE);
}

}

extern "C" void kernel_launch(void* const* d_in, const int* in_sizes, int n_in, void* d_out, int out_size) {
    (void)in_sizes; (void)n_in; (void)out_size;
    static EncodeFn enc = nullptr;
    if (!enc) {
        void* fn = nullptr;
        cudaDriverEntryPointQueryResult qr;
        cudaGetDriverEntryPoint("cuTensorMapEncodeTiled", &fn, cudaEnableDefault, &qr);
        enc = (EncodeFn)fn;
        cudaFuncSetAttribute(fused_kernel, cudaFuncAttributeMaxDynamicSharedMemorySize, SM_TOTAL);
    }
    Params P;
    make_map(enc, &P.tmWq, d_in[2], DM, 4096);
    make_map(enc, &P.tmWk, d_in[3], DM, 4096);
    make_map(enc, &P.tmWv, d_in[4], DM, 4096);
    make_map(enc, &P.tmWo, d_in[5], 4096, DM);
    make_map(enc, &P.tmW2, d_in[10], FF, DM);
    P.x = (const bf16*)d_in[0];
    P.mem0 = (const bf16*)d_in[1];
    P.w1 = (const bf16*)d_in[8];
    P.w3 = (const bf16*)d_in[9];
    P.w2 = (const bf16*)d_in[10];
    P.out = (bf16*)d_out;
    P.zero = 0;
    fused_kernel<<<NCTA, NTHREADS, SM_TOTAL>>>(P);
}
```

```cpp
#include <cuda_runtime.h>
#include <cuda_bf16.h>
#include <cuda.h>
#include <stdint.h>

typedef __nv_bfloat16 bf16;

namespace {

constexpr int DM = 576, FF = 4608, NSEG = 64;
constexpr int NENG = 64, NF1 = 36, ND = 32, NCTA = NENG + NF1 + ND;
constexpr int NTHREADS = 512;
#define LAG 8
#define RING 16
static_assert(RING > LAG, "ring too short");
#define USE_ONE 1
constexpr int NSTEP = NSEG + LAG;

enum { F_X0 = 0, F_X1, F_O, F_P1, F_XF, F_H, F_P2, F_H2, F_COUNT };
constexpr int B_ZERO = 95;
__device__ uint32_t g_flag[F_COUNT][96][8];
__device__ uint32_t g_epoch[NCTA][8];
constexpr int XIMG = 9 * 8192;
constexpr int O_BYTES = 65 * 8192;
constexpr int H_BYTES = 73 * 8192;
constexpr int PART = 32 * DM * 4;
constexpr int NP1 = 5, NP2 = 7;
__device__ __align__(1024) uint8_t g_x[NSTEP * XIMG];
__device__ __align__(1024) uint8_t g_xf[RING * XIMG];
__device__ __align__(1024) uint8_t g_o[RING * O_BYTES];
__device__ __align__(1024) uint8_t g_h[RING * H_BYTES];
__device__ __align__(1024) uint8_t g_p1[RING * NP1 * PART];
__device__ __align__(1024) uint8_t g_p2[RING * NP2 * PART];
__device__ __align__(1024) uint8_t g_r1[RING * PART];
__device__ __align__(1024) uint8_t g_r2[NSEG * PART / 2];
#define AR_STR 4352
constexpr int AR_SLOT = 144 * AR_STR;
__device__ __align__(1024) uint8_t g_ar[4 * AR_SLOT];

struct Params {
    CUtensorMap tmWq, tmWk, tmWv, tmWo, tmW2;
    const bf16 *x, *mem0, *w1, *w3, *w2;
    bf16* out;
    uint32_t zero;
};

constexpr uint32_t SM_ORG = 1024;
extern __shared__ __align__(1024) uint8_t smem_raw[];
#define sb ((uint32_t)__cvta_generic_to_shared(smem_raw))
#define bars (sb + SM_BAR)
constexpr int SM_BAR = 231936;
constexpr int SM_TOTAL = SM_BAR + 512;
#define NRQ 25
#define NRK 25
#define NRV 25
#define REGQ 160
#define REGK 168
#define REGV 160
constexpr int E_WQ = 0;
constexpr int E_WK = E_WQ + (36 - NRQ) * 2048;
constexpr int E_WV = E_WK + (36 - NRK) * 2048;
constexpr int E_WO = E_WV + (36 - NRV) * 2048;
constexpr int E_MEM = E_WO + 36 * 2048;
constexpr int E_R0 = E_MEM + 18432;
constexpr int E_R2 = E_R0 + 8192, E_R3 = E_R2 + 8192, E_R1 = E_R3 + 8192;
constexpr int E_SX = E_R1;
constexpr int E_QT = E_R1 + 8192;
constexpr int E_KT = E_QT + 8192;
constexpr int E_VT = E_KT + 10240;
constexpr int E_OM = E_VT + 10240;
constexpr int E_QM = E_OM + 4096;
constexpr int E_SR = E_QM + 2048;
constexpr int E_SL = E_SR + 2560;
constexpr int E_END = E_SL + 2048;
static_assert(E_END <= SM_BAR, "engine smem overflow");
static_assert(E_WO + (NRQ + NRK + NRV) * 2048 <= E_OM, "weight staging: the peer writes there without asking");
enum {
    EB_FULL = 0  , EB_EMPTY = 6  , EB_V0 = 9, EB_WL, EB_WO, EB_STEP, EB_SM, EB_SX, EB_OX,
    EB_QF, EB_KF, EB_CONS, EB_OST, EB_OFREE, EB_MEMA, EB_MEM, EB_PRDY
};
enum { NB_G = 1, NB_LEAD, NB_QK, NB_S, NB_OM, NB_W, NB_R, NB_T, NB_PV, NB_WO, NB_V, NB_KT, NB_S2, NB_VL };
constexpr int NB_VL2 = NB_LEAD;
#define REGF 208
constexpr int NRF = REGF == 200 ? 35 : 36;
constexpr int F_W = 0;
constexpr int F_X = 2 * (72 - NRF) * 2048;
constexpr int F_RED = F_X + 9 * 8192;
static_assert(F_RED + 512 <= SM_BAR, "F1 smem overflow");
enum { FB_FULL = 0, FB_EMPTY = 9, FB_H = 18, FB_H2, FB_RACK, FB_JOB, FB_RDONE };
constexpr int NRD = 25;
constexpr int D_B = 3 * (52 - NRD) * 2048;
static_assert(D_B + 8 * 8192 <= SM_BAR, "D smem overflow");
enum { DB_FULL = 0, DB_EMPTY = 8, DB_WL = 16, DB_P };
constexpr int SM_DONE = SM_BAR + 248, SM_XRDY = SM_BAR + 376, SM_ONES = SM_BAR + 384;
constexpr uint32_t TIME_LIMIT = 2000000000u;

#define SPIN_CHECK(n, code)

#define TS(thr, step, k)
#define TX(thr, k)
#define TG(step, k)
#define PROF_INC(n, k)

__device__ __forceinline__ uint32_t mapa(uint32_t a, uint32_t r) {
    uint32_t o; asm("mapa.shared::cluster.u32 %0, %1, %2;" : "=r"(o) : "r"(a), "r"(r)); return o;
}
__device__ __forceinline__ void mbar_init(uint32_t b, uint32_t cnt) {
    asm volatile("mbarrier.init.shared::cta.b64 [%0], %1;" :: "r"(b), "r"(cnt) : "memory");
}
__device__ __forceinline__ void mbar_arrive(uint32_t b) {
    asm volatile("mbarrier.arrive.shared::cta.b64 _, [%0];" :: "r"(b) : "memory");
}
__device__ __forceinline__ void mbar_arrive_warp(uint32_t b) {
    asm volatile("{.reg .pred p; bar.warp.sync -1; elect.sync _|p, -1; @p mbarrier.arrive.shared::cta.b64 _, [%0];}" :: "r"(b) : "memory");
}
__device__ __forceinline__ void mbar_arrive_remote(uint32_t b) {
    asm volatile("fence.release.sync_restrict::shared::cta.cluster; mbarrier.arrive.relaxed.cluster.shared::cluster.b64 _, [%0];" :: "r"(b) : "memory");
}
__device__ __forceinline__ void mbar_expect(uint32_t b, uint32_t bytes) {
    asm volatile("mbarrier.arrive.expect_tx.shared::cta.b64 _, [%0], %1;" :: "r"(b), "r"(bytes) : "memory");
}
__device__ __forceinline__ uint32_t mbar_wait(uint32_t b, uint32_t par) {
    uint32_t ok; [[maybe_unused]] int n = 0;
    while (true) {
        asm volatile("{.reg .pred p; mbarrier.try_wait.parity.shared::cta.b64 p, [%1], %2; selp.u32 %0, 1, 0, p;}"
                     : "=r"(ok) : "r"(b), "r"(par) : "memory");
        if (ok) break;
        SPIN_CHECK(n, 1000 + ((b & 511) >> 3));
    }
    return ok;
}
__device__ __forceinline__ bool mbar_test(uint32_t b, uint32_t par) {
    uint32_t ok;
    asm volatile("{.reg .pred p; mbarrier.test_wait.parity.shared::cta.b64 p, [%1], %2; selp.u32 %0, 1, 0, p;}" : "=r"(ok) : "r"(b), "r"(par) : "memory");
    return ok;
}
__device__ __forceinline__ void mbar_wait_cl(uint32_t b, uint32_t par) {
    uint32_t ok; [[maybe_unused]] int n = 0;
    while (true) {
        asm volatile("{.reg .pred p; mbarrier.try_wait.parity.relaxed.cluster.shared::cta.b64 p, [%1], %2; selp.u32 %0, 1, 0, p;}"
                     : "=r"(ok) : "r"(b), "r"(par) : "memory");
        if (ok) break;
        SPIN_CHECK(n, 1000 + ((b & 511) >> 3));
    }
    asm volatile("fence.acquire.sync_restrict::shared::cluster.cluster;" ::: "memory");
}
__device__ __forceinline__ void nbar_sync(int id, int n) { asm volatile("bar.sync %0, %1;" :: "r"(id), "r"(n) : "memory"); }
__device__ __forceinline__ void nbar_arrive(int id, int n) { asm volatile("bar.arrive %0, %1;" :: "r"(id), "r"(n) : "memory"); }
__device__ __forceinline__ void cluster_sync_all() {
    asm volatile("barrier.cluster.arrive.release.aligned; barrier.cluster.wait.acquire.aligned;" ::: "memory");
}
__device__ __forceinline__ void fence_async_smem() { asm volatile("fence.proxy.async.shared::cta;" ::: "memory"); }
__device__ __forceinline__ void fence_async_glb() { asm volatile("fence.proxy.async.global;" ::: "memory"); }
__device__ __forceinline__ void fence_rel_gpu() { asm volatile("fence.release.gpu;" ::: "memory"); }
__device__ __forceinline__ void fence_acq_gpu() { asm volatile("fence.acquire.gpu;" ::: "memory"); }
__device__ __forceinline__ void fence_gpu() { asm volatile("fence.acq_rel.gpu;" ::: "memory"); }
__device__ __forceinline__ int fresh_tid() { int t; asm volatile("mov.u32 %0, %%tid.x;" : "=r"(t)); return t; }
__device__ __forceinline__ int fresh_bid() { int t; asm volatile("mov.u32 %0, %%ctaid.x;" : "=r"(t)); return t; }
__device__ __forceinline__ uint32_t pin(uint32_t v) { asm volatile("" : "+r"(v)); return v; }
__device__ __forceinline__ int warp_in_group() { return __shfl_sync(~0u, (fresh_tid() >> 5) & 3, 0); }
__device__ __forceinline__ int cta_rank() { int t; asm volatile("mov.u32 %0, %%cluster_ctarank;" : "=r"(t)); return t; }
__device__ __forceinline__ uint32_t timer_lo() { uint32_t t; asm volatile("mov.u32 %0, %%globaltimer_lo;" : "=r"(t)); return t; }
__device__ __forceinline__ uint32_t keep(uint32_t v) { return __shfl_xor_sync(~0u, v, 0); }
__device__ __forceinline__ void red_add_u32(uint32_t* p, uint32_t v) {
    asm volatile("red.relaxed.gpu.global.add.u32 [%0], %1;" :: "l"(p), "r"(v) : "memory");
}
__device__ __forceinline__ uint32_t ld_rlx(const void* p) {
    uint32_t v; asm volatile("ld.relaxed.gpu.global.u32 %0, [%1];" : "=r"(v) : "l"(p) : "memory"); return v;
}
__device__ __forceinline__ uint2 ld_rlx64(const void* p) {
    uint2 v; asm volatile("ld.relaxed.gpu.global.v2.u32 {%0,%1}, [%2];" : "=r"(v.x), "=r"(v.y) : "l"(p) : "memory"); return v;
}
__device__ __forceinline__ uint4 ld_rlx128(const void* p) {
    uint4 v;
    asm volatile("ld.relaxed.gpu.global.v4.u32 {%0,%1,%2,%3}, [%4];" : "=r"(v.x), "=r"(v.y), "=r"(v.z), "=r"(v.w) : "l"(p) : "memory");
    return v;
}
__device__ __forceinline__ void stg128(void* p, uint4 v) {
    asm volatile("st.global.v4.b32 [%0], {%1,%2,%3,%4};" :: "l"(p), "r"(v.x), "r"(v.y), "r"(v.z), "r"(v.w) : "memory");
}
__device__ __forceinline__ void stg64(void* p, uint32_t a, uint32_t b) {
    asm volatile("st.global.v2.b32 [%0], {%1,%2};" :: "l"(p), "r"(a), "r"(b) : "memory");
}
__device__ __forceinline__ void stg16(void* p, uint32_t a) { asm volatile("st.global.b16 [%0], %1;" :: "l"(p), "h"((uint16_t)a) : "memory"); }
__device__ __forceinline__ void stg32(void* p, uint32_t a) { asm volatile("st.global.b32 [%0], %1;" :: "l"(p), "r"(a) : "memory"); }
__device__ __forceinline__ void st_async128(uint32_t a, uint32_t x, uint32_t y, uint32_t z, uint32_t w, uint32_t mb) {
    asm volatile("st.async.shared::cluster.mbarrier::complete_tx::bytes.v4.b32 [%0], {%1,%2,%3,%4}, [%5];"
                 :: "r"(a), "r"(x), "r"(y), "r"(z), "r"(w), "r"(mb) : "memory");
}
__device__ __forceinline__ void st_async64(uint32_t a, uint32_t x, uint32_t y, uint32_t mb) {
    asm volatile("st.async.shared::cluster.mbarrier::complete_tx::bytes.v2.b32 [%0], {%1,%2}, [%3];"
                 :: "r"(a), "r"(x), "r"(y), "r"(mb) : "memory");
}
__device__ __forceinline__ void sts128(uint32_t a, uint32_t x, uint32_t y, uint32_t z, uint32_t w) {
    asm volatile("st.shared.v4.b32 [%0], {%1,%2,%3,%4};" :: "r"(a), "r"(x), "r"(y), "r"(z), "r"(w) : "memory");
}
__device__ __forceinline__ void sts32(uint32_t a, uint32_t v) { asm volatile("st.shared.b32 [%0], %1;" :: "r"(a), "r"(v) : "memory"); }
__device__ __forceinline__ uint4 lds128(uint32_t a) {
    uint4 v; asm volatile("ld.shared.v4.b32 {%0,%1,%2,%3}, [%4];" : "=r"(v.x), "=r"(v.y), "=r"(v.z), "=r"(v.w) : "r"(a) : "memory"); return v;
}
__device__ __forceinline__ uint2 lds64(uint32_t a) {
    uint2 v; asm volatile("ld.shared.v2.b32 {%0,%1}, [%2];" : "=r"(v.x), "=r"(v.y) : "r"(a) : "memory"); return v;
}
__device__ __forceinline__ uint32_t lds32(uint32_t a) {
    uint32_t v; asm volatile("ld.shared.b32 %0, [%1];" : "=r"(v) : "r"(a) : "memory"); return v;
}
__device__ __forceinline__ void bulk_g2s(uint32_t dst, const void* src, uint32_t bytes, uint32_t mb) {
    asm volatile("cp.async.bulk.shared::cluster.global.mbarrier::complete_tx::bytes [%0], [%1], %2, [%3];"
                 :: "r"(dst), "l"(src), "r"(bytes), "r"(mb) : "memory");
}
__device__ __forceinline__ void bulk_s2g(void* dst, uint32_t src, uint32_t bytes) {
    asm volatile("cp.async.bulk.global.shared::cta.bulk_group [%0], [%1], %2;" :: "l"(dst), "r"(src), "r"(bytes) : "memory");
}
__device__ __forceinline__ void bulk_s2peer(uint32_t dst, uint32_t src, uint32_t bytes, uint32_t mb) {
    asm volatile("cp.async.bulk.shared::cluster.shared::cta.mbarrier::complete_tx::bytes [%0], [%1], %2, [%3];"
                 :: "r"(dst), "r"(src), "r"(bytes), "r"(mb) : "memory");
}
__device__ __forceinline__ void tma_unit(uint32_t dst, const CUtensorMap* tm, int kstep, int mgroup, uint32_t mb) {
    asm volatile("cp.async.bulk.tensor.2d.shared::cluster.global.mbarrier::complete_tx::bytes [%0], [%1, {%2,%3}], [%4];"
                 :: "r"(dst), "l"(tm), "r"(mgroup * 64), "r"(kstep * 16), "r"(mb) : "memory");
}
__device__ __forceinline__ void ldsm4(uint32_t* r, uint32_t a) {
    asm volatile("ldmatrix.sync.aligned.m8n8.x4.shared.b16 {%0,%1,%2,%3}, [%4];"
                 : "=r"(r[0]), "=r"(r[1]), "=r"(r[2]), "=r"(r[3]) : "r"(a) : "memory");
}
__device__ __forceinline__ void ldsm4t(uint32_t* r, uint32_t a) {
    asm volatile("ldmatrix.sync.aligned.m8n8.x4.trans.shared.b16 {%0,%1,%2,%3}, [%4];"
                 : "=r"(r[0]), "=r"(r[1]), "=r"(r[2]), "=r"(r[3]) : "r"(a) : "memory");
}
__device__ __forceinline__ void stsm4(uint32_t a, uint32_t r0, uint32_t r1, uint32_t r2, uint32_t r3) {
    asm volatile("stmatrix.sync.aligned.m8n8.x4.shared.b16 [%0], {%1,%2,%3,%4};" :: "r"(a), "r"(r0), "r"(r1), "r"(r2), "r"(r3) : "memory");
}
__device__ __forceinline__ void stsm4t(uint32_t a, uint32_t r0, uint32_t r1, uint32_t r2, uint32_t r3) {
    asm volatile("stmatrix.sync.aligned.m8n8.x4.trans.shared.b16 [%0], {%1,%2,%3,%4};" :: "r"(a), "r"(r0), "r"(r1), "r"(r2), "r"(r3) : "memory");
}
__device__ __forceinline__ uint32_t pack2(float lo, float hi) {
    uint32_t d; asm("cvt.rn.bf16x2.f32 %0, %1, %2;" : "=r"(d) : "f"(hi), "f"(lo)); return d;
}
__device__ __forceinline__ float bf_lo(uint32_t w) { return __uint_as_float(w << 16); }
__device__ __forceinline__ float bf_hi(uint32_t w) { return __uint_as_float(w & 0xffff0000u); }
__device__ __forceinline__ float ex2(float x) { float y; asm("ex2.approx.ftz.f32 %0, %1;" : "=f"(y) : "f"(x)); return y; }
__device__ __forceinline__ float rcp(float x) { float y; asm("rcp.approx.ftz.f32 %0, %1;" : "=f"(y) : "f"(x)); return y; }
__device__ __forceinline__ uint32_t fu(float x) { return __float_as_uint(x); }
__device__ __forceinline__ float uf(uint32_t x) { return __uint_as_float(x); }
__device__ __forceinline__ void mma16816(float* d, const uint32_t* a, uint32_t b0, uint32_t b1) {
    asm volatile("mma.sync.aligned.m16n8k16.row.col.f32.bf16.bf16.f32 {%0,%1,%2,%3}, {%4,%5,%6,%7}, {%8,%9}, {%0,%1,%2,%3};"
                 : "+f"(d[0]), "+f"(d[1]), "+f"(d[2]), "+f"(d[3]) : "r"(a[0]), "r"(a[1]), "r"(a[2]), "r"(a[3]), "r"(b0), "r"(b1));
}
__device__ __forceinline__ void mma1688(float* d, uint32_t a0, uint32_t a1, uint32_t b0) {
    asm volatile("mma.sync.aligned.m16n8k8.row.col.f32.bf16.bf16.f32 {%0,%1,%2,%3}, {%4,%5}, {%6}, {%0,%1,%2,%3};"
                 : "+f"(d[0]), "+f"(d[1]), "+f"(d[2]), "+f"(d[3]) : "r"(a0), "r"(a1), "r"(b0));
}
template <int N> __device__ __forceinline__ void reg_inc() { asm volatile("setmaxnreg.inc.sync.aligned.u32 %0;" :: "n"(N)); }
template <int N> __device__ __forceinline__ void reg_dec() { asm volatile("setmaxnreg.dec.sync.aligned.u32 %0;" :: "n"(N)); }

__device__ __forceinline__ uint64_t mkdesc(uint32_t addr, uint32_t lbo, uint32_t sbo, uint32_t swz) {
    return (uint64_t)((addr + SM_ORG) >> 4) | ((uint64_t)(lbo >> 4) << 16) | ((uint64_t)(sbo >> 4) << 32) | ((uint64_t)swz << 62);
}
__device__ __forceinline__ void wg_fence() { asm volatile("wgmma.fence.sync.aligned;" ::: "memory"); }
__device__ __forceinline__ void wg_commit() { asm volatile("wgmma.commit_group.sync.aligned;" ::: "memory"); }
template <int N> __device__ __forceinline__ void wg_wait() { asm volatile("wgmma.wait_group.sync.aligned %0;" :: "n"(N) : "memory"); }
template <int M> __device__ __forceinline__ void acc_ready(float* d) {
#pragma unroll
    for (int j = 0; j < M; j++) asm volatile("" : "+f"(d[j]) :: "memory");
}
template <int N, int M> __device__ __forceinline__ void wg_wait_acc(float* d) { wg_wait<N>(); acc_ready<M>(d); }

#define F8(c, d, o) c(d[o]), c(d[o + 1]), c(d[o + 2]), c(d[o + 3]), c(d[o + 4]), c(d[o + 5]), c(d[o + 6]), c(d[o + 7])
#define R8L "%0,%1,%2,%3,%4,%5,%6,%7"
#define R16L R8L ",%8,%9,%10,%11,%12,%13,%14,%15"
#define R32L R16L ",%16,%17,%18,%19,%20,%21,%22,%23,%24,%25,%26,%27,%28,%29,%30,%31"
#define R40L R32L ",%32,%33,%34,%35,%36,%37,%38,%39"
#define WG_BOTH(TXT_PRE, TXT_POST, OUTS, ...)                                                   \
    if (acc) asm volatile(TXT_PRE "1" TXT_POST : OUTS("+f") : __VA_ARGS__);                     \
    else asm volatile(TXT_PRE "0" TXT_POST : OUTS("=f") : __VA_ARGS__)
#define O8(c) F8(c, d, 0)
#define O16(c) F8(c, d, 0), F8(c, d, 8)
#define O32(c) O16(c), F8(c, d, 16), F8(c, d, 24)
#define O40(c) O32(c), F8(c, d, 32)
#define WGM(n) "wgmma.mma_async.sync.aligned.m64n" #n "k16.f32.bf16.bf16 "
__device__ __forceinline__ void wg_rs16(float* d, const uint32_t* a, uint64_t db, bool acc) {
    WG_BOTH(WGM(16) "{" R8L "}, {%8,%9,%10,%11}, %12, ", ", 1, 1, 1;", O8, "r"(a[0]), "r"(a[1]), "r"(a[2]), "r"(a[3]), "l"(db));
}
__device__ __forceinline__ void wg_ss16(float* d, uint64_t da, uint64_t db, bool acc) {
    WG_BOTH(WGM(16) "{" R8L "}, %8, %9, ", ", 1, 1, 1, 1;", O8, "l"(da), "l"(db));
}
__device__ __forceinline__ void wg_rs8(float* d, const uint32_t* a, uint64_t db, bool acc) {
#define O4(c) c(d[0]), c(d[1]), c(d[2]), c(d[3])
    WG_BOTH(WGM(8) "{%0,%1,%2,%3}, {%4,%5,%6,%7}, %8, ", ", 1, 1, 0;", O4, "r"(a[0]), "r"(a[1]), "r"(a[2]), "r"(a[3]), "l"(db));
}
__device__ __forceinline__ void wg_rs32(float* d, const uint32_t* a, uint64_t db, bool acc) {
    WG_BOTH(WGM(32) "{" R16L "}, {%16,%17,%18,%19}, %20, ", ", 1, 1, 0;", O16, "r"(a[0]), "r"(a[1]), "r"(a[2]), "r"(a[3]), "l"(db));
}
__device__ __forceinline__ void wg_ss32(float* d, uint64_t da, uint64_t db, bool acc) {
    WG_BOTH(WGM(32) "{" R16L "}, %16, %17, ", ", 1, 1, 1, 0;", O16, "l"(da), "l"(db));
}
template <int TB> __device__ __forceinline__ void wg_rs64(float* d, const uint32_t* a, uint64_t db, bool acc) {
    WG_BOTH(WGM(64) "{" R32L "}, {%32,%33,%34,%35}, %36, ", ", 1, 1, %37;", O32, "r"(a[0]), "r"(a[1]), "r"(a[2]), "r"(a[3]), "l"(db), "n"(TB));
}
template <int TB> __device__ __forceinline__ void wg_ss64(float* d, uint64_t da, uint64_t db, bool acc) {
    WG_BOTH(WGM(64) "{" R32L "}, %32, %33, ", ", 1, 1, 1, %34;", O32, "l"(da), "l"(db), "n"(TB));
}
__device__ __forceinline__ void wg_ss80(float* d, uint64_t da, uint64_t db, bool acc) {
    WG_BOTH(WGM(80) "{" R40L "}, %40, %41, ", ", 1, 1, 1, 1;", O40, "l"(da), "l"(db));
}

constexpr float SM_SCALE = 0.08838834764831845f;
constexpr float LOG2E = 1.4426950408889634f;

#define WO_DELAY 3000
#define D_DELAY 7000
#define F1_DELAY 7000
#define W2_DELAY 16500
#define F1_DEPTH 30
#define PF_DELAY 6000
#define PF_PACE 400
__device__ __forceinline__ void hold_back(uint32_t ns) {
    const uint32_t t0 = timer_lo();
    while (timer_lo() - t0 < ns) __nanosleep(50);
}

__device__ __forceinline__ uint32_t* flag_ptr(int stage, int b) { return &g_flag[stage][b][0]; }
__device__ __forceinline__ uint32_t this_launch() { return ld_rlx(&g_epoch[fresh_bid()][0]) + 1; }
__device__ __forceinline__ bool flag_up(int stage, int b, uint32_t target) { return (int)(ld_rlx(flag_ptr(stage, b)) - target) >= 0; }
__device__ __forceinline__ void flag_wait(int stage, int b, uint32_t target) {
    [[maybe_unused]] int n = 0;
    while (!flag_up(stage, b, target)) {
        __nanosleep(20);
        SPIN_CHECK(n, 10 + stage);
    }
    fence_acq_gpu();
    fence_async_glb();
}
__device__ __forceinline__ void publish(int stage, int b) {
    fence_async_glb();
    fence_rel_gpu();
    red_add_u32(flag_ptr(stage, b), 1);
}
__device__ __forceinline__ uint32_t unit_frag_addr(int tid) {
    const int lane = tid & 31, w = (tid >> 5) & 3, i = lane & 7, j = lane >> 3;
    return ((j >> 1) * 8 + i) * 128 + ((((w << 1) + (j & 1)) ^ i) << 4);
}

#define V_BURST1 3
#define V_BURST2 1
#define V_PRE 9
#define SX_BF16 0
#define V_REV 1
#define K_GATE 1
#define WO_R8 1
#define OX_V4 0
#define V_LEAD 9
static_assert((V_BURST1 + V_BURST2 >= 2 || V_PRE == 7) && V_BURST1 <= 3 && V_LEAD > V_BURST1 + V_BURST2, "q and k rely on v for the arrival of the blocks");
#define K_LEAD 0
#define Q_LEAD 36
#define V_FIRST 8
#define SX_GATE 1
static_assert(SX_GATE, "EB_QF also stands for the K tile");
#define V_EARLY 0
__host__ __device__ constexpr int x_order(int mat, int j) {
    return mat == 2 ? j : j < 3 ? j + 5 : j < 5 ? j : j == 5 ? 2 : j == 6 ? 8 : 8 - j;
}
#define SS0Q 0
#define SS0K 0
#define SS0V 22
#define SSLQ 36
#define SSLK 36
#define SSLV 14
__host__ __device__ constexpr uint64_t ss_mask(int mat) {
    const int ns = 36 - (mat == 0 ? NRQ : mat == 1 ? NRK : NRV);
    const int j0 = mat == 0 ? SS0Q : mat == 1 ? SS0K : SS0V, len = mat == 0 ? SSLQ : mat == 1 ? SSLK : SSLV;
    uint64_t m = 0;
    for (int j = j0; j < j0 + len; j++)
        if ((j - j0) * ns / len != (j - j0 + 1) * ns / len) m |= 1ull << (x_order(mat, j >> 2) * 4 + (j & 3));
    return m;
}
__device__ __forceinline__ int popc_below(uint64_t m, int k) { return __popcll(m & ((1ull << k) - 1)); }
__host__ __device__ constexpr int x_slot(int f) {
    return f < 3 ? E_R0 + f * 8192 : f == 3 ? E_QT : f == 4 ? E_KT : f < 7 ? E_MEM + (f - 5) * 8192 : f == 8 ? E_R2 : f == 10 ? E_R1 : E_R0;
}
__host__ __device__ constexpr int x_full(int f) { return f < 3 ? 0 : f < 9 ? (f - 1) / 2 : 14 - f; }
__host__ __device__ constexpr bool x_first(int f) { return f == 0 || x_full(f) != x_full(f - 1); }
__host__ __device__ constexpr int x_empty(int blk) { return blk == 6 ? 0 : blk == 7 ? 1 : blk == 4 ? 2 : -1; }
__host__ __device__ constexpr int ar_tile(int j) { return j == 0 ? 8 : ((j - 1) & 1) * 4 + ((j - 1) >> 1); }
__host__ __device__ constexpr int sx_off(int u) { return u == 0 ? 0 : u == 1 ? 1536 : u == 2 ? 2560 : u == 3 ? 3072 : 5120; }

template <int MAT, int NR, int K0, int K1>
__device__ __forceinline__ void proj_mem(float* d, const uint32_t (&w)[NR][4]) {
    constexpr uint64_t M = ss_mask(MAT);
    const uint64_t db = mkdesc(E_MEM, 128, 9216, 0);
    const uint64_t da = mkdesc((MAT == 0 ? E_WQ : MAT == 1 ? E_WK : E_WV), 1024, 1024, 1);
#pragma unroll
    for (int j = K0; j < K1; j++) {
        const int ks = MAT != 2 ? ar_tile(j >> 2) * 4 + (j & 3) : V_REV ? 35 - j : j, s = popc_below(M, ks);
        if ((M >> ks) & 1) wg_ss16(d, da + s * 128, db + ks * 16, j > 0);
        else wg_rs16(d, w[ks - s], db + ks * 16, j > 0);
    }
}
__device__ __forceinline__ uint32_t tl_lane(int tid, int group_bytes) {
    return ((tid >> 4) & 1) * group_bytes + (((tid >> 5) & 3) * 16 + (tid & 15)) * 16;
}
struct ArWords {
    uint32_t w[5];
    __device__ __forceinline__ ArWords(const float* y) {
        w[0] = pack2(y[0], y[1]); w[1] = pack2(y[2], y[3]); w[2] = pack2(y[4], y[5]); w[3] = pack2(y[6], 1.f); w[4] = pack2(y[7], 1.f);
    }
    __device__ __forceinline__ void force(uint32_t zero) {
        asm volatile("{.reg .pred p; setp.ne.u32 p, %0, 0; @p st.shared.v4.b32 [%5], {%1,%2,%3,%4};}" :: "r"(zero), "r"(w[0]), "r"(w[1]), "r"(w[2]), "r"(w[3]), "r"(w[4]) : "memory");
    }
    __device__ __forceinline__ void red(uint8_t* p, uint8_t* q) {
        asm volatile("red.relaxed.gpu.global.add.noftz.v4.bf16x2 [%0], {%1,%2,%3,%4};" :: "l"(p), "r"(w[0]), "r"(w[1]), "r"(w[2]), "r"(w[3]) : "memory");
        asm volatile("red.relaxed.gpu.global.add.noftz.bf16x2 [%0], %1;" :: "l"(q), "r"(w[4]) : "memory");
    }
};
__device__ __forceinline__ uint32_t ar_main(int tid) { return ((tid & 127) >> 3) * AR_STR + (tid & 7) * 16; }
__device__ __forceinline__ uint32_t ar_side(int tid) { return ((tid & 127) >> 5) * (4 * AR_STR) + AR_STR / 2 + (tid & 31) * 4; }

#define AR_VA 0
#define AR_VA1 1
#define AR_SPLIT 5
template <bool B> struct Bool { static constexpr bool value = B; };
template <int J0, int J1>
__device__ __forceinline__ int ar_fetch(const Params& P, int i, int tid, uint32_t gate, uint32_t done) {
    const uint8_t* pm = g_ar + ((i & 3) * AR_SLOT + ar_main(tid));
    const uint8_t* ps = g_ar + ((i & 3) * AR_SLOT + ar_side(tid));
    const uint32_t a = sb + E_MEM + tl_lane(tid, 9216);
    asm volatile("{.reg .pred p; setp.ne.u32 p, %0, 0; @p st.shared.v2.b64 [%3], {%1,%2};}" :: "r"(P.zero), "l"(pm), "l"(ps), "r"(a) : "memory");
    mbar_wait(gate, (i & 1) ^ 1);
    int n = -1;
    bool bad = i >= 0;
    while (bad) {
        uint4 av[J1 - J0];
        uint32_t as[J1 - J0];
#pragma unroll
        for (int j = J0; j < J1; j++) { av[j - J0] = ld_rlx128(pm + ar_tile(j) * (16 * AR_STR)); as[j - J0] = ld_rlx(ps + ar_tile(j) * (16 * AR_STR)); }
        bad = false;
#pragma unroll
        for (int j = J0; j < J1; j++) {
            bad |= __byte_perm(av[j - J0].w, as[j - J0], 0x7632) != (ar_tile(j) == 8 ? 0x42804280u : 0x42004200u);
            stsm4(a + ar_tile(j) * 1024, av[j - J0].x, av[j - J0].y, av[j - J0].z, __byte_perm(av[j - J0].w, as[j - J0], 0x5410));
        }
        bad = __any_sync(~0u, bad);
        SPIN_CHECK(n, 2);
        PROF_INC(n, 1);
    }
    if (i < 0 || i + 1 == LAG) {
        const uint16_t* m = (const uint16_t*)P.mem0 + (tid & 3) * (2 * DM) + (tid >> 5) * 16 + ((tid & 31) >> 2);
        const uint32_t a2 = sb + E_MEM + (tid >> 5) * 256 + (tid & 31) * 4;
        uint32_t v[18];
#pragma unroll
        for (int T = 2 * J0; T < 2 * J1; T++) v[T] = (uint32_t)__ldg(m + ar_tile(T >> 1) * 64 + (T & 1) * 8) | ((uint32_t)__ldg(m + ar_tile(T >> 1) * 64 + (T & 1) * 8 + DM) << 16);
        __syncwarp();
#pragma unroll
        for (int T = 2 * J0; T < 2 * J1; T++) {
            sts32(a2 + 9216 + ar_tile(T >> 1) * 1024 + (T & 1) * 128, v[T]);
            if (i < 0) sts32(a2 + ar_tile(T >> 1) * 1024 + (T & 1) * 128, v[T]);
        }
    }
    fence_async_smem();
    mbar_arrive_warp(done);
    return n;
}

__device__ __forceinline__ void attn_mem(float* d, uint32_t par, int i, int tid) {
    const int lane = tid & 31, warp = tid >> 5, c = warp >> 1, hf = warp & 1;
    const int rank = cta_rank();
    const uint32_t peer = mapa(sb, rank ^ 1);
    const uint32_t l4 = (lane >> 4) * 1024 + (lane & 15) * 16;
    uint32_t kb[4][4];
    {
        const uint32_t aK = sb + E_KT + (c * 6 + hf * 2) * 1024 + l4;
#pragma unroll
        for (int ks = 0; ks < 4; ks++) ldsm4t(kb[ks], aK + ks * 256);
    }
    const uint32_t aQs = pin(sb + E_QM + tl_lane(tid, 1024));
    const uint32_t aQ = pin(sb + E_QM + c * 1024 + (((lane >> 3) & 1) * 16 + (lane >> 4) * 8 + (lane & 7)) * 16);
    const uint32_t aM = pin(sb + E_KT + (4 + c) * 1024 + lane * 16);
    const uint32_t oS = pin(tid * 16);
    wg_wait_acc<0, 8>(d);
    stsm4(aQs, pack2(d[0], d[1]), pack2(d[2], d[3]), pack2(d[4], d[5]), pack2(d[6], d[7]));
    nbar_sync(NB_QK, 256);
    TS(0, i, 1);
    float s[6];
    {
        uint32_t q[2][4], km[2][4];
        ldsm4t(q[0], aQ); ldsm4t(km[0], aM); ldsm4t(q[1], aQ + 512); ldsm4t(km[1], aM + 512);
        float a[6][4];
#pragma unroll
        for (int m = 0; m < 6; m++) a[m][0] = a[m][1] = a[m][2] = a[m][3] = 0.f;
#pragma unroll
        for (int j = 0; j < 2; j++) {
#pragma unroll
            for (int o = 0; o < 2; o++) {
                mma16816(a[o * 3], q[j], kb[2 * j + o][0], kb[2 * j + o][1]);
                mma16816(a[o * 3 + 1], q[j], kb[2 * j + o][2], kb[2 * j + o][3]);
            }
            mma16816(a[2], q[j], km[j][0], km[j][1]);
            mma16816(a[5], q[j], km[j][2], km[j][3]);
        }
        nbar_arrive(NB_S, 256);
        if (SX_GATE) nbar_arrive(NB_S2, 256);
#pragma unroll
        for (int m = 0; m < 3; m++) { s[2 * m] = a[m][0] + a[3 + m][2]; s[2 * m + 1] = a[m][1] + a[3 + m][3]; }
    }
    st_async128(peer + E_SR + oS, fu(s[0]), fu(s[1]), fu(s[2]), fu(s[3]), peer + SM_BAR + EB_SM * 8);
    const uint32_t oM = E_SR + 2048 + c * 256 + lane * 8;
    asm volatile("st.async.shared::cluster.mbarrier::complete_tx::bytes.b32 [%0], %1, [%2];"
                 :: "r"(peer + oM + hf * 4), "r"(fu(hf ? s[5] : s[4])), "r"(peer + SM_BAR + EB_SM * 8) : "memory");
    sts128(sb + E_SL + oS, fu(s[0]), fu(s[1]), fu(s[2]), fu(s[3]));
    mbar_arrive_warp(bars + EB_KF * 8);
    TS(0, i, 2);
#pragma unroll
    for (int j = 0; j < 4; j++) ldsm4(kb[j], sb + E_VT + c * 6144 + l4 + hf * 512 + ((j >> 1) ^ hf) * 2048 + (j & 1) * 256);
    nbar_sync(NB_G, 128);
    const uint32_t aR = sb + E_SR + oS, aR1 = sb + E_SR + (oS ^ 512), aRm = sb + oM;
    const uint4 l1 = lds128(aR1 + (E_SL - E_SR));
    mbar_wait_cl(bars + EB_SM * 8, par);
    TS(0, i, 3);
    float p[10];
    {
        const uint4 r0 = lds128(aR), r1 = lds128(aR1);
        const uint2 rm = lds64(aRm);
        p[0] = s[0] + uf(r0.x); p[1] = s[1] + uf(r0.y); p[2] = s[2] + uf(r0.z); p[3] = s[3] + uf(r0.w);
        p[4] = uf(l1.x) + uf(r1.x); p[5] = uf(l1.y) + uf(r1.y); p[6] = uf(l1.z) + uf(r1.z); p[7] = uf(l1.w) + uf(r1.w);
        p[8] = s[4] + uf(rm.x); p[9] = s[5] + uf(rm.y);
    }
    float mx = fmaxf(fmaxf(fmaxf(p[0], p[1]), fmaxf(p[2], p[3])), fmaxf(fmaxf(fmaxf(p[4], p[5]), fmaxf(p[6], p[7])), fmaxf(p[8], p[9])));
    mx = fmaxf(mx, __shfl_xor_sync(~0u, mx, 1));
    mx = fmaxf(mx, __shfl_xor_sync(~0u, mx, 2));
    const float mo = mx * (SM_SCALE * LOG2E);
    mbar_wait(bars + EB_KF * 8, par);
    uint32_t vm[4], pb[5];
    ldsm4(vm, aM + (E_VT - E_KT) + hf * 512);
    float o[3][4];
    const uint32_t ones[4] = {0x3f803f80u, 0x3f803f80u, 0x3f803f80u, 0x3f803f80u};
#pragma unroll
    for (int T = 0; T < 3; T++) o[T][0] = o[T][1] = o[T][2] = o[T][3] = 0.f;
#pragma unroll
    for (int j = 0; j < 2; j++) {
#pragma unroll
        for (int m = 2 * j; m < 2 * j + 2; m++) pb[m] = pack2(ex2(fmaf(p[2 * m], SM_SCALE * LOG2E, -mo)), ex2(fmaf(p[2 * m + 1], SM_SCALE * LOG2E, -mo)));
        mma16816(o[2], ones, pb[2 * j], pb[2 * j + 1]);
#pragma unroll
        for (int T = 0; T < 2; T++) mma16816(o[T], kb[2 * j + T], pb[2 * j], pb[2 * j + 1]);
    }
    pb[4] = pack2(ex2(fmaf(p[8], SM_SCALE * LOG2E, -mo)), ex2(fmaf(p[9], SM_SCALE * LOG2E, -mo)));
    mma1688(o[2], ones[0], ones[1], pb[4]);
#pragma unroll
    for (int T = 0; T < 2; T++) mma1688(o[T], vm[2 * T], vm[2 * T + 1], pb[4]);
    nbar_arrive(NB_PV, 256);
    mbar_arrive_warp(bars + EB_CONS * 8);
    const float i0 = rcp(o[2][0]), i1 = rcp(o[2][1]);
    uint32_t ow[4];
#pragma unroll
    for (int j = 0; j < 4; j++) ow[j] = pack2(o[j >> 1][2 * (j & 1)] * i0, o[j >> 1][2 * (j & 1) + 1] * i1);
    const uint32_t oO = E_OM + c * 2048 + hf * 512;
    stsm4(sb + oO + lane * 16, ow[0], ow[1], ow[2], ow[3]);
    if (OX_V4) {
        __syncwarp();
        const uint4 r = lds128(sb + oO + lane * 16);
        nbar_sync(NB_G, 128);
        st_async128(peer + oO + 1024 + lane * 16, r.x, r.y, r.z, r.w, peer + SM_BAR + EB_OX * 8);
    } else {
#pragma unroll
        for (int j = 0; j < 4; j++)
            asm volatile("st.async.shared::cluster.mbarrier::complete_tx::bytes.b32 [%0], %1, [%2];"
                         :: "r"(peer + oO + 1024 + j * 128 + lane * 4), "r"(ow[j]), "r"(peer + SM_BAR + EB_OX * 8) : "memory");
    }
}

__device__ __forceinline__ void attn_x_scores(float (&p)[2][10], uint32_t par, int i, int tid) {
    {
        float s[40];
        const uint64_t da = mkdesc(E_QT, 128, 1024, 0), db = mkdesc(E_KT, 128, 1024, 0);
        wg_fence();
#pragma unroll
        for (int ks = 0; ks < 4; ks++) wg_ss80(s, da + ks * 16, db + ks * 16, ks > 0);
        wg_commit();
        const int dq = (tid >> 2) - 2 * (tid & 3);
        float mask[8];
#pragma unroll
        for (int j = 0; j < 8; j++) mask[j] = (j >> 1) * 8 + (j & 1) > dq ? -1e9f * LOG2E : 0.f;
        mbar_wait_cl(bars + EB_PRDY * 8, par);
        wg_wait_acc<0, 40>(s);
#pragma unroll
        for (int u = 0; u < 5; u++) {
            const int v = u < 4 ? 6 + u : 5;
            constexpr float C = SM_SCALE * LOG2E;
            const float m0 = u < 4 ? mask[2 * u & 7] : 0.f, m1 = u < 4 ? mask[(2 * u + 1) & 7] : 0.f;
            p[0][2 * u] = fmaf(s[4 * u], C, m0); p[0][2 * u + 1] = fmaf(s[4 * u + 1], C, m1); p[1][2 * u] = fmaf(s[4 * v + 2], C, m0); p[1][2 * u + 1] = fmaf(s[4 * v + 3], C, m1);
        }
    }
    mbar_arrive_warp(bars + EB_QF * 8);
    const int w = tid >> 5;
    if (!SX_BF16) {
        const uint32_t peer = mapa(sb, cta_rank() ^ 1);
#pragma unroll
        for (int u = 0; u < 5; u++)
            if (u == 0 || u <= w || u == 4) st_async128(peer + E_SX + sx_off(u) + tid * 16, fu(p[0][2 * u]), fu(p[0][2 * u + 1]), fu(p[1][2 * u]), fu(p[1][2 * u + 1]), peer + SM_BAR + EB_SX * 8);
    } else {
        const uint32_t peer = mapa(sb, cta_rank() ^ 1), a = peer + E_SX + tid * 16, mb = peer + SM_BAR + EB_SX * 8;
        st_async128(a, pack2(p[0][0], p[0][1]), pack2(p[1][0], p[1][1]), pack2(p[0][8], p[0][9]), pack2(p[1][8], p[1][9]), mb);
        if (w >= 1) st_async128(a + 2048, pack2(p[0][2], p[0][3]), pack2(p[1][2], p[1][3]), pack2(p[0][4], p[0][5]), pack2(p[1][4], p[1][5]), mb);
        if (w >= 3) st_async64(a + 4096, pack2(p[0][6], p[0][7]), pack2(p[1][6], p[1][7]), mb);
    }
    TS(128, i, 10);
}
__device__ __forceinline__ void attn_x_finish(float (&p)[2][10], uint32_t par, int i, int& tid, uint32_t zero) {
    const int w = tid >> 5;
    mbar_wait_cl(bars + EB_SX * 8, par);
    TS(128, i, 11);
    if (SX_BF16) {
        const uint32_t a = sb + E_SX + tid * 16;
        const uint4 r0 = lds128(a), r1 = lds128(a + (w >= 1 ? 2048 : 0));
        const uint2 r2 = lds64(a + (w >= 3 ? 4096 : 0));
        const uint32_t r[10] = {r0.x, r0.y, r1.x, r1.y, r1.z, r1.w, r2.x, r2.y, r0.z, r0.w};
#pragma unroll
        for (int j = 0; j < 10; j++) { p[j & 1][j & ~1] += bf_lo(r[j]); p[j & 1][j | 1] += bf_hi(r[j]); }
    } else
#pragma unroll
    for (int u = 0; u < 5; u++) {
        const uint4 r = lds128(pin(sb + tid * 16 + (u == 0 || u <= w ? sx_off(u) : sx_off(4))) + E_SX);
        p[0][2 * u] += uf(r.x); p[0][2 * u + 1] += uf(r.y); p[1][2 * u] += uf(r.z); p[1][2 * u + 1] += uf(r.w);
    }
    nbar_sync(NB_W, 128);
    uint32_t pa[5][4];
    float mx[2], inv[2];
#pragma unroll
    for (int h = 0; h < 2; h++) {
        const float* q = p[h];
        mx[h] = fmaxf(fmaxf(fmaxf(q[0], q[1]), fmaxf(q[2], q[3])), fmaxf(fmaxf(fmaxf(q[4], q[5]), fmaxf(q[6], q[7])), fmaxf(q[8], q[9])));
    }
#pragma unroll
    for (int o = 1; o < 4; o <<= 1) { mx[0] = fmaxf(mx[0], __shfl_xor_sync(~0u, mx[0], o)); mx[1] = fmaxf(mx[1], __shfl_xor_sync(~0u, mx[1], o)); }
#pragma unroll
    for (int h = 0; h < 2; h++) {
        float* q = p[h];
#pragma unroll
        for (int j = 0; j < 10; j++) q[j] = ex2(q[j] - mx[h]);
#pragma unroll
        for (int u = 0; u < 4; u++) {
            pa[h * 3 + (u >> 1)][(u & 1) * 2 + h] = pack2(q[2 * u], q[2 * u + 1]);
            pa[h * 3 + (u >> 1)][(u & 1) * 2 + (h ^ 1)] = zero << (h * 5 + u + 1);
        }
        pa[2][h * 3] = pack2(q[8], q[9]);
        pa[2][1 + h] = zero << (h * 5 + 5);
    }
    mbar_wait(bars + EB_CONS * 8, par);
    fence_async_smem();
    tid = pin(tid << zero);
    const uint32_t aO = pin(sb + (((tid >> 4) & 1) * 8 + (tid & 7)) * 128 + (((((tid >> 3) & 1) * 4 + (tid >> 5)) ^ (tid & 7)) << 4)) + E_R1;
    TS(128, i, 12);
#pragma unroll
    for (int nh = 0; nh < 2; nh++) {
        float o[16], sum[4];
        const uint64_t db = mkdesc(E_VT + nh * 512, 1024, 128, 0);
        wg_fence();
#pragma unroll
        for (int kk = 0; kk < 5; kk++) {
            if (nh == 0) wg_rs8(sum, pa[kk], mkdesc(SM_ONES, 0, 0, 0), kk > 0);
            wg_rs32(o, pa[kk], db + kk * 128, kk > 0);
        }
        wg_commit();
        wg_wait_acc<0, 16>(o);
        if (nh == 0) { acc_ready<4>(sum); inv[0] = rcp(sum[0]); inv[1] = rcp(sum[2]); }
#pragma unroll
        for (int j = 0; j < 2; j++) {
            const float* y = &o[8 * j];
            stsm4t(aO + nh * 4096 + j * 2048, pack2(y[0] * inv[0], y[1] * inv[0]), pack2(y[2] * inv[1], y[3] * inv[1]), pack2(y[4] * inv[0], y[5] * inv[0]), pack2(y[6] * inv[1], y[7] * inv[1]));
        }
    }
    mbar_arrive_warp(bars + EB_OST * 8);
    TS(128, i, 13);
}

template <int MAT>
__device__ __forceinline__ void engine_main(const Params& P) {
    constexpr int NR = MAT == 0 ? NRQ : MAT == 1 ? NRK : NRV;
    constexpr uint64_t M = ss_mask(MAT);
    uint32_t w[NR][4];
    {
        const uint32_t a = sb + E_WO + (MAT == 0 ? 0 : MAT == 1 ? NRQ : NRQ + NRK) * 2048 + unit_frag_addr(fresh_tid());
        mbar_wait(bars + EB_WL * 8, 0);
        if (MAT == 0 && threadIdx.x == 0) TG(79, 2);
#pragma unroll
        for (int u = 0; u < NR; u++) ldsm4t(w[u], a + u * 2048);
    }
    nbar_arrive(NB_T, 448);
    int tid = fresh_tid() - MAT * 128;
#define TID (tid = pin(tid << P.zero))
    if (MAT == 0) { if (V_FIRST == 36) nbar_arrive(NB_S, 256); nbar_arrive(NB_PV, 256); nbar_arrive(NB_WO, 256); }
    auto project = [&](auto one, const int i) {
        constexpr bool ONE = decltype(one)::value;
        const uint32_t par = i & 1;
        {
            float d[ONE ? 16 : 32];
            const uint64_t da = mkdesc((MAT == 0 ? E_WQ : MAT == 1 ? E_WK : E_WV), 1024, 1024, 1);
            constexpr int R1 = V_BURST1, R2 = V_BURST1 + V_BURST2;
#pragma unroll
            for (int n = 0; n < 9; n++) {
                const int blk = x_order(MAT, n), prev = n ? x_order(MAT, n - 1) : -1, f = MAT != 2 && blk < 2 ? 9 + blk : blk;
                if (MAT == 2) {
                    if (R2 >= 2 && n == (R1 >= 2 ? R1 : R2)) { wg_wait<0>(); mbar_arrive_warp(bars + EB_V0 * 8); }
                    if ((n == 0 && (V_FIRST == 36 || i == 0)) || n == R1 || n == R2) {
#pragma unroll
                        for (int j = n; j < (n < R1 ? R1 : n < R2 ? R2 : V_PRE); j++) if (x_first(j)) mbar_wait(bars + (EB_FULL + x_full(j)) * 8, par);
                    }
                    if (n == 0 && V_FIRST == 36) nbar_sync(NB_S, 256);
                    if (n == R1) nbar_sync(NB_PV, 256);
                    if (n == R2) nbar_sync(NB_WO, 256);
                } else {
                    if (n == 0) nbar_sync(MAT ? NB_VL : NB_VL2, 256);
                }
                static_assert(V_PRE == 9 || (V_PRE == 7 && V_LEAD > 7), "see the barriers");
                const bool wt = MAT == 2 ? f == V_PRE : f >= 9;
                if (wt) mbar_wait(bars + (EB_FULL + x_full(f)) * 8, par);
                TX(MAT * 128, 1 + MAT * 9 + n);
                if (wt || n == 0 || (MAT == 2 && (n == R1 || n == R2))) wg_fence();
                if (n == 0) TS(MAT * 128, i, 20 + MAT);
                const uint64_t db = mkdesc(x_slot(f), 16, 1024, 1);
#pragma unroll
                for (int j = 0; j < 4; j++) {
                    const int ks = blk * 4 + j, s = popc_below(M, ks);
                    if constexpr (ONE) {
                        if ((M >> ks) & 1) wg_ss32(d, da + s * 128, db + j * 2, n + j > 0);
                        else wg_rs32(d, w[ks - s], db + j * 2, n + j > 0);
                    } else {
                        if ((M >> ks) & 1) wg_ss64<0>(d, da + s * 128, db + j * 2, n + j > 0);
                        else wg_rs64<0>(d, w[ks - s], db + j * 2, n + j > 0);
                    }
                }
                wg_commit();
                if (MAT == 2 && n + 1 == V_LEAD) { nbar_arrive(NB_VL, 256); if (!K_LEAD) nbar_arrive(NB_VL2, 256); }
                if (MAT == 1 && n + 1 == K_LEAD) nbar_arrive(NB_VL2, 256);
                if (MAT == 2 && R2 < 2 && n == 3) { wg_wait<2>(); mbar_arrive_warp(bars + EB_V0 * 8); }
                if (MAT != 2 && x_empty(prev) >= 0) { wg_wait<1>(); mbar_arrive_warp(bars + (EB_EMPTY + x_empty(prev)) * 8); }
            }
            const uint32_t a = sb + (MAT == 0 ? E_QT : MAT == 1 ? E_KT : E_VT) + tl_lane(TID, MAT == 0 ? 2048 : 1024) + (ONE && i >= NSEG ? (MAT == 0 ? 1024 : 6144) : 0);
            if (MAT != 2) {
                mbar_wait(bars + (EB_EMPTY + 2) * 8, par);
                if (!ONE) mbar_wait(bars + EB_MEMA * 8, par);
            } else {
                mbar_wait(bars + EB_OST * 8, par ^ 1);
            }
            wg_wait_acc<0, ONE ? 16 : 32>(d);
            TS(MAT * 128, i, 23 + MAT);
#pragma unroll
            for (int j = 0; j < (ONE ? 4 : 8); j += 2) {
                const int grp = MAT == 0 ? 2 * (j & 3) + (j >> 2) : j < 4 ? j : j + 2;
                stsm4(a + grp * 1024, pack2(d[4 * j], d[4 * j + 1]), pack2(d[4 * j + 2], d[4 * j + 3]), pack2(d[4 * j + 4], d[4 * j + 5]), pack2(d[4 * j + 6], d[4 * j + 7]));
            }
        }
        if (MAT != 2) {
            if (ONE) mbar_arrive_warp(bars + EB_STEP * 8);
            if (ONE) mbar_wait(bars + EB_MEMA * 8, par);
        } else {
            __syncwarp();
            if ((TID & 31) < 3) mbar_arrive(bars + (EB_EMPTY + (tid & 31)) * 8);
        }
    };
    auto step = [&](const int i) {
        const uint32_t par = i & 1;
        if (MAT == 2) {
            if (Q_LEAD) nbar_sync(NB_OM, K_GATE ? 384 : 256);
            else mbar_wait(bars + EB_MEM * 8, par);
        }
        float d[8];
        TS(MAT * 128, i, MAT == 2 ? 26 : 14 + MAT);
        wg_fence();
        constexpr int MID = MAT == 2 ? V_FIRST : Q_LEAD;
        if (MAT != 2) {
            static_assert(Q_LEAD >= AR_SPLIT * 4, "v relies on q for the rest");
            proj_mem<MAT, NR, 0, AR_SPLIT * 4>(d, w);
            mbar_wait(bars + EB_MEM * 8, par);
            wg_fence();
        }
        proj_mem<MAT, NR, MAT != 2 ? AR_SPLIT * 4 : 0, MID>(d, w);
        if ((MAT == 0 || (MAT == 1 && K_GATE)) && Q_LEAD) nbar_arrive(NB_OM, K_GATE ? 384 : 256);
        if (MAT == 2 && V_FIRST < 36) {
            if (V_BURST1) mbar_wait(bars + EB_FULL * 8, i == NSTEP - 1 ? par : par ^ 1);
            nbar_sync(NB_S, 256);
            wg_fence();
        }
        proj_mem<MAT, NR, MID, 36>(d, w);
        wg_commit();
        if (MAT == 0) {
            mbar_wait(bars + EB_WO * 8, 0);
            tid *= mbar_wait(bars + EB_STEP * 8, par);
            attn_mem(d, par, i, tid);
        } else if (MAT == 1) {
            tid *= mbar_wait(bars + EB_STEP * 8, par);
            const uint32_t a = pin(sb + E_KT + 4096 + tl_lane(tid, 1024));
            wg_wait_acc<0, 8>(d);
            stsm4(a, pack2(d[0], d[1]), pack2(d[2], d[3]), pack2(d[4], d[5]), pack2(d[6], d[7]));
            nbar_arrive(NB_QK, 256);
            TS(128, i, 18);
            fence_async_smem();
            nbar_sync(SX_GATE ? NB_S2 : NB_W, SX_GATE ? 256 : 128);
            float p[2][10];
            attn_x_scores(p, par, i, TID);
            attn_x_finish(p, par, i, TID, pin(P.zero));
        } else {
            const uint32_t a = pin(sb + E_VT + 4096 + tl_lane(TID, 1024));
            wg_wait_acc<0, 8>(d);
            stsm4(a, pack2(d[0], d[1]), pack2(d[2], d[3]), pack2(d[4], d[5]), pack2(d[6], d[7]));
            mbar_arrive_warp(bars + EB_KF * 8);
            TS(256, i, 16);
        }
        if (MAT == 0) {
            const int rank = cta_rank();
            uint8_t* const ar = g_ar + (i & 3) * AR_SLOT;
            uint8_t* const pm = ar + pin(ar_main(TID) + rank * (64 * AR_STR));
            uint8_t* const ps = ar + pin(ar_side(tid) + rank * (64 * AR_STR));
            const uint32_t o8 = (128 - rank * 64) * AR_STR;
            const uint64_t db = mkdesc(E_OM, 128, 2048, 0), da = mkdesc(E_WO, 1024, 1024, 1);
            if (!OX_V4) nbar_sync(NB_G, 128);
            fence_async_smem();
            TS(0, i, 6);
            if (i == NSTEP - 1) { mbar_wait_cl(bars + EB_OX * 8, par); return; }
            float y[4][8];
            wg_fence();
#pragma unroll
            for (int ks = 0; ks < 4; ks++) wg_ss16(y[3], da + (32 + ks) * 128, db + ks * 16, ks > 0);
            wg_commit();
#pragma unroll
            for (int j = 0; j < 12; j++) wg_ss16(y[j % 3], da + ((j % 3) * 8 + j / 3) * 128, db + (j / 3) * 16, j >= 3);
            wg_commit();
            wg_wait_acc<1, 8>(y[3]);
            ArWords z(y[3]);
            if (WO_R8) z.red(pm + o8, ps + o8); else z.force(P.zero);
            mbar_wait_cl(bars + EB_OX * 8, par);
            fence_async_smem();
            wg_fence();
#pragma unroll
            for (int T = 0; T < 4; T++) {
#pragma unroll
                for (int ks = T < 3 ? 4 : 0; ks < 8; ks++) wg_ss16(y[T], da + (T * 8 + ks) * 128, db + ks * 16, ks > 0);
                wg_commit();
            }
            if (V_EARLY) nbar_arrive(NB_WO, 256);
            if (!WO_R8) z.red(pm + o8, ps + o8);
            wg_wait_acc<1, 8>(y[0]); acc_ready<8>(y[1]); acc_ready<8>(y[2]);
#pragma unroll
            for (int T = 0; T < 3; T++) ArWords(y[T]).red(pm + T * 16 * AR_STR, ps + T * 16 * AR_STR);
            wg_wait_acc<0, 8>(y[3]);
            ArWords(y[3]).red(pm + 48 * AR_STR, ps + 48 * AR_STR);
            if (!V_EARLY) nbar_arrive(NB_WO, 256);
            TS(0, i, 7);
        }
    };
    auto either = [&](const int i) {
        if (__builtin_expect(USE_ONE == 2 || (USE_ONE && (i < LAG || i >= NSEG)), MAT != 2)) project(Bool<true>(), i);
        else project(Bool<false>(), i);
    };
    if (MAT != 2) {
#pragma unroll 1
        for (int i = 0; i < NSTEP; i++) {
            either(i);
            if (!USE_ONE || (USE_ONE == 1 && i >= LAG && i < NSEG)) mbar_arrive_warp(bars + EB_STEP * 8);
            step(i);
        }
    } else {
#pragma unroll 1
        for (int i = -1; i < NSTEP; i++) {
            if (i >= 0) step(i);
            if (i < NSTEP - 1) {
                either(i + 1);
                const bool one = USE_ONE == 2 || (USE_ONE && (i + 1 < LAG || i + 1 >= NSEG));
                [[maybe_unused]] const int n0 = ar_fetch<0, AR_SPLIT>(P, i, TID, bars + (EB_EMPTY + (one ? AR_VA1 : AR_VA)) * 8, bars + EB_MEMA * 8);
                [[maybe_unused]] const int n1 = ar_fetch<AR_SPLIT, 9>(P, i, tid, bars + EB_EMPTY * 8, bars + EB_MEM * 8);
            }
        }
    }
    if (MAT == 2) { if (V_FIRST == 36) nbar_sync(NB_S, 256); nbar_sync(NB_PV, 256); }
}

__device__ __forceinline__ void engine_helper(const Params& P) {
    const int lane = threadIdx.x & 31, hw = warp_in_group(), e = blockIdx.x, rank = e & 1;
    if (hw < 3) {
        constexpr uint64_t M0 = ss_mask(0), M1 = ss_mask(1), M2 = ss_mask(2);
        const uint64_t m = hw == 0 ? M0 : hw == 1 ? M1 : M2;
        const uint32_t ws = sb + (hw == 0 ? E_WQ : hw == 1 ? E_WK : E_WV), wr = sb + E_WO + (hw == 0 ? 0 : hw == 1 ? NRQ : NRQ + NRK) * 2048;
        if (lane == 0) mbar_expect(bars + EB_WL * 8, 36 * 2048);
        __syncwarp();
        for (int ks = lane; ks < 36; ks += 32) {
            const int s = __popcll(m & ((1ull << ks) - 1));
            tma_unit(((m >> ks) & 1) ? ws + s * 2048 : wr + (ks - s) * 2048, hw == 0 ? &P.tmWq : hw == 1 ? &P.tmWk : &P.tmWv, ks, e, bars + EB_WL * 8);
        }
    }
    if (hw == 1) {
        hold_back(WO_DELAY);
        for (int u = lane; u < 36; u += 32)
            asm volatile("cp.async.bulk.prefetch.tensor.2d.L2.global [%0, {%1,%2}];"
                         :: "l"(&P.tmWo), "r"((u < 32 ? rank * 4 + (u >> 3) : 8) * 64), "r"(((e >> 1) * 8 + (u < 32 ? u & 7 : rank * 4 + (u & 3))) * 16) : "memory");
    }
    __syncwarp();
    if (hw < 2) nbar_sync(NB_T, 448);
    if (lane == 0) TG(79, 3);
    if (hw == 0) {
        if (lane == 0) {
#pragma unroll 1
            for (int n = 0; n < NSTEP; n++) {
                const uint32_t par = (n & 1) ^ 1;
                uint32_t rdy;
                do { asm volatile("ld.acquire.cta.shared.u32 %0, [%1];" : "=r"(rdy) : "r"(sb + SM_XRDY) : "memory"); } while (rdy <= n && (__nanosleep(20), true));
                fence_async_glb();
                TG(n, 30);
                const uint8_t* src = g_x + n * XIMG;
#pragma unroll
                for (int j = 0; j < 6; j++) {
                    const int f = j == 0 ? 0 : j < 4 ? 2 * j + 1 : 14 - j, blk = f < 9 ? f : f - 9, bytes = j == 0 ? 24576 : j < 4 ? 16384 : 8192;
                    if (j == 3 || j == 5) mbar_wait(bars + (j == 3 ? EB_V0 : EB_EMPTY + 1) * 8, par ^ 1);
                    else mbar_wait(bars + (j == 0 ? EB_STEP : j == 1 ? EB_QF : j == 2 ? EB_KF : EB_OFREE) * 8, par);
                    const uint32_t fb = bars + (EB_FULL + j) * 8;
                    mbar_expect(fb, bytes);
                    bulk_g2s(sb + x_slot(f), src + blk * 8192, bytes, fb);
                }
            }
        }
    } else if (hw == 1) {
        if (lane == 0) mbar_expect(bars + EB_WO * 8, 36 * 2048);
        __syncwarp();
        for (int u = lane; u < 36; u += 32)
            tma_unit(sb + E_WO + u * 2048, &P.tmWo, (e >> 1) * 8 + ((u & 7) ^ (rank * 4)), u < 32 ? rank * 4 + (u >> 3) : 8, bars + EB_WO * 8);
        __syncwarp();
        if (lane == 0) {
#pragma unroll 1
            for (int i = 0; i < NSTEP; i++) {
                mbar_wait(bars + EB_STEP * 8, i & 1);
                mbar_arrive_remote(mapa(sb, rank ^ 1) + SM_BAR + EB_PRDY * 8);
                mbar_wait(bars + EB_OST * 8, i & 1);
                fence_async_smem();
                bulk_s2g(g_o + (i & (RING - 1)) * O_BYTES + e * 8192, sb + E_R1, 8192);
                asm volatile("cp.async.bulk.commit_group;" ::: "memory");
                asm volatile("cp.async.bulk.wait_group.read 0;" ::: "memory");
                mbar_arrive(bars + EB_OFREE * 8);
                asm volatile("cp.async.bulk.wait_group 0;" ::: "memory");
                publish(F_O, i);
                TG(i, 31);
            }
        }
    } else if (hw == 2) {
        const int idx = e * 23 + lane, line = idx >> 3;
        uint8_t* z = g_ar + (line < 144 ? line * AR_STR : (line - 144) * (4 * AR_STR) + AR_STR / 2) + (idx & 7) * 16;
        if (lane < 23 && idx < 1440) { stg128(z, make_uint4(0, 0, 0, 0)); stg128(z + AR_SLOT, make_uint4(0, 0, 0, 0)); }
        __syncwarp();
        if (lane == 0) {
            publish(F_X0, B_ZERO);
            mbar_arrive(bars + EB_MEM * 8);
            flag_wait(F_X0, B_ZERO, NENG * this_launch());
            mbar_arrive(bars + EB_WO * 8);
            TG(79, 5);
        }
        __syncwarp();
#pragma unroll 1
        for (int i = 0; i < NSTEP; i++) {
            mbar_wait(bars + EB_MEM * 8, i & 1);
            if (lane < 3) mbar_expect(bars + (EB_SM + lane) * 8, lane == 0 ? 2560 : lane == 1 ? (SX_BF16 ? 3840 : 7168) : 2048);
            if (lane < 23 && idx < 1440) stg128(z + ((i + 2) & 3) * AR_SLOT, make_uint4(0, 0, 0, 0));
            __syncwarp();
            if (lane == 0) { fence_gpu(); mbar_arrive(bars + EB_MEM * 8); }
            __syncwarp();
        }
    } else {
        for (int j = lane; j < 72; j += 32) asm volatile("prefetch.global.L2 [%0];" :: "l"(P.mem0 + j * 64));
        const uint32_t ep = this_launch(), t0 = timer_lo();
        if (lane == 0) {
#pragma unroll 1
            for (int n = 0; n < NSTEP; n++) {
                while ((n < NSEG && !flag_up(F_X0, n, 16 * ep)) || (n >= LAG && !flag_up(F_X1, n - LAG, 16 * ep))) {
                    __nanosleep(20);
                    if (timer_lo() - t0 > TIME_LIMIT) break;
                }
                fence_acq_gpu();
                asm volatile("st.release.cta.shared.u32 [%0], %1;" :: "r"(sb + SM_XRDY), "r"(n + 1) : "memory");
            }
        }
    }
    __syncwarp();
}

__device__ __forceinline__ void f1_fetch(const Params& P, uint32_t dst, int f0, int ks0, int n) {
    const int tid = threadIdx.x & 127, r = tid >> 3, c = (tid & 3) * 2 + ((tid >> 2) & 1);
    const bf16* src = ((c & 1) ? P.w3 : P.w1) + (size_t)(ks0 * 16 + r) * FF + f0 + (c >> 1) * 8;
    dst += r * 128 + ((c ^ (r & 7)) << 4);
#pragma unroll 1
    for (int u = 0; u < n; u++) {
        asm volatile("cp.async.cg.shared.global [%0], [%1], 16;" :: "r"(dst + u * 2048), "l"(src + (size_t)u * 16 * FF) : "memory");
        asm volatile("cp.async.commit_group; cp.async.wait_group %0;" :: "n"(F1_DEPTH) : "memory");
    }
}
constexpr int R_BACKLOG = 6;
static_assert(R_BACKLOG <= RING, "the partial sums would be overwritten");
#define F1_LEAD 0
template <int a, bool second>
__device__ __forceinline__ void f1_tile(const uint32_t (&w)[NRF][4], uint32_t ws, int b) {
    constexpr bool RF = (a == 1) == second;
    const uint32_t par = b & 1;
    float d[32];
    const uint64_t da = mkdesc(ws, 1024, 1024, 1), db = mkdesc(F_X, 16, 1024, 1);
#pragma unroll
    for (int blk = 0; blk < 9; blk++) {
        if (a == 1 && !second && blk == 0 && F1_LEAD) nbar_sync(NB_QK, 256);
        const bool wt = blk == 0 || (!second && (a == 0 || blk >= F1_LEAD));
        if (wt) { mbar_wait(bars + (FB_FULL + blk) * 8, par); wg_fence(); }
#pragma unroll
        for (int j = 0; j < 4; j++) {
            const int ks = blk * 4 + j;
            if (RF && ks < NRF) wg_rs64<0>(d, w[ks < NRF ? ks : 0], db + blk * 512 + j * 2, ks > 0);
            else wg_ss64<0>(d, da + (RF ? ks - NRF : 36 - NRF + ks) * 128, db + blk * 512 + j * 2, ks > 0);
        }
        wg_commit();
        if (a == 0 && !second && blk + 1 == F1_LEAD) nbar_arrive(NB_QK, 256);
        if (blk > 0 && second) { wg_wait<1>(); mbar_arrive_warp(bars + (FB_EMPTY + blk - 1) * 8); }
    }
    const int tid = fresh_tid(), g = (tid & 31) >> 2;
    uint8_t* dst = g_h + (b & (RING - 1)) * H_BYTES + ((fresh_bid() - NENG + (second ? 37 : 0)) * 64 + a * 32 + ((tid >> 5) & 3) * 8 + g) * 128;
    if (!second) mbar_wait(bars + FB_RACK * 8, par ^ 1);
    wg_wait_acc<0, 32>(d);
    if (second) mbar_arrive_warp(bars + (FB_EMPTY + 8) * 8);
    uint32_t h[8];
#pragma unroll
    for (int j = 0; j < 8; j++) {
        const float g0 = d[4 * j], g1 = d[4 * j + 1];
        const float e0 = 1.f + ex2(fminf(-LOG2E * g0, 60.f)), e1 = 1.f + ex2(fminf(-LOG2E * g1, 60.f));
        const float r = rcp(e0 * e1);
        h[j] = pack2(g0 * d[4 * j + 2] * (e1 * r), g1 * d[4 * j + 3] * (e0 * r));
    }
    stg128(dst + (((tid & 3) ^ g) << 4), make_uint4(h[0], h[1], h[2], h[3]));
    stg128(dst + ((((tid & 3) + 4) ^ g) << 4), make_uint4(h[4], h[5], h[6], h[7]));
    mbar_arrive_warp(bars + (second ? FB_H2 : FB_H) * 8);
}
template <int a>
__device__ __forceinline__ void f1_main(const Params& P) {
    constexpr uint32_t ws = F_W + a * (72 - NRF) * 2048;
    const int f0 = (blockIdx.x - NENG) * 128 + a * 96;
    uint32_t w[NRF][4];
    hold_back(F1_DELAY);
    f1_fetch(P, sb + ws, f0, 0, NRF);
    asm volatile("cp.async.wait_all;" ::: "memory");
    nbar_sync(NB_G + a, 128);
    {
        const uint32_t fa = sb + ws + unit_frag_addr(threadIdx.x);
#pragma unroll
        for (int u = 0; u < NRF; u++) ldsm4t(w[u], fa + u * 2048);
    }
    nbar_sync(NB_G + a, 128);
    f1_fetch(P, sb + ws, f0, NRF, 36 - NRF);
    f1_fetch(P, sb + ws + (36 - NRF) * 2048, f0 + (a ? -64 : 64), 0, 36);
    asm volatile("cp.async.wait_all;" ::: "memory");
    fence_async_smem();
    nbar_sync(NB_G + a, 128);
    if (threadIdx.x == 0) TG(79, 2);
#pragma unroll 1
    for (int b = 0; b < NSTEP; b++) {
        f1_tile<a, false>(w, ws, b);
        f1_tile<a, true>(w, ws, b);
    }
}
__device__ __forceinline__ uint32_t n_pairs(int b) { return (b < NSEG ? 16 : 0) + (b >= LAG ? 16 : 0); }
__device__ __forceinline__ void publisher(uint32_t done, uint32_t ack, int stage) {
#pragma unroll 1
    for (int b = 0; b < NSTEP; b++) {
        if (stage == F_H2) { mbar_wait(done - 8, b & 1); publish(F_H, b); }
        mbar_wait(done, b & 1);
        mbar_arrive(ack);
        TG(b, 30);
        publish(stage, b);
        TG(b, 31);
    }
}
__device__ __forceinline__ void f1_helper(const Params& P) {
    const int hw = warp_in_group();
    if ((threadIdx.x & 31) == 0) {
        const bool chain = blockIdx.x >= NENG + 16;
        if (hw == 0) {
            const uint32_t ep = this_launch();
#pragma unroll 1
            for (int b = 0; b < NSTEP; b++) {
                flag_wait(F_XF, b, n_pairs(b) * ep);
                TG(b, 29);
                const uint8_t* src = g_xf + (b & (RING - 1)) * (9 * 8192);
#pragma unroll 1
                for (int blk = 0; blk < 9; blk++) {
                    mbar_wait(bars + (FB_EMPTY + blk) * 8, (b & 1) ^ 1);
                    mbar_expect(bars + (FB_FULL + blk) * 8, 8192);
                    bulk_g2s(sb + F_X + blk * 8192, src + blk * 8192, 8192, bars + (FB_FULL + blk) * 8);
                }
            }
        } else if (hw == 1) {
            const uint32_t ep = this_launch();
            int b1 = chain ? LAG : 0, b2 = b1;
            const int bend = b1 + NSEG;
            bool second = true;
#pragma unroll 1
            for (int j = blockIdx.x < NENG + 32 ? 0 : 2 * NSEG; j < 2 * NSEG; j++) {
                [[maybe_unused]] int n = 0;
                const bool may1 = b1 < bend && b1 < b2 + R_BACKLOG;
                bool may2 = !chain || !second || !may1, any;
                do {
                    const bool r1 = flag_up(F_P1, b1, 15 * ep) & may1, r2 = flag_up(F_P2, b2, 17 * ep) & may2;
                    second = chain ? !r1 : r2;
                    any = r1 | r2;
                    may2 = !chain || !may1;
                    SPIN_CHECK(n, 20);
                } while (!any);
                fence_acq_gpu();
                TG(second ? b2 : b1, 25 + 2 * second);
                sts32(sb + F_RED + 192 + (j & 1) * 4, second ? b2 + 256 : b1);
                mbar_arrive(bars + FB_JOB * 8);
                if (second) b2++; else b1++;
                mbar_wait(bars + FB_JOB * 8, j & 1);
            }
        } else if (hw == 2) {
#pragma unroll 1
            for (int j = blockIdx.x < NENG + 32 ? 0 : 2 * NSEG; j < 2 * NSEG; j++) {
                if (j == 0) mbar_arrive(bars + FB_JOB * 8);
                mbar_wait(bars + FB_RDONE * 8, j & 1);
                const int job = lds32(sb + F_RED + 192 + (j & 1) * 4);
                mbar_arrive(bars + FB_JOB * 8);
                TG(job & 255, 23 + (job >> 8));
                if (job < 256 || !chain) publish(job < 256 ? F_XF : F_X1, job & 255);
                TG(job & 255, 26 + 2 * (job >> 8));
            }
        } else {
            hold_back(PF_DELAY);
#pragma unroll 1
            for (int j = 0; j < 24; j++) {
                const bf16* w = j >= 16 ? P.w2 : (j & 1) ? P.w3 : P.w1;
                asm volatile("cp.async.bulk.prefetch.L2.global [%0], %1;" :: "l"(w + (size_t)((j >= 16 ? j - 16 : j >> 1) * NF1 + blockIdx.x - NENG) * (2 * FF)), "r"(4 * FF) : "memory");
                hold_back(PF_PACE);
            }
            publisher(bars + FB_H2 * 8, bars + FB_RACK * 8, F_H2);
        }
    }
    __syncwarp();
}

__device__ __forceinline__ void add8(float* f, uint4 a) {
    f[0] += bf_lo(a.x); f[1] += bf_hi(a.x); f[2] += bf_lo(a.y); f[3] += bf_hi(a.y);
    f[4] += bf_lo(a.z); f[5] += bf_hi(a.z); f[6] += bf_lo(a.w); f[7] += bf_hi(a.w);
}
__device__ __forceinline__ void set8(float* f, uint4 a) {
    f[0] = bf_lo(a.x); f[1] = bf_hi(a.x); f[2] = bf_lo(a.y); f[3] = bf_hi(a.y);
    f[4] = bf_lo(a.z); f[5] = bf_hi(a.z); f[6] = bf_lo(a.w); f[7] = bf_hi(a.w);
}
__device__ __forceinline__ void ln0_rows(const Params& P, int r) {
    const int lane = threadIdx.x & 31, l = lane < 24 ? lane : 0;
    const uint4* xrow = (const uint4*)(P.x + r * DM) + l;
    uint4 xw[3];
#pragma unroll
    for (int k = 0; k < 3; k++) xw[k] = __ldg(xrow + 24 * k);
    asm volatile("prefetch.global.L2 [%0];" :: "l"(P.x + (r + 16) * DM + (lane < 9 ? lane : 0) * 64));
#pragma unroll 1
    for (int seg = 0; seg < NSEG; seg++) {
#pragma unroll 1
        for (int h = 0; h < 2; h++) {
            float f[24];
#pragma unroll
            for (int k = 0; k < 3; k++) set8(&f[k * 8], xw[k]);
            if (2 * seg + h + 1 < 2 * NSEG) {
#pragma unroll
                for (int k = 0; k < 3; k++) xw[k] = __ldg(xrow + (2 * seg + h + 1) * (16 * DM / 8) + 24 * k);
            }
            float s = 0.f, q = 0.f;
#pragma unroll
            for (int j = 0; j < 24; j++) s += f[j];
            if (lane >= 24) s = 0.f;
#pragma unroll
            for (int o = 16; o; o >>= 1) s += __shfl_xor_sync(~0u, s, o);
            const float mean = s * (1.f / DM);
#pragma unroll
            for (int j = 0; j < 24; j++) { f[j] -= mean; q += f[j] * f[j]; }
            if (lane >= 24) q = 0.f;
#pragma unroll
            for (int o = 16; o; o >>= 1) q += __shfl_xor_sync(~0u, q, o);
            const float rstd = rsqrtf(q * (1.f / DM) + 1e-5f);
            if (lane < 24) {
                uint8_t* d = g_x + seg * XIMG + (l >> 3) * 8192 + (r + 16 * h) * 128 + (((l & 7) ^ (r & 7)) << 4);
#pragma unroll
                for (int k = 0; k < 3; k++) {
                    const float* y = &f[8 * k];
                    stg128(d + k * 24576, make_uint4(pack2(y[0] * rstd, y[1] * rstd), pack2(y[2] * rstd, y[3] * rstd), pack2(y[4] * rstd, y[5] * rstd), pack2(y[6] * rstd, y[7] * rstd)));
                }
            }
        }
        __syncwarp();
        if (lane == 0 && seg == 0) TG(79, 4);
        if (lane == 0) publish(F_X0, seg);
        if (lane == 0 && seg == 0) TG(79, 5);
        __syncwarp();
    }
}

template <bool SECOND, bool CHAIN>
__device__ __forceinline__ void reduce_job(const Params& P, int b, int p, int t) {
    constexpr int NP = SECOND ? NP2 : NP1;
    const int seg = CHAIN ? b - LAG : b, lane = t & 31;
    const bool act = !(t & 1);
    const uint32_t ro = (b & (RING - 1)), po = p * (DM * 4) + t * 16, so = 2048 - t * 16 + (t >> 1) * 4;
    const int fa = (t >> 2) * 16 + (t & 3) * 2, fs = 512 + (t >> 5) * 16 + ((t >> 2) & 7) + (t & 2) * 4;
    const uint32_t row = (seg * 32 + (p & 15) * 2) * DM;
    uint8_t* const r1 = g_r1 + ro * PART + po;
    uint8_t* const r2 = g_r2 + seg * (PART / 2) + po - (CHAIN ? PART / 2 : 0);
    float f[10];
    uint4 x;
    uint32_t y;
    {
        const uint8_t* src = (SECOND ? g_p2 : g_p1) + ro * (NP * PART) + po;
        uint4 a[NP];
        uint32_t c[NP];
#pragma unroll
        for (int k = 0; k < NP; k++) { a[k] = ld_rlx128(src + k * PART); c[k] = ld_rlx(src + so + k * PART); }
        if (SECOND || CHAIN) {
            x = ld_rlx128(SECOND ? r1 : r2); y = ld_rlx((SECOND ? r1 : r2) + so);
        } else {
            const bf16* xr = P.x + row;
            const uint32_t a0 = ld_rlx(xr + fa), b0 = ld_rlx(xr + fa + 8), a1 = ld_rlx(xr + fa + DM), b1 = ld_rlx(xr + fa + DM + 8);
            const uint32_t s0 = ld_rlx(xr + (fs & ~1)), s1 = ld_rlx(xr + (fs & ~1) + DM);
            x = make_uint4(__byte_perm(a0, a1, 0x5410), __byte_perm(b0, b1, 0x5410), __byte_perm(a0, a1, 0x7632), __byte_perm(b0, b1, 0x7632));
            y = __byte_perm(s0, s1, (fs & 1) ? 0x7632 : 0x5410);
        }
        set8(f, a[0]); f[8] = bf_lo(c[0]); f[9] = bf_hi(c[0]);
#pragma unroll
        for (int k = 1; k < NP; k++) { add8(f, a[k]); f[8] += bf_lo(c[k]); f[9] += bf_hi(c[k]); }
    }
    add8(f, x);
    x = make_uint4(pack2(f[0], f[1]), pack2(f[2], f[3]), pack2(f[4], f[5]), pack2(f[6], f[7]));
    y = pack2(f[8] + bf_lo(y), f[9] + bf_hi(y));
    if (SECOND && CHAIN) {
        bf16* o = P.out + row;
        stg32(o + fa, __byte_perm(x.x, x.z, 0x5410));
        stg32(o + fa + 8, __byte_perm(x.y, x.w, 0x5410));
        stg32(o + fa + DM, __byte_perm(x.x, x.z, 0x7632));
        stg32(o + fa + DM + 8, __byte_perm(x.y, x.w, 0x7632));
        stg16(o + fs + (act ? 0 : DM), act ? y : y >> 16);
        return;
    }
    set8(f, x);
    f[8] = act ? bf_lo(y) : 0.f; f[9] = act ? 0.f : bf_hi(y);
    float st[4];
    st[0] = (f[0] + f[2]) + (f[4] + f[6]) + f[8]; st[2] = (f[0] * f[0] + f[2] * f[2]) + (f[4] * f[4] + f[6] * f[6]) + f[8] * f[8];
    st[1] = (f[1] + f[3]) + (f[5] + f[7]) + f[9]; st[3] = (f[1] * f[1] + f[3] * f[3]) + (f[5] * f[5] + f[7] * f[7]) + f[9] * f[9];
    {
        const bool u = lane & 1, v = lane & 2;
        st[0] = (u ? st[1] : st[0]) + __shfl_xor_sync(~0u, u ? st[0] : st[1], 1);
        st[2] = (u ? st[3] : st[2]) + __shfl_xor_sync(~0u, u ? st[2] : st[3], 1);
        st[0] = (v ? st[2] : st[0]) + __shfl_xor_sync(~0u, v ? st[0] : st[2], 2);
        st[0] = (st[0] + __shfl_xor_sync(~0u, st[0], 4)) + (__shfl_xor_sync(~0u, st[0], 8) + __shfl_xor_sync(~0u, st[0], 12));
        if (!(lane & 12)) sts32(sb + F_RED + (t >> 4) * 16 + (lane & 3) * 4, fu(st[0]));
    }
    nbar_sync(NB_R, 128);
#pragma unroll
    for (int k = 0; k < 8; k++) {
        const uint4 q = lds128(sb + F_RED + k * 16);
        if (k == 0) { st[0] = uf(q.x); st[1] = uf(q.y); st[2] = uf(q.z); st[3] = uf(q.w); }
        else { st[0] += uf(q.x); st[1] += uf(q.y); st[2] += uf(q.z); st[3] += uf(q.w); }
    }
    stg128(SECOND ? r2 : r1, x);
    if (act) stg32((SECOND ? r2 : r1) + so, y);
    const float m0 = st[0] * (1.f / DM), m1 = st[1] * (1.f / DM);
    const float q0 = rsqrtf(fmaxf(st[2] * (1.f / DM) - m0 * m0, 0.f) + 1e-5f), q1 = rsqrtf(fmaxf(st[3] * (1.f / DM) - m1 * m1, 0.f) + 1e-5f);
    constexpr int KB = 8192;
    uint8_t* d = (SECOND ? g_x + (b + LAG) * XIMG + (USE_ONE && b + LAG >= NSEG ? 0 : 4096) : g_xf + ro * XIMG) + p * 256;
#pragma unroll
    for (int e = 0; e < 2; e++) {
        const float m = e ? m1 : m0, q = e ? q1 : q0;
#pragma unroll
        for (int h = 0; h < 2; h++)
            stg32(d + (fa >> 6) * KB + (t & 3) * 4 + e * 128 + (((((fa >> 3) & 6) + h) ^ ((2 * p + e) & 7)) << 4), pack2((f[2 * h + e] - m) * q, (f[4 + 2 * h + e] - m) * q));
    }
    stg16(d + 8 * KB + (t & 1) * 128 + ((((fs >> 3) & 7) ^ ((2 * p + (t & 1)) & 7)) << 4) + (fs & 7) * 2, pack2(act ? (f[8] - m0) * q0 : (f[9] - m1) * q1, 0.f));
}
template <bool CHAIN>
__device__ __forceinline__ void reducer(const Params& P) {
#pragma unroll 1
    for (int j = 0; j < 2 * NSEG; j++) {
        const int t = fresh_tid() - 256, p = fresh_bid() - NENG;
        mbar_wait(bars + FB_JOB * 8, j & 1);
        const int job = lds32(sb + F_RED + 192 + (j & 1) * 4);
        if (job >= 256) reduce_job<true, CHAIN>(P, job - 256, p, t);
        else reduce_job<false, CHAIN>(P, job, p, t);
        mbar_arrive_warp(bars + FB_RDONE * 8);
    }
}

__host__ __device__ constexpr int d_rf(int u) { return u < 48 ? ((u & 3) < 2 ? (u >> 2) * 2 + (u & 1) : -1) : u == 48 ? 24 : -1; }
__host__ __device__ constexpr int d_ss(int u) { return u < 48 ? (u >> 2) * 2 + (u & 1) : u - 25; }
template <bool WIDE, int wg>
__device__ __forceinline__ void d_main() {
    constexpr int NR = WIDE ? 24 : NRD;
    uint32_t w[NR][4];
    {
        const uint32_t fa = sb + wg * (NRD * 2048) + unit_frag_addr(threadIdx.x);
        mbar_wait(bars + DB_WL * 8, 0);
#pragma unroll
        for (int u = 0; u < NR; u++) ldsm4t(w[u], fa + u * 2048);
        nbar_arrive(NB_W, 416);
        mbar_wait(bars + DB_WL * 8, 1);
        if (threadIdx.x == 0) TG(79, 2);
    }
    const uint64_t da = mkdesc(wg * ((52 - NRD) * 2048), 1024, 1024, 1);
#pragma unroll 1
    for (int b = 0; b < NSTEP; b++) {
#pragma unroll
        for (int T = 0; T < (WIDE ? 3 : 1); T++) {
            float d[32];
            constexpr int NB = WIDE ? 4 : 13;
#pragma unroll
            for (int blk = 0; blk < NB; blk++) {
                const int c = blk;
                if (T == 0 || blk == 0) mbar_wait(bars + (DB_FULL + (c & 7)) * 8, WIDE || (c & 7) >= 5 ? b & 1 : c >> 3);
                if (T == 0 || blk == 0) wg_fence();
                const uint64_t db = mkdesc(D_B + (c & 7) * 8192, 8192, 1024, 1);
#pragma unroll
                for (int j = 0; j < 4; j++) {
                    const int u = T * 16 + blk * 4 + j;
                    if (d_rf(u) >= 0) wg_rs64<1>(d, w[d_rf(u) >= 0 ? d_rf(u) : 0], db + j * 128, blk + j > 0);
                    else wg_ss64<1>(d, da + d_ss(u) * 128, db + j * 128, blk + j > 0);
                }
                wg_commit();
                if (!WIDE && blk > 0) { wg_wait<1>(); mbar_arrive_warp(bars + (DB_EMPTY + ((c - 1) & 7)) * 8); }
            }
            const int tid = fresh_tid(), t = tid & 3, ds = fresh_bid() - NENG - NF1;
            const bool w2 = ds >= 15;
            const int tile = WIDE ? wg * 3 + T : (ds % 3) * 3 + wg;
            uint8_t* dst = (w2 ? g_p2 + ((b & (RING - 1)) * NP2 + (WIDE ? ds - 25 : (ds - 15) / 3)) * PART : g_p1 + ((b & (RING - 1)) * NP1 + ds / 3) * PART)
                         + (tile * 64 + ((tid >> 5) & 3) * 16 + ((tid & 31) >> 2) * 2) * 4 + (w2 ? 4 * t : t) * (DM * 4);
            const uint32_t js = w2 ? DM * 4 : DM * 16;
            if (T == 0) mbar_wait(bars + (DB_P + 1) * 8, (b & 1) ^ 1);
            wg_wait_acc<0, 32>(d);
            if (!WIDE) mbar_arrive_warp(bars + (DB_EMPTY + ((NB - 1) & 7)) * 8);
            else if (T == 2) {
#pragma unroll
                for (int blk = 0; blk < 4; blk++) mbar_arrive_warp(bars + (DB_EMPTY + blk) * 8);
            }
#pragma unroll
            for (int j = 0; j < 8; j++) stg64(dst + (j >> 2) * (DM * 64) + (j & 3) * js, pack2(d[4 * j], d[4 * j + 1]), pack2(d[4 * j + 2], d[4 * j + 3]));
        }
        mbar_arrive_warp(bars + DB_P * 8);
    }
}
__device__ __forceinline__ void d_helper(const Params& P, int ds) {
    const int lane = threadIdx.x & 31, hw = warp_in_group();
    const bool w2 = ds >= 15, wide = ds >= 30;
    const int kr = (w2 ? ds - 15 : ds) / 3, nb = wide ? 4 : 13;
    const int blk0 = wide ? 29 + (ds - 30) * 4 : kr * (w2 ? 6 : 13), n1 = w2 ? (kr == 4 ? 5 : 6) : 13, blk1 = 37 + kr * 7 - n1;
    if (hw == 0) {
        const int nu = wide ? 48 : 52;
        hold_back(w2 ? W2_DELAY : D_DELAY);
#pragma unroll 1
        for (int ph = 0; ph < 2; ph++) {
            if (ph) nbar_sync(NB_W, 416);
            if (lane == 0) mbar_expect(bars + DB_WL * 8, (wide ? 72 : ph ? 3 * (52 - NRD) : 3 * NRD) * 2048);
            __syncwarp();
#pragma unroll 1
            for (int x = lane; x < 3 * nu; x += 32) {
                const int wg = x / nu, u = x - wg * nu, j = (wide ? u & 15 : u) >> 2;
                const int kb = !w2 ? blk0 + j : j < n1 ? (blk0 + j) * 2 : (blk1 + j - 37) * 2 + 1;
                if ((d_rf(u) < 0) == (ph != 0))
                    tma_unit(sb + (ph ? wg * (52 - NRD) + d_ss(u) : wg * NRD + d_rf(u)) * 2048, w2 ? &P.tmW2 : &P.tmWo,
                             kb * 4 + (u & 3), wide ? wg * 3 + (u >> 4) : (ds % 3) * 3 + wg, bars + DB_WL * 8);
            }
        }
        __syncwarp();
        if (lane == 0) {
            const uint32_t target = (w2 ? NF1 : NENG) * this_launch();
#pragma unroll 1
            for (int b = 0; b < NSTEP; b++) {
                flag_wait(w2 ? F_H : F_O, b, target);
                TG(b, 29);
                const uint8_t* src = (w2 ? g_h + (b & (RING - 1)) * H_BYTES : g_o + (b & (RING - 1)) * O_BYTES);
#pragma unroll 1
                for (int blk = 0; blk < nb; blk++) {
                    const int c = blk;
                    if (blk == n1) flag_wait(F_H2, b, target);
                    mbar_wait(bars + (DB_EMPTY + (c & 7)) * 8, (wide || (c & 7) >= 5 ? b & 1 : c >> 3) ^ 1);
                    mbar_expect(bars + (DB_FULL + (c & 7)) * 8, 8192);
                    bulk_g2s(sb + D_B + (c & 7) * 8192, src + (blk + (blk < n1 ? blk0 : blk1)) * 8192, 8192, bars + (DB_FULL + (c & 7)) * 8);
                }
            }
        }
    } else if (hw == 1 && lane == 0) {
        publisher(bars + DB_P * 8, bars + (DB_P + 1) * 8, w2 ? F_P2 : F_P1);
    }
    __syncwarp();
}

__device__ __forceinline__ void sign_off() { mbar_arrive_warp(sb + SM_DONE); }
__device__ __forceinline__ void sign_off_helper() {
    if (warp_in_group() < 3) { sign_off(); return; }
    uint32_t ok;
    const uint32_t t0 = timer_lo(), ep = this_launch();
    do {
        __nanosleep(100);
        asm volatile("{.reg .pred p; mbarrier.test_wait.parity.shared::cta.b64 p, [%1], 0; selp.u32 %0, 1, 0, p;}" : "=r"(ok) : "r"(sb + SM_DONE) : "memory");
    } while (!ok && timer_lo() - t0 < TIME_LIMIT);
    if (!ok || (sb & 0x3ffff) != SM_ORG) __trap();
    if (fresh_tid() == NTHREADS - 32) { g_epoch[fresh_bid()][0] = ep; TG(79, 1); }
    __syncwarp();
}

__global__ void __cluster_dims__(2, 1, 1) __launch_bounds__(NTHREADS, 1) fused_kernel(const __grid_constant__ Params P) {
    const int wg = __shfl_sync(~0u, threadIdx.x >> 7, 0);
    const int bid = blockIdx.x;
    if (threadIdx.x >= NTHREADS - 32) sts32(sb + SM_ONES + (threadIdx.x & 31) * 4, 0x3f803f80u);
    if (threadIdx.x == 0) {
        TG(79, 0);
        mbar_init(sb + SM_DONE, 15);
        sts32(sb + SM_XRDY, 0);
        if (bid < NENG) {
            for (int i = 0; i < 9; i++) mbar_init(bars + (EB_FULL + i) * 8, i < 6 ? 1 : 12);
            mbar_init(bars + EB_V0 * 8, 4); mbar_init(bars + EB_WL * 8, 3); mbar_init(bars + EB_WO * 8, 2); mbar_init(bars + EB_STEP * 8, 8);
            mbar_init(bars + EB_SM * 8, 1); mbar_init(bars + EB_SX * 8, 1); mbar_init(bars + EB_OX * 8, 1);
            mbar_init(bars + EB_QF * 8, 4); mbar_init(bars + EB_KF * 8, 8); mbar_init(bars + EB_CONS * 8, 4); mbar_init(bars + EB_OST * 8, 4);
            mbar_init(bars + EB_OFREE * 8, 1); mbar_init(bars + EB_MEMA * 8, 4); mbar_init(bars + EB_MEM * 8, 5); mbar_init(bars + EB_PRDY * 8, 1);
        } else if (bid < NENG + NF1) {
            for (int i = 0; i < 9; i++) { mbar_init(bars + (FB_FULL + i) * 8, 1); mbar_init(bars + (FB_EMPTY + i) * 8, 8); }
            mbar_init(bars + FB_H * 8, 8); mbar_init(bars + FB_H2 * 8, 8); mbar_init(bars + FB_RACK * 8, 1); mbar_init(bars + FB_JOB * 8, 2); mbar_init(bars + FB_RDONE * 8, 4);
        } else {
            for (int i = 0; i < 8; i++) { mbar_init(bars + (DB_FULL + i) * 8, 1); mbar_init(bars + (DB_EMPTY + i) * 8, 12); }
            mbar_init(bars + DB_WL * 8, 1); mbar_init(bars + DB_P * 8, 12); mbar_init(bars + (DB_P + 1) * 8, 1);
        }
        asm volatile("fence.mbarrier_init.release.cluster;" ::: "memory");
    }
    __syncthreads();
    asm volatile("barrier.cluster.arrive.relaxed.aligned; barrier.cluster.wait.aligned;" ::: "memory");
    if (bid < NENG) {
        if (wg == 0) { reg_inc<REGQ>(); engine_main<0>(P); sign_off(); cluster_sync_all(); }
        else if (wg == 1) { reg_inc<REGK>(); engine_main<1>(P); sign_off(); cluster_sync_all(); }
        else if (wg == 2) { reg_inc<REGV>(); engine_main<2>(P); sign_off(); cluster_sync_all(); }
        else { reg_dec<24>(); engine_helper(P); sign_off_helper(); cluster_sync_all(); }
    } else if (bid < NENG + NF1) {
        if (wg < 2) {
            reg_inc<REGF>();
            if (wg == 0) f1_main<0>(P); else f1_main<1>(P);
            sign_off();
        } else if (wg == 2) {
            reg_dec<488 - 2 * REGF>();
            if (bid >= NENG + 32) ln0_rows(P, (bid - NENG - 32) * 4 + warp_in_group());
            else if (bid < NENG + 16) reducer<false>(P);
            else reducer<true>(P);
            sign_off();
        } else {
            reg_dec<24>();
            f1_helper(P);
            sign_off_helper();
        }
    } else {
        const int ds = bid - NENG - NF1;
        if (wg < 3) {
            reg_inc<160>();
            if (ds < 30) { if (wg == 0) d_main<false, 0>(); else if (wg == 1) d_main<false, 1>(); else d_main<false, 2>(); }
            else { if (wg == 0) d_main<true, 0>(); else if (wg == 1) d_main<true, 1>(); else d_main<true, 2>(); }
            sign_off();
        } else {
            reg_dec<32>();
            d_helper(P, ds);
            sign_off_helper();
        }
    }
}

typedef CUresult (*EncodeFn)(CUtensorMap*, CUtensorMapDataType, cuuint32_t, void*, const cuuint64_t*, const cuuint64_t*,
                             const cuuint32_t*, const cuuint32_t*, CUtensorMapInterleave, CUtensorMapSwizzle,
                             CUtensorMapL2promotion, CUtensorMapFloatOOBfill);

void make_map(EncodeFn enc, CUtensorMap* m, const void* p, int rows, int cols) {
    cuuint64_t dims[2] = {(cuuint64_t)cols, (cuuint64_t)rows};
    cuuint64_t strides[1] = {(cuuint64_t)cols * 2};
    cuuint32_t box[2] = {64, 16};
    cuuint32_t es[2] = {1, 1};
    enc(m, CU_TENSOR_MAP_DATA_TYPE_BFLOAT16, 2, (void*)p, dims, strides, box, es, CU_TENSOR_MAP_INTERLEAVE_NONE,
        CU_TENSOR_MAP_SWIZZLE_128B, CU_TENSOR_MAP_L2_PROMOTION_L2_128B, CU_TENSOR_MAP_FLOAT_OOB_FILL_NONE);
}

}

extern "C" void kernel_launch(void* const* d_in, const int* in_sizes, int n_in, void* d_out, int out_size) {
    (void)in_sizes; (void)n_in; (void)out_size;
    static EncodeFn enc = nullptr;
    if (!enc) {
        void* fn = nullptr;
        cudaDriverEntryPointQueryResult qr;
        cudaGetDriverEntryPoint("cuTensorMapEncodeTiled", &fn, cudaEnableDefault, &qr);
        enc = (EncodeFn)fn;
        cudaFuncSetAttribute(fused_kernel, cudaFuncAttributeMaxDynamicSharedMemorySize, SM_TOTAL);
    }
    Params P;
    make_map(enc, &P.tmWq, d_in[2], DM, 4096);
    make_map(enc, &P.tmWk, d_in[3], DM, 4096);
    make_map(enc, &P.tmWv, d_in[4], DM, 4096);
    make_map(enc, &P.tmWo, d_in[5], 4096, DM);
    make_map(enc, &P.tmW2, d_in[10], FF, DM);
    P.x = (const bf16*)d_in[0];
    P.mem0 = (const bf16*)d_in[1];
    P.w1 = (const bf16*)d_in[8];
    P.w3 = (const bf16*)d_in[9];
    P.w2 = (const bf16*)d_in[10];
    P.out = (bf16*)d_out;
    P.zero = 0;
    fused_kernel<<<NCTA, NTHREADS, SM_TOTAL>>>(P);
}
```

```cpp
#include <cuda_runtime.h>
#include <cuda_bf16.h>
#include <cuda.h>
#include <stdint.h>

typedef __nv_bfloat16 bf16;

namespace {

constexpr int DM = 576, FF = 4608, NSEG = 64;
constexpr int NENG = 64, NF1 = 36, ND = 32, NCTA = NENG + NF1 + ND;
constexpr int NTHREADS = 512;
#define LAG 8
#define RING 16
static_assert(RING > LAG, "ring too short");
#define USE_ONE 1
constexpr int NSTEP = NSEG + LAG;

enum { F_X0 = 0, F_X1, F_O, F_P1, F_XF, F_H, F_P2, F_H2, F_COUNT };
constexpr int B_ZERO = 95;
__device__ uint32_t g_flag[F_COUNT][96][8];
__device__ uint32_t g_epoch[NCTA][8];
constexpr int XIMG = 9 * 8192;
constexpr int O_BYTES = 65 * 8192;
constexpr int H_BYTES = 73 * 8192;
constexpr int PART = 32 * DM * 4;
constexpr int NP1 = 5, NP2 = 7;
__device__ __align__(1024) uint8_t g_x[NSTEP * XIMG];
__device__ __align__(1024) uint8_t g_xf[RING * XIMG];
__device__ __align__(1024) uint8_t g_o[RING * O_BYTES];
__device__ __align__(1024) uint8_t g_h[RING * H_BYTES];
__device__ __align__(1024) uint8_t g_p1[RING * NP1 * PART];
__device__ __align__(1024) uint8_t g_p2[RING * NP2 * PART];
__device__ __align__(1024) uint8_t g_r1[RING * PART];
__device__ __align__(1024) uint8_t g_r2[NSEG * PART / 2];
#define AR_STR 4352
constexpr int AR_SLOT = 144 * AR_STR;
__device__ __align__(1024) uint8_t g_ar[4 * AR_SLOT];

struct Params {
    CUtensorMap tmWq, tmWk, tmWv, tmWo, tmW2;
    const bf16 *x, *mem0, *w1, *w3, *w2;
    bf16* out;
    uint32_t zero;
};

constexpr uint32_t SM_ORG = 1024;
extern __shared__ __align__(1024) uint8_t smem_raw[];
#define sb ((uint32_t)__cvta_generic_to_shared(smem_raw))
#define bars (sb + SM_BAR)
constexpr int SM_BAR = 231936;
constexpr int SM_TOTAL = SM_BAR + 512;
#define NRQ 25
#define NRK 25
#define NRV 25
#define REGQ 160
#define REGK 168
#define REGV 160
constexpr int E_WQ = 0;
constexpr int E_WK = E_WQ + (36 - NRQ) * 2048;
constexpr int E_WV = E_WK + (36 - NRK) * 2048;
constexpr int E_WO = E_WV + (36 - NRV) * 2048;
constexpr int E_MEM = E_WO + 36 * 2048;
constexpr int E_R0 = E_MEM + 18432;
constexpr int E_R2 = E_R0 + 8192, E_R3 = E_R2 + 8192, E_R1 = E_R3 + 8192;
constexpr int E_SX = E_R1;
constexpr int E_QT = E_R1 + 8192;
constexpr int E_KT = E_QT + 8192;
constexpr int E_VT = E_KT + 10240;
constexpr int E_OM = E_VT + 10240;
constexpr int E_QM = E_OM + 4096;
constexpr int E_SR = E_QM + 2048;
constexpr int E_SL = E_SR + 2560;
constexpr int E_END = E_SL + 2048;
static_assert(E_END <= SM_BAR, "engine smem overflow");
static_assert(E_WO + (NRQ + NRK + NRV) * 2048 <= E_OM, "weight staging: the peer writes there without asking");
enum {
    EB_FULL = 0  , EB_EMPTY = 6  , EB_V0 = 9, EB_WL, EB_WO, EB_STEP, EB_SM, EB_SX, EB_OX,
    EB_QF, EB_KF, EB_CONS, EB_OST, EB_OFREE, EB_MEM0, EB_MEMA, EB_MEM, EB_PRDY
};
enum { NB_G = 1, NB_LEAD, NB_QK, NB_S, NB_OM, NB_W, NB_R, NB_T, NB_PV, NB_WO, NB_V, NB_KT, NB_S2, NB_VL };
constexpr int NB_VL2 = NB_LEAD;
#define REGF 208
constexpr int NRF = REGF == 200 ? 35 : 36;
constexpr int F_W = 0;
constexpr int F_X = 2 * (72 - NRF) * 2048;
constexpr int F_RED = F_X + 9 * 8192;
static_assert(F_RED + 512 <= SM_BAR, "F1 smem overflow");
enum { FB_FULL = 0, FB_EMPTY = 9, FB_H = 18, FB_H2, FB_RACK, FB_JOB, FB_RDONE };
constexpr int NRD = 25;
constexpr int D_B = 3 * (52 - NRD) * 2048;
static_assert(D_B + 8 * 8192 <= SM_BAR, "D smem overflow");
enum { DB_FULL = 0, DB_EMPTY = 8, DB_WL = 16, DB_P };
constexpr int SM_DONE = SM_BAR + 248, SM_XRDY = SM_BAR + 376, SM_ONES = SM_BAR + 384;
constexpr uint32_t TIME_LIMIT = 2000000000u;

#define SPIN_CHECK(n, code)

#define TS(thr, step, k)
#define TX(thr, k)
#define TG(step, k)
#define PROF_INC(n, k)

__device__ __forceinline__ uint32_t mapa(uint32_t a, uint32_t r) {
    uint32_t o; asm("mapa.shared::cluster.u32 %0, %1, %2;" : "=r"(o) : "r"(a), "r"(r)); return o;
}
__device__ __forceinline__ void mbar_init(uint32_t b, uint32_t cnt) {
    asm volatile("mbarrier.init.shared::cta.b64 [%0], %1;" :: "r"(b), "r"(cnt) : "memory");
}
__device__ __forceinline__ void mbar_arrive(uint32_t b) {
    asm volatile("mbarrier.arrive.shared::cta.b64 _, [%0];" :: "r"(b) : "memory");
}
__device__ __forceinline__ void mbar_arrive_warp(uint32_t b) {
    asm volatile("{.reg .pred p; bar.warp.sync -1; elect.sync _|p, -1; @p mbarrier.arrive.shared::cta.b64 _, [%0];}" :: "r"(b) : "memory");
}
__device__ __forceinline__ void mbar_arrive_remote(uint32_t b) {
    asm volatile("fence.release.sync_restrict::shared::cta.cluster; mbarrier.arrive.relaxed.cluster.shared::cluster.b64 _, [%0];" :: "r"(b) : "memory");
}
__device__ __forceinline__ void mbar_expect(uint32_t b, uint32_t bytes) {
    asm volatile("mbarrier.arrive.expect_tx.shared::cta.b64 _, [%0], %1;" :: "r"(b), "r"(bytes) : "memory");
}
__device__ __forceinline__ uint32_t mbar_wait(uint32_t b, uint32_t par) {
    uint32_t ok; [[maybe_unused]] int n = 0;
    while (true) {
        asm volatile("{.reg .pred p; mbarrier.try_wait.parity.shared::cta.b64 p, [%1], %2; selp.u32 %0, 1, 0, p;}"
                     : "=r"(ok) : "r"(b), "r"(par) : "memory");
        if (ok) break;
        SPIN_CHECK(n, 1000 + ((b & 511) >> 3));
    }
    return ok;
}
__device__ __forceinline__ bool mbar_test(uint32_t b, uint32_t par) {
    uint32_t ok;
    asm volatile("{.reg .pred p; mbarrier.test_wait.parity.shared::cta.b64 p, [%1], %2; selp.u32 %0, 1, 0, p;}" : "=r"(ok) : "r"(b), "r"(par) : "memory");
    return ok;
}
__device__ __forceinline__ void mbar_wait_cl(uint32_t b, uint32_t par) {
    uint32_t ok; [[maybe_unused]] int n = 0;
    while (true) {
        asm volatile("{.reg .pred p; mbarrier.try_wait.parity.relaxed.cluster.shared::cta.b64 p, [%1], %2; selp.u32 %0, 1, 0, p;}"
                     : "=r"(ok) : "r"(b), "r"(par) : "memory");
        if (ok) break;
        SPIN_CHECK(n, 1000 + ((b & 511) >> 3));
    }
    asm volatile("fence.acquire.sync_restrict::shared::cluster.cluster;" ::: "memory");
}
__device__ __forceinline__ void nbar_sync(int id, int n) { asm volatile("bar.sync %0, %1;" :: "r"(id), "r"(n) : "memory"); }
__device__ __forceinline__ void nbar_arrive(int id, int n) { asm volatile("bar.arrive %0, %1;" :: "r"(id), "r"(n) : "memory"); }
__device__ __forceinline__ void cluster_sync_all() {
    asm volatile("barrier.cluster.arrive.release.aligned; barrier.cluster.wait.acquire.aligned;" ::: "memory");
}
__device__ __forceinline__ void fence_async_smem() { asm volatile("fence.proxy.async.shared::cta;" ::: "memory"); }
__device__ __forceinline__ void fence_async_glb() { asm volatile("fence.proxy.async.global;" ::: "memory"); }
__device__ __forceinline__ void fence_rel_gpu() { asm volatile("fence.release.gpu;" ::: "memory"); }
__device__ __forceinline__ void fence_acq_gpu() { asm volatile("fence.acquire.gpu;" ::: "memory"); }
__device__ __forceinline__ void fence_gpu() { asm volatile("fence.acq_rel.gpu;" ::: "memory"); }
__device__ __forceinline__ int fresh_tid() { int t; asm volatile("mov.u32 %0, %%tid.x;" : "=r"(t)); return t; }
__device__ __forceinline__ int fresh_bid() { int t; asm volatile("mov.u32 %0, %%ctaid.x;" : "=r"(t)); return t; }
__device__ __forceinline__ uint32_t pin(uint32_t v) { asm volatile("" : "+r"(v)); return v; }
__device__ __forceinline__ int warp_in_group() { return __shfl_sync(~0u, (fresh_tid() >> 5) & 3, 0); }
__device__ __forceinline__ int cta_rank() { int t; asm volatile("mov.u32 %0, %%cluster_ctarank;" : "=r"(t)); return t; }
__device__ __forceinline__ uint32_t timer_lo() { uint32_t t; asm volatile("mov.u32 %0, %%globaltimer_lo;" : "=r"(t)); return t; }
__device__ __forceinline__ uint32_t keep(uint32_t v) { return __shfl_xor_sync(~0u, v, 0); }
__device__ __forceinline__ void red_add_u32(uint32_t* p, uint32_t v) {
    asm volatile("red.relaxed.gpu.global.add.u32 [%0], %1;" :: "l"(p), "r"(v) : "memory");
}
__device__ __forceinline__ uint32_t ld_rlx(const void* p) {
    uint32_t v; asm volatile("ld.relaxed.gpu.global.u32 %0, [%1];" : "=r"(v) : "l"(p) : "memory"); return v;
}
__device__ __forceinline__ uint2 ld_rlx64(const void* p) {
    uint2 v; asm volatile("ld.relaxed.gpu.global.v2.u32 {%0,%1}, [%2];" : "=r"(v.x), "=r"(v.y) : "l"(p) : "memory"); return v;
}
__device__ __forceinline__ uint4 ld_rlx128(const void* p) {
    uint4 v;
    asm volatile("ld.relaxed.gpu.global.v4.u32 {%0,%1,%2,%3}, [%4];" : "=r"(v.x), "=r"(v.y), "=r"(v.z), "=r"(v.w) : "l"(p) : "memory");
    return v;
}
__device__ __forceinline__ void stg128(void* p, uint4 v) {
    asm volatile("st.global.v4.b32 [%0], {%1,%2,%3,%4};" :: "l"(p), "r"(v.x), "r"(v.y), "r"(v.z), "r"(v.w) : "memory");
}
__device__ __forceinline__ void stg64(void* p, uint32_t a, uint32_t b) {
    asm volatile("st.global.v2.b32 [%0], {%1,%2};" :: "l"(p), "r"(a), "r"(b) : "memory");
}
__device__ __forceinline__ void stg16(void* p, uint32_t a) { asm volatile("st.global.b16 [%0], %1;" :: "l"(p), "h"((uint16_t)a) : "memory"); }
__device__ __forceinline__ void stg32(void* p, uint32_t a) { asm volatile("st.global.b32 [%0], %1;" :: "l"(p), "r"(a) : "memory"); }
__device__ __forceinline__ void st_async128(uint32_t a, uint32_t x, uint32_t y, uint32_t z, uint32_t w, uint32_t mb) {
    asm volatile("st.async.shared::cluster.mbarrier::complete_tx::bytes.v4.b32 [%0], {%1,%2,%3,%4}, [%5];"
                 :: "r"(a), "r"(x), "r"(y), "r"(z), "r"(w), "r"(mb) : "memory");
}
__device__ __forceinline__ void st_async64(uint32_t a, uint32_t x, uint32_t y, uint32_t mb) {
    asm volatile("st.async.shared::cluster.mbarrier::complete_tx::bytes.v2.b32 [%0], {%1,%2}, [%3];"
                 :: "r"(a), "r"(x), "r"(y), "r"(mb) : "memory");
}
__device__ __forceinline__ void sts128(uint32_t a, uint32_t x, uint32_t y, uint32_t z, uint32_t w) {
    asm volatile("st.shared.v4.b32 [%0], {%1,%2,%3,%4};" :: "r"(a), "r"(x), "r"(y), "r"(z), "r"(w) : "memory");
}
__device__ __forceinline__ void sts32(uint32_t a, uint32_t v) { asm volatile("st.shared.b32 [%0], %1;" :: "r"(a), "r"(v) : "memory"); }
__device__ __forceinline__ uint4 lds128(uint32_t a) {
    uint4 v; asm volatile("ld.shared.v4.b32 {%0,%1,%2,%3}, [%4];" : "=r"(v.x), "=r"(v.y), "=r"(v.z), "=r"(v.w) : "r"(a) : "memory"); return v;
}
__device__ __forceinline__ uint2 lds64(uint32_t a) {
    uint2 v; asm volatile("ld.shared.v2.b32 {%0,%1}, [%2];" : "=r"(v.x), "=r"(v.y) : "r"(a) : "memory"); return v;
}
__device__ __forceinline__ uint32_t lds32(uint32_t a) {
    uint32_t v; asm volatile("ld.shared.b32 %0, [%1];" : "=r"(v) : "r"(a) : "memory"); return v;
}
__device__ __forceinline__ void bulk_g2s(uint32_t dst, const void* src, uint32_t bytes, uint32_t mb) {
    asm volatile("cp.async.bulk.shared::cluster.global.mbarrier::complete_tx::bytes [%0], [%1], %2, [%3];"
                 :: "r"(dst), "l"(src), "r"(bytes), "r"(mb) : "memory");
}
__device__ __forceinline__ void bulk_s2g(void* dst, uint32_t src, uint32_t bytes) {
    asm volatile("cp.async.bulk.global.shared::cta.bulk_group [%0], [%1], %2;" :: "l"(dst), "r"(src), "r"(bytes) : "memory");
}
__device__ __forceinline__ void bulk_s2peer(uint32_t dst, uint32_t src, uint32_t bytes, uint32_t mb) {
    asm volatile("cp.async.bulk.shared::cluster.shared::cta.mbarrier::complete_tx::bytes [%0], [%1], %2, [%3];"
                 :: "r"(dst), "r"(src), "r"(bytes), "r"(mb) : "memory");
}
__device__ __forceinline__ void tma_unit(uint32_t dst, const CUtensorMap* tm, int kstep, int mgroup, uint32_t mb) {
    asm volatile("cp.async.bulk.tensor.2d.shared::cluster.global.mbarrier::complete_tx::bytes [%0], [%1, {%2,%3}], [%4];"
                 :: "r"(dst), "l"(tm), "r"(mgroup * 64), "r"(kstep * 16), "r"(mb) : "memory");
}
__device__ __forceinline__ void ldsm4(uint32_t* r, uint32_t a) {
    asm volatile("ldmatrix.sync.aligned.m8n8.x4.shared.b16 {%0,%1,%2,%3}, [%4];"
                 : "=r"(r[0]), "=r"(r[1]), "=r"(r[2]), "=r"(r[3]) : "r"(a) : "memory");
}
__device__ __forceinline__ void ldsm4t(uint32_t* r, uint32_t a) {
    asm volatile("ldmatrix.sync.aligned.m8n8.x4.trans.shared.b16 {%0,%1,%2,%3}, [%4];"
                 : "=r"(r[0]), "=r"(r[1]), "=r"(r[2]), "=r"(r[3]) : "r"(a) : "memory");
}
__device__ __forceinline__ void stsm4(uint32_t a, uint32_t r0, uint32_t r1, uint32_t r2, uint32_t r3) {
    asm volatile("stmatrix.sync.aligned.m8n8.x4.shared.b16 [%0], {%1,%2,%3,%4};" :: "r"(a), "r"(r0), "r"(r1), "r"(r2), "r"(r3) : "memory");
}
__device__ __forceinline__ void stsm4t(uint32_t a, uint32_t r0, uint32_t r1, uint32_t r2, uint32_t r3) {
    asm volatile("stmatrix.sync.aligned.m8n8.x4.trans.shared.b16 [%0], {%1,%2,%3,%4};" :: "r"(a), "r"(r0), "r"(r1), "r"(r2), "r"(r3) : "memory");
}
__device__ __forceinline__ uint32_t pack2(float lo, float hi) {
    uint32_t d; asm("cvt.rn.bf16x2.f32 %0, %1, %2;" : "=r"(d) : "f"(hi), "f"(lo)); return d;
}
__device__ __forceinline__ float bf_lo(uint32_t w) { return __uint_as_float(w << 16); }
__device__ __forceinline__ float bf_hi(uint32_t w) { return __uint_as_float(w & 0xffff0000u); }
__device__ __forceinline__ float ex2(float x) { float y; asm("ex2.approx.ftz.f32 %0, %1;" : "=f"(y) : "f"(x)); return y; }
__device__ __forceinline__ float rcp(float x) { float y; asm("rcp.approx.ftz.f32 %0, %1;" : "=f"(y) : "f"(x)); return y; }
__device__ __forceinline__ uint32_t fu(float x) { return __float_as_uint(x); }
__device__ __forceinline__ float uf(uint32_t x) { return __uint_as_float(x); }
__device__ __forceinline__ void mma16816(float* d, const uint32_t* a, uint32_t b0, uint32_t b1) {
    asm volatile("mma.sync.aligned.m16n8k16.row.col.f32.bf16.bf16.f32 {%0,%1,%2,%3}, {%4,%5,%6,%7}, {%8,%9}, {%0,%1,%2,%3};"
                 : "+f"(d[0]), "+f"(d[1]), "+f"(d[2]), "+f"(d[3]) : "r"(a[0]), "r"(a[1]), "r"(a[2]), "r"(a[3]), "r"(b0), "r"(b1));
}
__device__ __forceinline__ void mma1688(float* d, uint32_t a0, uint32_t a1, uint32_t b0) {
    asm volatile("mma.sync.aligned.m16n8k8.row.col.f32.bf16.bf16.f32 {%0,%1,%2,%3}, {%4,%5}, {%6}, {%0,%1,%2,%3};"
                 : "+f"(d[0]), "+f"(d[1]), "+f"(d[2]), "+f"(d[3]) : "r"(a0), "r"(a1), "r"(b0));
}
template <int N> __device__ __forceinline__ void reg_inc() { asm volatile("setmaxnreg.inc.sync.aligned.u32 %0;" :: "n"(N)); }
template <int N> __device__ __forceinline__ void reg_dec() { asm volatile("setmaxnreg.dec.sync.aligned.u32 %0;" :: "n"(N)); }

__device__ __forceinline__ uint64_t mkdesc(uint32_t addr, uint32_t lbo, uint32_t sbo, uint32_t swz) {
    return (uint64_t)((addr + SM_ORG) >> 4) | ((uint64_t)(lbo >> 4) << 16) | ((uint64_t)(sbo >> 4) << 32) | ((uint64_t)swz << 62);
}
__device__ __forceinline__ void wg_fence() { asm volatile("wgmma.fence.sync.aligned;" ::: "memory"); }
__device__ __forceinline__ void wg_commit() { asm volatile("wgmma.commit_group.sync.aligned;" ::: "memory"); }
template <int N> __device__ __forceinline__ void wg_wait() { asm volatile("wgmma.wait_group.sync.aligned %0;" :: "n"(N) : "memory"); }
template <int M> __device__ __forceinline__ void acc_ready(float* d) {
#pragma unroll
    for (int j = 0; j < M; j++) asm volatile("" : "+f"(d[j]) :: "memory");
}
template <int N, int M> __device__ __forceinline__ void wg_wait_acc(float* d) { wg_wait<N>(); acc_ready<M>(d); }

#define F8(c, d, o) c(d[o]), c(d[o + 1]), c(d[o + 2]), c(d[o + 3]), c(d[o + 4]), c(d[o + 5]), c(d[o + 6]), c(d[o + 7])
#define R8L "%0,%1,%2,%3,%4,%5,%6,%7"
#define R16L R8L ",%8,%9,%10,%11,%12,%13,%14,%15"
#define R32L R16L ",%16,%17,%18,%19,%20,%21,%22,%23,%24,%25,%26,%27,%28,%29,%30,%31"
#define R40L R32L ",%32,%33,%34,%35,%36,%37,%38,%39"
#define WG_BOTH(TXT_PRE, TXT_POST, OUTS, ...)                                                   \
    if (acc) asm volatile(TXT_PRE "1" TXT_POST : OUTS("+f") : __VA_ARGS__);                     \
    else asm volatile(TXT_PRE "0" TXT_POST : OUTS("=f") : __VA_ARGS__)
#define O8(c) F8(c, d, 0)
#define O16(c) F8(c, d, 0), F8(c, d, 8)
#define O32(c) O16(c), F8(c, d, 16), F8(c, d, 24)
#define O40(c) O32(c), F8(c, d, 32)
#define WGM(n) "wgmma.mma_async.sync.aligned.m64n" #n "k16.f32.bf16.bf16 "
__device__ __forceinline__ void wg_rs16(float* d, const uint32_t* a, uint64_t db, bool acc) {
    WG_BOTH(WGM(16) "{" R8L "}, {%8,%9,%10,%11}, %12, ", ", 1, 1, 1;", O8, "r"(a[0]), "r"(a[1]), "r"(a[2]), "r"(a[3]), "l"(db));
}
__device__ __forceinline__ void wg_ss16(float* d, uint64_t da, uint64_t db, bool acc) {
    WG_BOTH(WGM(16) "{" R8L "}, %8, %9, ", ", 1, 1, 1, 1;", O8, "l"(da), "l"(db));
}
__device__ __forceinline__ void wg_rs8(float* d, const uint32_t* a, uint64_t db, bool acc) {
#define O4(c) c(d[0]), c(d[1]), c(d[2]), c(d[3])
    WG_BOTH(WGM(8) "{%0,%1,%2,%3}, {%4,%5,%6,%7}, %8, ", ", 1, 1, 0;", O4, "r"(a[0]), "r"(a[1]), "r"(a[2]), "r"(a[3]), "l"(db));
}
__device__ __forceinline__ void wg_rs32(float* d, const uint32_t* a, uint64_t db, bool acc) {
    WG_BOTH(WGM(32) "{" R16L "}, {%16,%17,%18,%19}, %20, ", ", 1, 1, 0;", O16, "r"(a[0]), "r"(a[1]), "r"(a[2]), "r"(a[3]), "l"(db));
}
__device__ __forceinline__ void wg_ss32(float* d, uint64_t da, uint64_t db, bool acc) {
    WG_BOTH(WGM(32) "{" R16L "}, %16, %17, ", ", 1, 1, 1, 0;", O16, "l"(da), "l"(db));
}
template <int TB> __device__ __forceinline__ void wg_rs64(float* d, const uint32_t* a, uint64_t db, bool acc) {
    WG_BOTH(WGM(64) "{" R32L "}, {%32,%33,%34,%35}, %36, ", ", 1, 1, %37;", O32, "r"(a[0]), "r"(a[1]), "r"(a[2]), "r"(a[3]), "l"(db), "n"(TB));
}
template <int TB> __device__ __forceinline__ void wg_ss64(float* d, uint64_t da, uint64_t db, bool acc) {
    WG_BOTH(WGM(64) "{" R32L "}, %32, %33, ", ", 1, 1, 1, %34;", O32, "l"(da), "l"(db), "n"(TB));
}
__device__ __forceinline__ void wg_ss80(float* d, uint64_t da, uint64_t db, bool acc) {
    WG_BOTH(WGM(80) "{" R40L "}, %40, %41, ", ", 1, 1, 1, 1;", O40, "l"(da), "l"(db));
}

constexpr float SM_SCALE = 0.08838834764831845f;
constexpr float LOG2E = 1.4426950408889634f;

#define WO_DELAY 3000
#define D_DELAY 7000
#define F1_DELAY 7000
#define W2_DELAY 16500
#define F1_DEPTH 30
#define PF_DELAY 6000
#define PF_PACE 400
__device__ __forceinline__ void hold_back(uint32_t ns) {
    const uint32_t t0 = timer_lo();
    while (timer_lo() - t0 < ns) __nanosleep(50);
}

__device__ __forceinline__ uint32_t* flag_ptr(int stage, int b) { return &g_flag[stage][b][0]; }
__device__ __forceinline__ uint32_t this_launch() { return ld_rlx(&g_epoch[fresh_bid()][0]) + 1; }
__device__ __forceinline__ bool flag_up(int stage, int b, uint32_t target) { return (int)(ld_rlx(flag_ptr(stage, b)) - target) >= 0; }
__device__ __forceinline__ void flag_wait(int stage, int b, uint32_t target) {
    [[maybe_unused]] int n = 0;
    while (!flag_up(stage, b, target)) {
        __nanosleep(20);
        SPIN_CHECK(n, 10 + stage);
    }
    fence_acq_gpu();
    fence_async_glb();
}
__device__ __forceinline__ void publish(int stage, int b) {
    fence_async_glb();
    fence_rel_gpu();
    red_add_u32(flag_ptr(stage, b), 1);
}
__device__ __forceinline__ uint32_t unit_frag_addr(int tid) {
    const int lane = tid & 31, w = (tid >> 5) & 3, i = lane & 7, j = lane >> 3;
    return ((j >> 1) * 8 + i) * 128 + ((((w << 1) + (j & 1)) ^ i) << 4);
}

#define V_BURST1 3
#define V_BURST2 1
#define V_CUT 2
#define V_PRE 9
#define SX_BF16 0
#define V_REV 1
#define K_GATE 1
#define WO_R8 1
#define OX_V4 0
#define V_LEAD 9
static_assert((V_BURST1 + V_BURST2 >= 2 || V_PRE == 7) && V_BURST1 <= 3 && V_LEAD > V_BURST1 + V_BURST2, "q and k rely on v for the arrival of the blocks");
#define K_LEAD 0
#define Q_LEAD 36
#define V_FIRST 8
#define SX_GATE 1
static_assert(SX_GATE, "EB_QF also stands for the K tile");
#define V_EARLY 1
__host__ __device__ constexpr int x_order(int mat, int j) {
    return mat == 2 ? j : j < 3 ? j + 5 : j < 5 ? j : j == 5 ? 2 : j == 6 ? 8 : 8 - j;
}
#define SS0Q 0
#define SS0K 0
#define SS0V 22
#define SSLQ 36
#define SSLK 36
#define SSLV 14
__host__ __device__ constexpr uint64_t ss_mask(int mat) {
    const int ns = 36 - (mat == 0 ? NRQ : mat == 1 ? NRK : NRV);
    const int j0 = mat == 0 ? SS0Q : mat == 1 ? SS0K : SS0V, len = mat == 0 ? SSLQ : mat == 1 ? SSLK : SSLV;
    uint64_t m = 0;
    for (int j = j0; j < j0 + len; j++)
        if ((j - j0) * ns / len != (j - j0 + 1) * ns / len) m |= 1ull << (x_order(mat, j >> 2) * 4 + (j & 3));
    return m;
}
__device__ __forceinline__ int popc_below(uint64_t m, int k) { return __popcll(m & ((1ull << k) - 1)); }
__host__ __device__ constexpr int x_slot(int f) {
    return f < 3 ? E_R0 + f * 8192 : f == 3 ? E_QT : f == 4 ? E_KT : f < 7 ? E_MEM + (f - 5) * 8192 : f == 8 ? E_R2 : f == 10 ? E_R1 : E_R0;
}
__host__ __device__ constexpr int x_full(int f) { return f < 3 ? 0 : f < 9 ? (f - 1) / 2 : 14 - f; }
__host__ __device__ constexpr bool x_first(int f) { return f == 0 || x_full(f) != x_full(f - 1); }
__host__ __device__ constexpr int x_empty(int blk) { return blk == 6 ? 0 : blk == 7 ? 1 : blk == 4 ? 2 : -1; }
__host__ __device__ constexpr int ar_tile(int j) { return j == 0 ? 8 : ((j - 1) & 1) * 4 + ((j - 1) >> 1); }
__host__ __device__ constexpr int sx_off(int u) { return u == 0 ? 0 : u == 1 ? 1536 : u == 2 ? 2560 : u == 3 ? 3072 : 5120; }

template <int MAT, int NR, int K0, int K1>
__device__ __forceinline__ void proj_mem(float* d, const uint32_t (&w)[NR][4]) {
    constexpr uint64_t M = ss_mask(MAT);
    const uint64_t db = mkdesc(E_MEM, 128, 9216, 0);
    const uint64_t da = mkdesc((MAT == 0 ? E_WQ : MAT == 1 ? E_WK : E_WV), 1024, 1024, 1);
#pragma unroll
    for (int j = K0; j < K1; j++) {
        const int ks = MAT != 2 ? ar_tile(j >> 2) * 4 + (j & 3) : V_REV ? 35 - j : j, s = popc_below(M, ks);
        if ((M >> ks) & 1) wg_ss16(d, da + s * 128, db + ks * 16, j > 0);
        else wg_rs16(d, w[ks - s], db + ks * 16, j > 0);
    }
}
__device__ __forceinline__ uint32_t tl_lane(int tid, int group_bytes) {
    return ((tid >> 4) & 1) * group_bytes + (((tid >> 5) & 3) * 16 + (tid & 15)) * 16;
}
struct ArWords {
    uint32_t w[5];
    __device__ __forceinline__ ArWords(const float* y) {
        w[0] = pack2(y[0], y[1]); w[1] = pack2(y[2], y[3]); w[2] = pack2(y[4], y[5]); w[3] = pack2(y[6], 1.f); w[4] = pack2(y[7], 1.f);
    }
    __device__ __forceinline__ void force(uint32_t zero) {
        asm volatile("{.reg .pred p; setp.ne.u32 p, %0, 0; @p st.shared.v4.b32 [%5], {%1,%2,%3,%4};}" :: "r"(zero), "r"(w[0]), "r"(w[1]), "r"(w[2]), "r"(w[3]), "r"(w[4]) : "memory");
    }
    __device__ __forceinline__ void red(uint8_t* p, uint8_t* q) {
        asm volatile("red.relaxed.gpu.global.add.noftz.v4.bf16x2 [%0], {%1,%2,%3,%4};" :: "l"(p), "r"(w[0]), "r"(w[1]), "r"(w[2]), "r"(w[3]) : "memory");
        asm volatile("red.relaxed.gpu.global.add.noftz.bf16x2 [%0], %1;" :: "l"(q), "r"(w[4]) : "memory");
    }
};
__device__ __forceinline__ uint32_t ar_main(int tid) { return ((tid & 127) >> 3) * AR_STR + (tid & 7) * 16; }
__device__ __forceinline__ uint32_t ar_side(int tid) { return ((tid & 127) >> 5) * (4 * AR_STR) + AR_STR / 2 + (tid & 31) * 4; }

#define AR_VA 0
#define AR_VA1 1
#define AR_SPLIT 5
template <bool B> struct Bool { static constexpr bool value = B; };
template <int J0, int J1>
__device__ __forceinline__ int ar_fetch(const Params& P, int i, int tid, uint32_t gate, uint32_t done) {
    const uint8_t* pm = g_ar + ((i & 3) * AR_SLOT + ar_main(tid));
    const uint8_t* ps = g_ar + ((i & 3) * AR_SLOT + ar_side(tid));
    const uint32_t a = sb + E_MEM + tl_lane(tid, 9216);
    asm volatile("{.reg .pred p; setp.ne.u32 p, %0, 0; @p st.shared.v2.b64 [%3], {%1,%2};}" :: "r"(P.zero), "l"(pm), "l"(ps), "r"(a) : "memory");
    if (J0 == 0) mbar_wait(gate, (i & 1) ^ 1);
    int n = -1;
    bool bad = i >= 0;
    while (bad) {
        uint4 av[J1 - J0];
        uint32_t as[J1 - J0];
#pragma unroll
        for (int j = J0; j < J1; j++) { av[j - J0] = ld_rlx128(pm + ar_tile(j) * (16 * AR_STR)); as[j - J0] = ld_rlx(ps + ar_tile(j) * (16 * AR_STR)); }
        bad = false;
#pragma unroll
        for (int j = J0; j < J1; j++) {
            bad |= __byte_perm(av[j - J0].w, as[j - J0], 0x7632) != (ar_tile(j) == 8 ? 0x42804280u : 0x42004200u);
            stsm4(a + ar_tile(j) * 1024, av[j - J0].x, av[j - J0].y, av[j - J0].z, __byte_perm(av[j - J0].w, as[j - J0], 0x5410));
        }
        bad = __any_sync(~0u, bad);
        SPIN_CHECK(n, 2);
        PROF_INC(n, 1);
    }
    if (i < 0 || i + 1 == LAG) {
        const uint16_t* m = (const uint16_t*)P.mem0 + (tid & 3) * (2 * DM) + (tid >> 5) * 16 + ((tid & 31) >> 2);
        const uint32_t a2 = sb + E_MEM + (tid >> 5) * 256 + (tid & 31) * 4;
        uint32_t v[18];
#pragma unroll
        for (int T = 2 * J0; T < 2 * J1; T++) v[T] = (uint32_t)__ldg(m + ar_tile(T >> 1) * 64 + (T & 1) * 8) | ((uint32_t)__ldg(m + ar_tile(T >> 1) * 64 + (T & 1) * 8 + DM) << 16);
        __syncwarp();
#pragma unroll
        for (int T = 2 * J0; T < 2 * J1; T++) {
            sts32(a2 + 9216 + ar_tile(T >> 1) * 1024 + (T & 1) * 128, v[T]);
            if (i < 0) sts32(a2 + ar_tile(T >> 1) * 1024 + (T & 1) * 128, v[T]);
        }
    }
    if (J0) fence_async_smem();
    mbar_arrive_warp(done);
    return n;
}

__device__ __forceinline__ void attn_mem(float* d, uint32_t par, int i, int tid) {
    const int lane = tid & 31, warp = tid >> 5, c = warp >> 1, hf = warp & 1;
    const int rank = cta_rank();
    const uint32_t peer = mapa(sb, rank ^ 1);
    const uint32_t l4 = (lane >> 4) * 1024 + (lane & 15) * 16;
    uint32_t kb[4][4];
    {
        const uint32_t aK = sb + E_KT + (c * 6 + hf * 2) * 1024 + l4;
#pragma unroll
        for (int ks = 0; ks < 4; ks++) ldsm4t(kb[ks], aK + ks * 256);
    }
    const uint32_t aQs = pin(sb + E_QM + tl_lane(tid, 1024));
    const uint32_t aQ = pin(sb + E_QM + c * 1024 + (((lane >> 3) & 1) * 16 + (lane >> 4) * 8 + (lane & 7)) * 16);
    const uint32_t aM = pin(sb + E_KT + (4 + c) * 1024 + lane * 16);
    const uint32_t oS = pin(tid * 16);
    wg_wait_acc<0, 8>(d);
    stsm4(aQs, pack2(d[0], d[1]), pack2(d[2], d[3]), pack2(d[4], d[5]), pack2(d[6], d[7]));
    nbar_sync(NB_QK, 256);
    TS(0, i, 1);
    float s[6];
    {
        uint32_t q[2][4], km[2][4];
        ldsm4t(q[0], aQ); ldsm4t(km[0], aM); ldsm4t(q[1], aQ + 512); ldsm4t(km[1], aM + 512);
        float a[6][4];
#pragma unroll
        for (int m = 0; m < 6; m++) a[m][0] = a[m][1] = a[m][2] = a[m][3] = 0.f;
#pragma unroll
        for (int j = 0; j < 2; j++) {
#pragma unroll
            for (int o = 0; o < 2; o++) {
                mma16816(a[o * 3], q[j], kb[2 * j + o][0], kb[2 * j + o][1]);
                mma16816(a[o * 3 + 1], q[j], kb[2 * j + o][2], kb[2 * j + o][3]);
            }
            mma16816(a[2], q[j], km[j][0], km[j][1]);
            mma16816(a[5], q[j], km[j][2], km[j][3]);
        }
        nbar_arrive(NB_S, 256);
        if (SX_GATE) nbar_arrive(NB_S2, 256);
#pragma unroll
        for (int m = 0; m < 3; m++) { s[2 * m] = a[m][0] + a[3 + m][2]; s[2 * m + 1] = a[m][1] + a[3 + m][3]; }
    }
    st_async128(peer + E_SR + oS, fu(s[0]), fu(s[1]), fu(s[2]), fu(s[3]), peer + SM_BAR + EB_SM * 8);
    const uint32_t oM = E_SR + 2048 + c * 256 + lane * 8;
    asm volatile("st.async.shared::cluster.mbarrier::complete_tx::bytes.b32 [%0], %1, [%2];"
                 :: "r"(peer + oM + hf * 4), "r"(fu(hf ? s[5] : s[4])), "r"(peer + SM_BAR + EB_SM * 8) : "memory");
    sts128(sb + E_SL + oS, fu(s[0]), fu(s[1]), fu(s[2]), fu(s[3]));
    mbar_arrive_warp(bars + EB_KF * 8);
    TS(0, i, 2);
#pragma unroll
    for (int j = 0; j < 4; j++) ldsm4(kb[j], sb + E_VT + c * 6144 + l4 + hf * 512 + ((j >> 1) ^ hf) * 2048 + (j & 1) * 256);
    nbar_sync(NB_G, 128);
    const uint32_t aR = sb + E_SR + oS, aR1 = sb + E_SR + (oS ^ 512), aRm = sb + oM;
    const uint4 l1 = lds128(aR1 + (E_SL - E_SR));
    mbar_wait_cl(bars + EB_SM * 8, par);
    TS(0, i, 3);
    float p[10];
    {
        const uint4 r0 = lds128(aR), r1 = lds128(aR1);
        const uint2 rm = lds64(aRm);
        p[0] = s[0] + uf(r0.x); p[1] = s[1] + uf(r0.y); p[2] = s[2] + uf(r0.z); p[3] = s[3] + uf(r0.w);
        p[4] = uf(l1.x) + uf(r1.x); p[5] = uf(l1.y) + uf(r1.y); p[6] = uf(l1.z) + uf(r1.z); p[7] = uf(l1.w) + uf(r1.w);
        p[8] = s[4] + uf(rm.x); p[9] = s[5] + uf(rm.y);
    }
    float mx = fmaxf(fmaxf(fmaxf(p[0], p[1]), fmaxf(p[2], p[3])), fmaxf(fmaxf(fmaxf(p[4], p[5]), fmaxf(p[6], p[7])), fmaxf(p[8], p[9])));
    mx = fmaxf(mx, __shfl_xor_sync(~0u, mx, 1));
    mx = fmaxf(mx, __shfl_xor_sync(~0u, mx, 2));
    const float mo = mx * (SM_SCALE * LOG2E);
    mbar_wait(bars + EB_KF * 8, par);
    uint32_t vm[4], pb[5];
    ldsm4(vm, aM + (E_VT - E_KT) + hf * 512);
    float o[3][4];
    const uint32_t ones[4] = {0x3f803f80u, 0x3f803f80u, 0x3f803f80u, 0x3f803f80u};
#pragma unroll
    for (int T = 0; T < 3; T++) o[T][0] = o[T][1] = o[T][2] = o[T][3] = 0.f;
#pragma unroll
    for (int j = 0; j < 2; j++) {
#pragma unroll
        for (int m = 2 * j; m < 2 * j + 2; m++) pb[m] = pack2(ex2(fmaf(p[2 * m], SM_SCALE * LOG2E, -mo)), ex2(fmaf(p[2 * m + 1], SM_SCALE * LOG2E, -mo)));
        mma16816(o[2], ones, pb[2 * j], pb[2 * j + 1]);
#pragma unroll
        for (int T = 0; T < 2; T++) mma16816(o[T], kb[2 * j + T], pb[2 * j], pb[2 * j + 1]);
    }
    pb[4] = pack2(ex2(fmaf(p[8], SM_SCALE * LOG2E, -mo)), ex2(fmaf(p[9], SM_SCALE * LOG2E, -mo)));
    mma1688(o[2], ones[0], ones[1], pb[4]);
#pragma unroll
    for (int T = 0; T < 2; T++) mma1688(o[T], vm[2 * T], vm[2 * T + 1], pb[4]);
    nbar_arrive(NB_PV, 256);
    mbar_arrive_warp(bars + EB_CONS * 8);
    const float i0 = rcp(o[2][0]), i1 = rcp(o[2][1]);
    uint32_t ow[4];
#pragma unroll
    for (int j = 0; j < 4; j++) ow[j] = pack2(o[j >> 1][2 * (j & 1)] * i0, o[j >> 1][2 * (j & 1) + 1] * i1);
    const uint32_t oO = E_OM + c * 2048 + hf * 512;
    stsm4(sb + oO + lane * 16, ow[0], ow[1], ow[2], ow[3]);
    if (OX_V4) {
        __syncwarp();
        const uint4 r = lds128(sb + oO + lane * 16);
        nbar_sync(NB_G, 128);
        st_async128(peer + oO + 1024 + lane * 16, r.x, r.y, r.z, r.w, peer + SM_BAR + EB_OX * 8);
    } else {
#pragma unroll
        for (int j = 0; j < 4; j++)
            asm volatile("st.async.shared::cluster.mbarrier::complete_tx::bytes.b32 [%0], %1, [%2];"
                         :: "r"(peer + oO + 1024 + j * 128 + lane * 4), "r"(ow[j]), "r"(peer + SM_BAR + EB_OX * 8) : "memory");
    }
}

__device__ __forceinline__ void attn_x_scores(float (&p)[2][10], uint32_t par, int i, int tid) {
    {
        float s[40];
        const uint64_t da = mkdesc(E_QT, 128, 1024, 0), db = mkdesc(E_KT, 128, 1024, 0);
        wg_fence();
#pragma unroll
        for (int ks = 0; ks < 4; ks++) wg_ss80(s, da + ks * 16, db + ks * 16, ks > 0);
        wg_commit();
        const int dq = (tid >> 2) - 2 * (tid & 3);
        float mask[8];
#pragma unroll
        for (int j = 0; j < 8; j++) mask[j] = (j >> 1) * 8 + (j & 1) > dq ? -1e9f * LOG2E : 0.f;
        mbar_wait_cl(bars + EB_PRDY * 8, par);
        wg_wait_acc<0, 40>(s);
#pragma unroll
        for (int u = 0; u < 5; u++) {
            const int v = u < 4 ? 6 + u : 5;
            constexpr float C = SM_SCALE * LOG2E;
            const float m0 = u < 4 ? mask[2 * u & 7] : 0.f, m1 = u < 4 ? mask[(2 * u + 1) & 7] : 0.f;
            p[0][2 * u] = fmaf(s[4 * u], C, m0); p[0][2 * u + 1] = fmaf(s[4 * u + 1], C, m1); p[1][2 * u] = fmaf(s[4 * v + 2], C, m0); p[1][2 * u + 1] = fmaf(s[4 * v + 3], C, m1);
        }
    }
    mbar_arrive_warp(bars + EB_QF * 8);
    const int w = tid >> 5;
    if (!SX_BF16) {
        const uint32_t peer = mapa(sb, cta_rank() ^ 1);
#pragma unroll
        for (int u = 0; u < 5; u++)
            if (u == 0 || u <= w || u == 4) st_async128(peer + E_SX + sx_off(u) + tid * 16, fu(p[0][2 * u]), fu(p[0][2 * u + 1]), fu(p[1][2 * u]), fu(p[1][2 * u + 1]), peer + SM_BAR + EB_SX * 8);
    } else {
        const uint32_t peer = mapa(sb, cta_rank() ^ 1), a = peer + E_SX + tid * 16, mb = peer + SM_BAR + EB_SX * 8;
        st_async128(a, pack2(p[0][0], p[0][1]), pack2(p[1][0], p[1][1]), pack2(p[0][8], p[0][9]), pack2(p[1][8], p[1][9]), mb);
        if (w >= 1) st_async128(a + 2048, pack2(p[0][2], p[0][3]), pack2(p[1][2], p[1][3]), pack2(p[0][4], p[0][5]), pack2(p[1][4], p[1][5]), mb);
        if (w >= 3) st_async64(a + 4096, pack2(p[0][6], p[0][7]), pack2(p[1][6], p[1][7]), mb);
    }
    TS(128, i, 10);
}
__device__ __forceinline__ void attn_x_finish(float (&p)[2][10], uint32_t par, int i, int& tid, uint32_t zero) {
    const int w = tid >> 5;
    mbar_wait_cl(bars + EB_SX * 8, par);
    TS(128, i, 11);
    if (SX_BF16) {
        const uint32_t a = sb + E_SX + tid * 16;
        const uint4 r0 = lds128(a), r1 = lds128(a + (w >= 1 ? 2048 : 0));
        const uint2 r2 = lds64(a + (w >= 3 ? 4096 : 0));
        const uint32_t r[10] = {r0.x, r0.y, r1.x, r1.y, r1.z, r1.w, r2.x, r2.y, r0.z, r0.w};
#pragma unroll
        for (int j = 0; j < 10; j++) { p[j & 1][j & ~1] += bf_lo(r[j]); p[j & 1][j | 1] += bf_hi(r[j]); }
    } else
#pragma unroll
    for (int u = 0; u < 5; u++) {
        const uint4 r = lds128(pin(sb + tid * 16 + (u == 0 || u <= w ? sx_off(u) : sx_off(4))) + E_SX);
        p[0][2 * u] += uf(r.x); p[0][2 * u + 1] += uf(r.y); p[1][2 * u] += uf(r.z); p[1][2 * u + 1] += uf(r.w);
    }
    nbar_sync(NB_W, 128);
    uint32_t pa[5][4];
    float mx[2], inv[2];
#pragma unroll
    for (int h = 0; h < 2; h++) {
        const float* q = p[h];
        mx[h] = fmaxf(fmaxf(fmaxf(q[0], q[1]), fmaxf(q[2], q[3])), fmaxf(fmaxf(fmaxf(q[4], q[5]), fmaxf(q[6], q[7])), fmaxf(q[8], q[9])));
    }
#pragma unroll
    for (int o = 1; o < 4; o <<= 1) { mx[0] = fmaxf(mx[0], __shfl_xor_sync(~0u, mx[0], o)); mx[1] = fmaxf(mx[1], __shfl_xor_sync(~0u, mx[1], o)); }
#pragma unroll
    for (int h = 0; h < 2; h++) {
        float* q = p[h];
#pragma unroll
        for (int j = 0; j < 10; j++) q[j] = ex2(q[j] - mx[h]);
#pragma unroll
        for (int u = 0; u < 4; u++) {
            pa[h * 3 + (u >> 1)][(u & 1) * 2 + h] = pack2(q[2 * u], q[2 * u + 1]);
            pa[h * 3 + (u >> 1)][(u & 1) * 2 + (h ^ 1)] = zero << (h * 5 + u + 1);
        }
        pa[2][h * 3] = pack2(q[8], q[9]);
        pa[2][1 + h] = zero << (h * 5 + 5);
    }
    mbar_wait(bars + EB_CONS * 8, par);
    fence_async_smem();
    tid = pin(tid << zero);
    const uint32_t aO = pin(sb + (((tid >> 4) & 1) * 8 + (tid & 7)) * 128 + (((((tid >> 3) & 1) * 4 + (tid >> 5)) ^ (tid & 7)) << 4)) + E_R1;
    TS(128, i, 12);
#pragma unroll
    for (int nh = 0; nh < 2; nh++) {
        float o[16], sum[4];
        const uint64_t db = mkdesc(E_VT + nh * 512, 1024, 128, 0);
        wg_fence();
#pragma unroll
        for (int kk = 0; kk < 5; kk++) {
            if (nh == 0) wg_rs8(sum, pa[kk], mkdesc(SM_ONES, 0, 0, 0), kk > 0);
            wg_rs32(o, pa[kk], db + kk * 128, kk > 0);
        }
        wg_commit();
        wg_wait_acc<0, 16>(o);
        if (nh == 0) { acc_ready<4>(sum); inv[0] = rcp(sum[0]); inv[1] = rcp(sum[2]); }
#pragma unroll
        for (int j = 0; j < 2; j++) {
            const float* y = &o[8 * j];
            stsm4t(aO + nh * 4096 + j * 2048, pack2(y[0] * inv[0], y[1] * inv[0]), pack2(y[2] * inv[1], y[3] * inv[1]), pack2(y[4] * inv[0], y[5] * inv[0]), pack2(y[6] * inv[1], y[7] * inv[1]));
        }
    }
    mbar_arrive_warp(bars + EB_OST * 8);
    TS(128, i, 13);
}

template <int MAT>
__device__ __forceinline__ void engine_main(const Params& P) {
    constexpr int NR = MAT == 0 ? NRQ : MAT == 1 ? NRK : NRV;
    constexpr uint64_t M = ss_mask(MAT);
    uint32_t w[NR][4];
    {
        const uint32_t a = sb + E_WO + (MAT == 0 ? 0 : MAT == 1 ? NRQ : NRQ + NRK) * 2048 + unit_frag_addr(fresh_tid());
        mbar_wait(bars + EB_WL * 8, 0);
        if (MAT == 0 && threadIdx.x == 0) TG(79, 2);
#pragma unroll
        for (int u = 0; u < NR; u++) ldsm4t(w[u], a + u * 2048);
    }
    nbar_arrive(NB_T, 448);
    int tid = fresh_tid() - MAT * 128;
#define TID (tid = pin(tid << P.zero))
    if (MAT == 0) { if (V_FIRST == 36) nbar_arrive(NB_S, 256); nbar_arrive(NB_PV, 256); nbar_arrive(NB_WO, 256); }
    auto project = [&](auto one, const int i) {
        constexpr bool ONE = decltype(one)::value;
        const uint32_t par = i & 1;
        {
            float d[ONE ? 16 : 32];
            const uint64_t da = mkdesc((MAT == 0 ? E_WQ : MAT == 1 ? E_WK : E_WV), 1024, 1024, 1);
            constexpr int R1 = V_BURST1, R2 = V_BURST1 + V_BURST2;
#pragma unroll
            for (int n = 0; n < 9; n++) {
                const int blk = x_order(MAT, n), prev = n ? x_order(MAT, n - 1) : -1, f = MAT != 2 && blk < 2 ? 9 + blk : blk;
                if (MAT == 2) {
                    if (!V_CUT && R2 >= 2 && n == (R1 >= 2 ? R1 : R2)) { wg_wait<0>(); mbar_arrive_warp(bars + EB_V0 * 8); }
                    if ((n == 0 && (V_FIRST == 36 || i == 0)) || n == R1 || n == R2) {
#pragma unroll
                        for (int j = n; j < (n < R1 ? R1 : n < R2 ? R2 : V_PRE); j++) if (x_first(j)) mbar_wait(bars + (EB_FULL + x_full(j)) * 8, par);
                    }
                    if (n == 0 && V_FIRST == 36) nbar_sync(NB_S, 256);
                    if (n == R1 && !V_CUT) nbar_sync(NB_PV, 256);
                    if (n == R2) nbar_sync(NB_WO, 256);
                } else {
                    if (n == 0) nbar_sync(MAT ? NB_VL : NB_VL2, 256);
                }
                static_assert(V_PRE == 9 || (V_PRE == 7 && V_LEAD > 7), "see the barriers");
                const bool wt = MAT == 2 ? f == V_PRE : f >= 9;
                if (wt) mbar_wait(bars + (EB_FULL + x_full(f)) * 8, par);
                TX(MAT * 128, 1 + MAT * 9 + n);
                if (wt || n == 0 || (MAT == 2 && (n == R1 || n == R2))) wg_fence();
                if (n == 0) TS(MAT * 128, i, 20 + MAT);
                const uint64_t db = mkdesc(x_slot(f), 16, 1024, 1);
#pragma unroll
                for (int j = 0; j < 4; j++) {
                    const int ks = blk * 4 + j, s = popc_below(M, ks);
                    if (MAT == 2 && V_CUT && ks == R1 * 4 - V_CUT) { wg_commit(); wg_wait<0>(); mbar_arrive_warp(bars + EB_V0 * 8); nbar_sync(NB_PV, 256); wg_fence(); }
                    if constexpr (ONE) {
                        if ((M >> ks) & 1) wg_ss32(d, da + s * 128, db + j * 2, n + j > 0);
                        else wg_rs32(d, w[ks - s], db + j * 2, n + j > 0);
                    } else {
                        if ((M >> ks) & 1) wg_ss64<0>(d, da + s * 128, db + j * 2, n + j > 0);
                        else wg_rs64<0>(d, w[ks - s], db + j * 2, n + j > 0);
                    }
                }
                wg_commit();
                if (MAT == 2 && n + 1 == V_LEAD) { nbar_arrive(NB_VL, 256); if (!K_LEAD) nbar_arrive(NB_VL2, 256); }
                if (MAT == 1 && n + 1 == K_LEAD) nbar_arrive(NB_VL2, 256);
                if (MAT == 2 && R2 < 2 && n == 3) { wg_wait<2>(); mbar_arrive_warp(bars + EB_V0 * 8); }
                if (MAT != 2 && x_empty(prev) >= 0) { wg_wait<1>(); mbar_arrive_warp(bars + (EB_EMPTY + x_empty(prev)) * 8); }
            }
            const uint32_t a = sb + (MAT == 0 ? E_QT : MAT == 1 ? E_KT : E_VT) + tl_lane(TID, MAT == 0 ? 2048 : 1024) + (ONE && i >= NSEG ? (MAT == 0 ? 1024 : 6144) : 0);
            if (MAT != 2) {
                mbar_wait(bars + (EB_EMPTY + 2) * 8, par);
                if (!ONE) mbar_wait(bars + EB_MEMA * 8, par);
            } else {
                mbar_wait(bars + EB_OST * 8, par ^ 1);
            }
            wg_wait_acc<0, ONE ? 16 : 32>(d);
            TS(MAT * 128, i, 23 + MAT);
#pragma unroll
            for (int j = 0; j < (ONE ? 4 : 8); j += 2) {
                const int grp = MAT == 0 ? 2 * (j & 3) + (j >> 2) : j < 4 ? j : j + 2;
                stsm4(a + grp * 1024, pack2(d[4 * j], d[4 * j + 1]), pack2(d[4 * j + 2], d[4 * j + 3]), pack2(d[4 * j + 4], d[4 * j + 5]), pack2(d[4 * j + 6], d[4 * j + 7]));
            }
        }
        if (MAT != 2) {
            if (ONE) mbar_arrive_warp(bars + EB_STEP * 8);
            if (ONE) mbar_wait(bars + EB_MEMA * 8, par);
        } else {
            __syncwarp();
            if ((TID & 31) < 3) mbar_arrive(bars + (EB_EMPTY + (tid & 31)) * 8);
        }
    };
    auto step = [&](const int i) {
        const uint32_t par = i & 1;
        if (MAT == 2) {
            if (Q_LEAD) nbar_sync(NB_OM, K_GATE ? 384 : 256);
            else mbar_wait(bars + EB_MEM * 8, par);
        }
        float d[8];
        TS(MAT * 128, i, MAT == 2 ? 26 : 14 + MAT);
        wg_fence();
        constexpr int MID = MAT == 2 ? V_FIRST : Q_LEAD;
        if (MAT != 2) {
            static_assert(Q_LEAD >= AR_SPLIT * 4, "v relies on q for the rest");
            proj_mem<MAT, NR, 0, AR_SPLIT * 4>(d, w);
            mbar_wait(bars + EB_MEM * 8, par);
            wg_fence();
        }
        proj_mem<MAT, NR, MAT != 2 ? AR_SPLIT * 4 : 0, MID>(d, w);
        if ((MAT == 0 || (MAT == 1 && K_GATE)) && Q_LEAD) nbar_arrive(NB_OM, K_GATE ? 384 : 256);
        if (MAT == 2 && V_FIRST < 36) {
            if (V_BURST1) mbar_wait(bars + EB_FULL * 8, i == NSTEP - 1 ? par : par ^ 1);
            nbar_sync(NB_S, 256);
            wg_fence();
        }
        proj_mem<MAT, NR, MID, 36>(d, w);
        wg_commit();
        if (MAT == 0) {
            mbar_wait(bars + EB_WO * 8, 0);
            tid *= mbar_wait(bars + EB_STEP * 8, par);
            attn_mem(d, par, i, tid);
        } else if (MAT == 1) {
            tid *= mbar_wait(bars + EB_STEP * 8, par);
            const uint32_t a = pin(sb + E_KT + 4096 + tl_lane(tid, 1024));
            wg_wait_acc<0, 8>(d);
            stsm4(a, pack2(d[0], d[1]), pack2(d[2], d[3]), pack2(d[4], d[5]), pack2(d[6], d[7]));
            nbar_arrive(NB_QK, 256);
            TS(128, i, 18);
            fence_async_smem();
            nbar_sync(SX_GATE ? NB_S2 : NB_W, SX_GATE ? 256 : 128);
            float p[2][10];
            attn_x_scores(p, par, i, TID);
            attn_x_finish(p, par, i, TID, pin(P.zero));
        } else {
            const uint32_t a = pin(sb + E_VT + 4096 + tl_lane(TID, 1024));
            wg_wait_acc<0, 8>(d);
            stsm4(a, pack2(d[0], d[1]), pack2(d[2], d[3]), pack2(d[4], d[5]), pack2(d[6], d[7]));
            mbar_arrive_warp(bars + EB_KF * 8);
            TS(256, i, 16);
        }
        if (MAT == 0) {
            const int rank = cta_rank();
            uint8_t* const ar = g_ar + (i & 3) * AR_SLOT;
            uint8_t* const pm = ar + pin(ar_main(TID) + rank * (64 * AR_STR));
            uint8_t* const ps = ar + pin(ar_side(tid) + rank * (64 * AR_STR));
            const uint32_t o8 = (128 - rank * 64) * AR_STR;
            const uint64_t db = mkdesc(E_OM, 128, 2048, 0), da = mkdesc(E_WO, 1024, 1024, 1);
            if (!OX_V4) nbar_sync(NB_G, 128);
            fence_async_smem();
            TS(0, i, 6);
            if (i == NSTEP - 1) { mbar_wait_cl(bars + EB_OX * 8, par); return; }
            float y[4][8];
            wg_fence();
#pragma unroll
            for (int ks = 0; ks < 4; ks++) wg_ss16(y[3], da + (32 + ks) * 128, db + ks * 16, ks > 0);
            wg_commit();
#pragma unroll
            for (int j = 0; j < 12; j++) wg_ss16(y[j % 3], da + ((j % 3) * 8 + j / 3) * 128, db + (j / 3) * 16, j >= 3);
            wg_commit();
            wg_wait_acc<1, 8>(y[3]);
            ArWords z(y[3]);
            if (WO_R8) z.red(pm + o8, ps + o8); else z.force(P.zero);
            mbar_wait_cl(bars + EB_OX * 8, par);
            fence_async_smem();
            wg_fence();
#pragma unroll
            for (int T = 0; T < 4; T++) {
#pragma unroll
                for (int ks = T < 3 ? 4 : 0; ks < 8; ks++) wg_ss16(y[T], da + (T * 8 + ks) * 128, db + ks * 16, ks > 0);
                wg_commit();
            }
            if (V_EARLY) nbar_arrive(NB_WO, 256);
            if (!WO_R8) z.red(pm + o8, ps + o8);
            wg_wait_acc<1, 8>(y[0]); acc_ready<8>(y[1]); acc_ready<8>(y[2]);
#pragma unroll
            for (int T = 0; T < 3; T++) ArWords(y[T]).red(pm + T * 16 * AR_STR, ps + T * 16 * AR_STR);
            wg_wait_acc<0, 8>(y[3]);
            ArWords(y[3]).red(pm + 48 * AR_STR, ps + 48 * AR_STR);
            if (!V_EARLY) nbar_arrive(NB_WO, 256);
            TS(0, i, 7);
        }
    };
    auto either = [&](const int i) {
        if (__builtin_expect(USE_ONE == 2 || (USE_ONE && (i < LAG || i >= NSEG)), MAT != 2)) project(Bool<true>(), i);
        else project(Bool<false>(), i);
    };
    if (MAT != 2) {
#pragma unroll 1
        for (int i = 0; i < NSTEP; i++) {
            either(i);
            if (!USE_ONE || (USE_ONE == 1 && i >= LAG && i < NSEG)) mbar_arrive_warp(bars + EB_STEP * 8);
            step(i);
        }
    } else {
#pragma unroll 1
        for (int i = -1; i < NSTEP; i++) {
            if (i >= 0) step(i);
            if (i < NSTEP - 1) {
                either(i + 1);
                const bool one = USE_ONE == 2 || (USE_ONE && (i + 1 < LAG || i + 1 >= NSEG));
                [[maybe_unused]] const int n0 = ar_fetch<0, AR_SPLIT>(P, i, TID, bars + (EB_EMPTY + (one ? AR_VA1 : AR_VA)) * 8, bars + EB_MEM0 * 8);
                [[maybe_unused]] const int n1 = ar_fetch<AR_SPLIT, 9>(P, i, tid, bars + EB_EMPTY * 8, bars + EB_MEM * 8);
            }
        }
    }
    if (MAT == 2) { if (V_FIRST == 36) nbar_sync(NB_S, 256); nbar_sync(NB_PV, 256); }
}

__device__ __forceinline__ void engine_helper(const Params& P) {
    const int lane = threadIdx.x & 31, hw = warp_in_group(), e = blockIdx.x, rank = e & 1;
    if (hw < 3) {
        constexpr uint64_t M0 = ss_mask(0), M1 = ss_mask(1), M2 = ss_mask(2);
        const uint64_t m = hw == 0 ? M0 : hw == 1 ? M1 : M2;
        const uint32_t ws = sb + (hw == 0 ? E_WQ : hw == 1 ? E_WK : E_WV), wr = sb + E_WO + (hw == 0 ? 0 : hw == 1 ? NRQ : NRQ + NRK) * 2048;
        if (lane == 0) mbar_expect(bars + EB_WL * 8, 36 * 2048);
        __syncwarp();
        for (int ks = lane; ks < 36; ks += 32) {
            const int s = __popcll(m & ((1ull << ks) - 1));
            tma_unit(((m >> ks) & 1) ? ws + s * 2048 : wr + (ks - s) * 2048, hw == 0 ? &P.tmWq : hw == 1 ? &P.tmWk : &P.tmWv, ks, e, bars + EB_WL * 8);
        }
    }
    if (hw == 1) {
        hold_back(WO_DELAY);
        for (int u = lane; u < 36; u += 32)
            asm volatile("cp.async.bulk.prefetch.tensor.2d.L2.global [%0, {%1,%2}];"
                         :: "l"(&P.tmWo), "r"((u < 32 ? rank * 4 + (u >> 3) : 8) * 64), "r"(((e >> 1) * 8 + (u < 32 ? u & 7 : rank * 4 + (u & 3))) * 16) : "memory");
    }
    __syncwarp();
    if (hw < 2) nbar_sync(NB_T, 448);
    if (lane == 0) TG(79, 3);
    if (hw == 0) {
        if (lane == 0) {
#pragma unroll 1
            for (int n = 0; n < NSTEP; n++) {
                const uint32_t par = (n & 1) ^ 1;
                uint32_t rdy;
                do { asm volatile("ld.acquire.cta.shared.u32 %0, [%1];" : "=r"(rdy) : "r"(sb + SM_XRDY) : "memory"); } while (rdy <= n && (__nanosleep(20), true));
                fence_async_glb();
                TG(n, 30);
                const uint8_t* src = g_x + n * XIMG;
#pragma unroll
                for (int j = 0; j < 6; j++) {
                    const int f = j == 0 ? 0 : j < 4 ? 2 * j + 1 : 14 - j, blk = f < 9 ? f : f - 9, bytes = j == 0 ? 24576 : j < 4 ? 16384 : 8192;
                    if (j == 3 || j == 5) mbar_wait(bars + (j == 3 ? EB_V0 : EB_EMPTY + 1) * 8, par ^ 1);
                    else mbar_wait(bars + (j == 0 ? EB_STEP : j == 1 ? EB_QF : j == 2 ? EB_KF : EB_OFREE) * 8, par);
                    const uint32_t fb = bars + (EB_FULL + j) * 8;
                    mbar_expect(fb, bytes);
                    bulk_g2s(sb + x_slot(f), src + blk * 8192, bytes, fb);
                }
            }
        }
    } else if (hw == 1) {
        if (lane == 0) mbar_expect(bars + EB_WO * 8, 36 * 2048);
        __syncwarp();
        for (int u = lane; u < 36; u += 32)
            tma_unit(sb + E_WO + u * 2048, &P.tmWo, (e >> 1) * 8 + ((u & 7) ^ (rank * 4)), u < 32 ? rank * 4 + (u >> 3) : 8, bars + EB_WO * 8);
        __syncwarp();
        if (lane == 0) {
#pragma unroll 1
            for (int i = 0; i < NSTEP; i++) {
                mbar_wait(bars + EB_STEP * 8, i & 1);
                mbar_arrive_remote(mapa(sb, rank ^ 1) + SM_BAR + EB_PRDY * 8);
                mbar_wait(bars + EB_OST * 8, i & 1);
                fence_async_smem();
                bulk_s2g(g_o + (i & (RING - 1)) * O_BYTES + e * 8192, sb + E_R1, 8192);
                asm volatile("cp.async.bulk.commit_group;" ::: "memory");
                asm volatile("cp.async.bulk.wait_group.read 0;" ::: "memory");
                mbar_arrive(bars + EB_OFREE * 8);
                asm volatile("cp.async.bulk.wait_group 0;" ::: "memory");
                publish(F_O, i);
                TG(i, 31);
            }
        }
    } else if (hw == 2) {
        const int idx = e * 23 + lane, line = idx >> 3;
        uint8_t* z = g_ar + (line < 144 ? line * AR_STR : (line - 144) * (4 * AR_STR) + AR_STR / 2) + (idx & 7) * 16;
        if (lane < 23 && idx < 1440) { stg128(z, make_uint4(0, 0, 0, 0)); stg128(z + AR_SLOT, make_uint4(0, 0, 0, 0)); }
        __syncwarp();
        if (lane == 0) {
            publish(F_X0, B_ZERO);
            mbar_arrive(bars + EB_MEM * 8);
            flag_wait(F_X0, B_ZERO, NENG * this_launch());
            mbar_arrive(bars + EB_WO * 8);
            TG(79, 5);
        }
        __syncwarp();
#pragma unroll 1
        for (int i = 0; i < NSTEP; i++) {
            mbar_wait(bars + EB_MEM0 * 8, i & 1);
            fence_async_smem();
            if (lane == 0) mbar_arrive(bars + EB_MEMA * 8);
            if (lane < 3) mbar_expect(bars + (EB_SM + lane) * 8, lane == 0 ? 2560 : lane == 1 ? (SX_BF16 ? 3840 : 7168) : 2048);
            mbar_wait(bars + EB_MEM * 8, i & 1);
            if (lane < 23 && idx < 1440) stg128(z + ((i + 2) & 3) * AR_SLOT, make_uint4(0, 0, 0, 0));
            __syncwarp();
            if (lane == 0) { fence_gpu(); mbar_arrive(bars + EB_MEM * 8); }
            __syncwarp();
        }
    } else {
        for (int j = lane; j < 72; j += 32) asm volatile("prefetch.global.L2 [%0];" :: "l"(P.mem0 + j * 64));
        const uint32_t ep = this_launch(), t0 = timer_lo();
        if (lane == 0) {
#pragma unroll 1
            for (int n = 0; n < NSTEP; n++) {
                while ((n < NSEG && !flag_up(F_X0, n, 16 * ep)) || (n >= LAG && !flag_up(F_X1, n - LAG, 16 * ep))) {
                    __nanosleep(20);
                    if (timer_lo() - t0 > TIME_LIMIT) break;
                }
                fence_acq_gpu();
                asm volatile("st.release.cta.shared.u32 [%0], %1;" :: "r"(sb + SM_XRDY), "r"(n + 1) : "memory");
            }
        }
    }
    __syncwarp();
}

__device__ __forceinline__ void f1_fetch(const Params& P, uint32_t dst, int f0, int ks0, int n) {
    const int tid = threadIdx.x & 127, r = tid >> 3, c = (tid & 3) * 2 + ((tid >> 2) & 1);
    const bf16* src = ((c & 1) ? P.w3 : P.w1) + (size_t)(ks0 * 16 + r) * FF + f0 + (c >> 1) * 8;
    dst += r * 128 + ((c ^ (r & 7)) << 4);
#pragma unroll 1
    for (int u = 0; u < n; u++) {
        asm volatile("cp.async.cg.shared.global [%0], [%1], 16;" :: "r"(dst + u * 2048), "l"(src + (size_t)u * 16 * FF) : "memory");
        asm volatile("cp.async.commit_group; cp.async.wait_group %0;" :: "n"(F1_DEPTH) : "memory");
    }
}
constexpr int R_BACKLOG = 6;
static_assert(R_BACKLOG <= RING, "the partial sums would be overwritten");
#define F1_LEAD 0
template <int a, bool second>
__device__ __forceinline__ void f1_tile(const uint32_t (&w)[NRF][4], uint32_t ws, int b) {
    constexpr bool RF = (a == 1) == second;
    const uint32_t par = b & 1;
    float d[32];
    const uint64_t da = mkdesc(ws, 1024, 1024, 1), db = mkdesc(F_X, 16, 1024, 1);
#pragma unroll
    for (int blk = 0; blk < 9; blk++) {
        if (a == 1 && !second && blk == 0 && F1_LEAD) nbar_sync(NB_QK, 256);
        const bool wt = blk == 0 || (!second && (a == 0 || blk >= F1_LEAD));
        if (wt) { mbar_wait(bars + (FB_FULL + blk) * 8, par); wg_fence(); }
#pragma unroll
        for (int j = 0; j < 4; j++) {
            const int ks = blk * 4 + j;
            if (RF && ks < NRF) wg_rs64<0>(d, w[ks < NRF ? ks : 0], db + blk * 512 + j * 2, ks > 0);
            else wg_ss64<0>(d, da + (RF ? ks - NRF : 36 - NRF + ks) * 128, db + blk * 512 + j * 2, ks > 0);
        }
        wg_commit();
        if (a == 0 && !second && blk + 1 == F1_LEAD) nbar_arrive(NB_QK, 256);
        if (blk > 0 && second) { wg_wait<1>(); mbar_arrive_warp(bars + (FB_EMPTY + blk - 1) * 8); }
    }
    const int tid = fresh_tid(), g = (tid & 31) >> 2;
    uint8_t* dst = g_h + (b & (RING - 1)) * H_BYTES + ((fresh_bid() - NENG + (second ? 37 : 0)) * 64 + a * 32 + ((tid >> 5) & 3) * 8 + g) * 128;
    if (!second) mbar_wait(bars + FB_RACK * 8, par ^ 1);
    wg_wait_acc<0, 32>(d);
    if (second) mbar_arrive_warp(bars + (FB_EMPTY + 8) * 8);
    uint32_t h[8];
#pragma unroll
    for (int j = 0; j < 8; j++) {
        const float g0 = d[4 * j], g1 = d[4 * j + 1];
        const float e0 = 1.f + ex2(fminf(-LOG2E * g0, 60.f)), e1 = 1.f + ex2(fminf(-LOG2E * g1, 60.f));
        const float r = rcp(e0 * e1);
        h[j] = pack2(g0 * d[4 * j + 2] * (e1 * r), g1 * d[4 * j + 3] * (e0 * r));
    }
    stg128(dst + (((tid & 3) ^ g) << 4), make_uint4(h[0], h[1], h[2], h[3]));
    stg128(dst + ((((tid & 3) + 4) ^ g) << 4), make_uint4(h[4], h[5], h[6], h[7]));
    mbar_arrive_warp(bars + (second ? FB_H2 : FB_H) * 8);
}
template <int a>
__device__ __forceinline__ void f1_main(const Params& P) {
    constexpr uint32_t ws = F_W + a * (72 - NRF) * 2048;
    const int f0 = (blockIdx.x - NENG) * 128 + a * 96;
    uint32_t w[NRF][4];
    hold_back(F1_DELAY);
    f1_fetch(P, sb + ws, f0, 0, NRF);
    asm volatile("cp.async.wait_all;" ::: "memory");
    nbar_sync(NB_G + a, 128);
    {
        const uint32_t fa = sb + ws + unit_frag_addr(threadIdx.x);
#pragma unroll
        for (int u = 0; u < NRF; u++) ldsm4t(w[u], fa + u * 2048);
    }
    nbar_sync(NB_G + a, 128);
    f1_fetch(P, sb + ws, f0, NRF, 36 - NRF);
    f1_fetch(P, sb + ws + (36 - NRF) * 2048, f0 + (a ? -64 : 64), 0, 36);
    asm volatile("cp.async.wait_all;" ::: "memory");
    fence_async_smem();
    nbar_sync(NB_G + a, 128);
    if (threadIdx.x == 0) TG(79, 2);
#pragma unroll 1
    for (int b = 0; b < NSTEP; b++) {
        f1_tile<a, false>(w, ws, b);
        f1_tile<a, true>(w, ws, b);
    }
}
__device__ __forceinline__ uint32_t n_pairs(int b) { return (b < NSEG ? 16 : 0) + (b >= LAG ? 16 : 0); }
__device__ __forceinline__ void publisher(uint32_t done, uint32_t ack, int stage) {
#pragma unroll 1
    for (int b = 0; b < NSTEP; b++) {
        if (stage == F_H2) { mbar_wait(done - 8, b & 1); publish(F_H, b); }
        mbar_wait(done, b & 1);
        mbar_arrive(ack);
        TG(b, 30);
        publish(stage, b);
        TG(b, 31);
    }
}
__device__ __forceinline__ void f1_helper(const Params& P) {
    const int hw = warp_in_group();
    if ((threadIdx.x & 31) == 0) {
        const bool chain = blockIdx.x >= NENG + 16;
        if (hw == 0) {
            const uint32_t ep = this_launch();
#pragma unroll 1
            for (int b = 0; b < NSTEP; b++) {
                flag_wait(F_XF, b, n_pairs(b) * ep);
                TG(b, 29);
                const uint8_t* src = g_xf + (b & (RING - 1)) * (9 * 8192);
#pragma unroll 1
                for (int blk = 0; blk < 9; blk++) {
                    mbar_wait(bars + (FB_EMPTY + blk) * 8, (b & 1) ^ 1);
                    mbar_expect(bars + (FB_FULL + blk) * 8, 8192);
                    bulk_g2s(sb + F_X + blk * 8192, src + blk * 8192, 8192, bars + (FB_FULL + blk) * 8);
                }
            }
        } else if (hw == 1) {
            const uint32_t ep = this_launch();
            int b1 = chain ? LAG : 0, b2 = b1;
            const int bend = b1 + NSEG;
            bool second = true;
#pragma unroll 1
            for (int j = blockIdx.x < NENG + 32 ? 0 : 2 * NSEG; j < 2 * NSEG; j++) {
                [[maybe_unused]] int n = 0;
                const bool may1 = b1 < bend && b1 < b2 + R_BACKLOG;
                bool may2 = !chain || !second || !may1, any;
                do {
                    const bool r1 = flag_up(F_P1, b1, 15 * ep) & may1, r2 = flag_up(F_P2, b2, 17 * ep) & may2;
                    second = chain ? !r1 : r2;
                    any = r1 | r2;
                    may2 = !chain || !may1;
                    SPIN_CHECK(n, 20);
                } while (!any);
                fence_acq_gpu();
                TG(second ? b2 : b1, 25 + 2 * second);
                sts32(sb + F_RED + 192 + (j & 1) * 4, second ? b2 + 256 : b1);
                mbar_arrive(bars + FB_JOB * 8);
                if (second) b2++; else b1++;
                mbar_wait(bars + FB_JOB * 8, j & 1);
            }
        } else if (hw == 2) {
#pragma unroll 1
            for (int j = blockIdx.x < NENG + 32 ? 0 : 2 * NSEG; j < 2 * NSEG; j++) {
                if (j == 0) mbar_arrive(bars + FB_JOB * 8);
                mbar_wait(bars + FB_RDONE * 8, j & 1);
                const int job = lds32(sb + F_RED + 192 + (j & 1) * 4);
                mbar_arrive(bars + FB_JOB * 8);
                TG(job & 255, 23 + (job >> 8));
                if (job < 256 || !chain) publish(job < 256 ? F_XF : F_X1, job & 255);
                TG(job & 255, 26 + 2 * (job >> 8));
            }
        } else {
            hold_back(PF_DELAY);
#pragma unroll 1
            for (int j = 0; j < 24; j++) {
                const bf16* w = j >= 16 ? P.w2 : (j & 1) ? P.w3 : P.w1;
                asm volatile("cp.async.bulk.prefetch.L2.global [%0], %1;" :: "l"(w + (size_t)((j >= 16 ? j - 16 : j >> 1) * NF1 + blockIdx.x - NENG) * (2 * FF)), "r"(4 * FF) : "memory");
                hold_back(PF_PACE);
            }
            publisher(bars + FB_H2 * 8, bars + FB_RACK * 8, F_H2);
        }
    }
    __syncwarp();
}

__device__ __forceinline__ void add8(float* f, uint4 a) {
    f[0] += bf_lo(a.x); f[1] += bf_hi(a.x); f[2] += bf_lo(a.y); f[3] += bf_hi(a.y);
    f[4] += bf_lo(a.z); f[5] += bf_hi(a.z); f[6] += bf_lo(a.w); f[7] += bf_hi(a.w);
}
__device__ __forceinline__ void set8(float* f, uint4 a) {
    f[0] = bf_lo(a.x); f[1] = bf_hi(a.x); f[2] = bf_lo(a.y); f[3] = bf_hi(a.y);
    f[4] = bf_lo(a.z); f[5] = bf_hi(a.z); f[6] = bf_lo(a.w); f[7] = bf_hi(a.w);
}
__device__ __forceinline__ void ln0_rows(const Params& P, int r) {
    const int lane = threadIdx.x & 31, l = lane < 24 ? lane : 0;
    const uint4* xrow = (const uint4*)(P.x + r * DM) + l;
    uint4 xw[3];
#pragma unroll
    for (int k = 0; k < 3; k++) xw[k] = __ldg(xrow + 24 * k);
    asm volatile("prefetch.global.L2 [%0];" :: "l"(P.x + (r + 16) * DM + (lane < 9 ? lane : 0) * 64));
#pragma unroll 1
    for (int seg = 0; seg < NSEG; seg++) {
#pragma unroll 1
        for (int h = 0; h < 2; h++) {
            float f[24];
#pragma unroll
            for (int k = 0; k < 3; k++) set8(&f[k * 8], xw[k]);
            if (2 * seg + h + 1 < 2 * NSEG) {
#pragma unroll
                for (int k = 0; k < 3; k++) xw[k] = __ldg(xrow + (2 * seg + h + 1) * (16 * DM / 8) + 24 * k);
            }
            float s = 0.f, q = 0.f;
#pragma unroll
            for (int j = 0; j < 24; j++) s += f[j];
            if (lane >= 24) s = 0.f;
#pragma unroll
            for (int o = 16; o; o >>= 1) s += __shfl_xor_sync(~0u, s, o);
            const float mean = s * (1.f / DM);
#pragma unroll
            for (int j = 0; j < 24; j++) { f[j] -= mean; q += f[j] * f[j]; }
            if (lane >= 24) q = 0.f;
#pragma unroll
            for (int o = 16; o; o >>= 1) q += __shfl_xor_sync(~0u, q, o);
            const float rstd = rsqrtf(q * (1.f / DM) + 1e-5f);
            if (lane < 24) {
                uint8_t* d = g_x + seg * XIMG + (l >> 3) * 8192 + (r + 16 * h) * 128 + (((l & 7) ^ (r & 7)) << 4);
#pragma unroll
                for (int k = 0; k < 3; k++) {
                    const float* y = &f[8 * k];
                    stg128(d + k * 24576, make_uint4(pack2(y[0] * rstd, y[1] * rstd), pack2(y[2] * rstd, y[3] * rstd), pack2(y[4] * rstd, y[5] * rstd), pack2(y[6] * rstd, y[7] * rstd)));
                }
            }
        }
        __syncwarp();
        if (lane == 0 && seg == 0) TG(79, 4);
        if (lane == 0) publish(F_X0, seg);
        if (lane == 0 && seg == 0) TG(79, 5);
        __syncwarp();
    }
}

template <bool SECOND, bool CHAIN>
__device__ __forceinline__ void reduce_job(const Params& P, int b, int p, int t) {
    constexpr int NP = SECOND ? NP2 : NP1;
    const int seg = CHAIN ? b - LAG : b, lane = t & 31;
    const bool act = !(t & 1);
    const uint32_t ro = (b & (RING - 1)), po = p * (DM * 4) + t * 16, so = 2048 - t * 16 + (t >> 1) * 4;
    const int fa = (t >> 2) * 16 + (t & 3) * 2, fs = 512 + (t >> 5) * 16 + ((t >> 2) & 7) + (t & 2) * 4;
    const uint32_t row = (seg * 32 + (p & 15) * 2) * DM;
    uint8_t* const r1 = g_r1 + ro * PART + po;
    uint8_t* const r2 = g_r2 + seg * (PART / 2) + po - (CHAIN ? PART / 2 : 0);
    float f[10];
    uint4 x;
    uint32_t y;
    {
        const uint8_t* src = (SECOND ? g_p2 : g_p1) + ro * (NP * PART) + po;
        uint4 a[NP];
        uint32_t c[NP];
#pragma unroll
        for (int k = 0; k < NP; k++) { a[k] = ld_rlx128(src + k * PART); c[k] = ld_rlx(src + so + k * PART); }
        if (SECOND || CHAIN) {
            x = ld_rlx128(SECOND ? r1 : r2); y = ld_rlx((SECOND ? r1 : r2) + so);
        } else {
            const bf16* xr = P.x + row;
            const uint32_t a0 = ld_rlx(xr + fa), b0 = ld_rlx(xr + fa + 8), a1 = ld_rlx(xr + fa + DM), b1 = ld_rlx(xr + fa + DM + 8);
            const uint32_t s0 = ld_rlx(xr + (fs & ~1)), s1 = ld_rlx(xr + (fs & ~1) + DM);
            x = make_uint4(__byte_perm(a0, a1, 0x5410), __byte_perm(b0, b1, 0x5410), __byte_perm(a0, a1, 0x7632), __byte_perm(b0, b1, 0x7632));
            y = __byte_perm(s0, s1, (fs & 1) ? 0x7632 : 0x5410);
        }
        set8(f, a[0]); f[8] = bf_lo(c[0]); f[9] = bf_hi(c[0]);
#pragma unroll
        for (int k = 1; k < NP; k++) { add8(f, a[k]); f[8] += bf_lo(c[k]); f[9] += bf_hi(c[k]); }
    }
    add8(f, x);
    x = make_uint4(pack2(f[0], f[1]), pack2(f[2], f[3]), pack2(f[4], f[5]), pack2(f[6], f[7]));
    y = pack2(f[8] + bf_lo(y), f[9] + bf_hi(y));
    if (SECOND && CHAIN) {
        bf16* o = P.out + row;
        stg32(o + fa, __byte_perm(x.x, x.z, 0x5410));
        stg32(o + fa + 8, __byte_perm(x.y, x.w, 0x5410));
        stg32(o + fa + DM, __byte_perm(x.x, x.z, 0x7632));
        stg32(o + fa + DM + 8, __byte_perm(x.y, x.w, 0x7632));
        stg16(o + fs + (act ? 0 : DM), act ? y : y >> 16);
        return;
    }
    set8(f, x);
    f[8] = act ? bf_lo(y) : 0.f; f[9] = act ? 0.f : bf_hi(y);
    float st[4];
    st[0] = (f[0] + f[2]) + (f[4] + f[6]) + f[8]; st[2] = (f[0] * f[0] + f[2] * f[2]) + (f[4] * f[4] + f[6] * f[6]) + f[8] * f[8];
    st[1] = (f[1] + f[3]) + (f[5] + f[7]) + f[9]; st[3] = (f[1] * f[1] + f[3] * f[3]) + (f[5] * f[5] + f[7] * f[7]) + f[9] * f[9];
    {
        const bool u = lane & 1, v = lane & 2;
        st[0] = (u ? st[1] : st[0]) + __shfl_xor_sync(~0u, u ? st[0] : st[1], 1);
        st[2] = (u ? st[3] : st[2]) + __shfl_xor_sync(~0u, u ? st[2] : st[3], 1);
        st[0] = (v ? st[2] : st[0]) + __shfl_xor_sync(~0u, v ? st[0] : st[2], 2);
        st[0] = (st[0] + __shfl_xor_sync(~0u, st[0], 4)) + (__shfl_xor_sync(~0u, st[0], 8) + __shfl_xor_sync(~0u, st[0], 12));
        if (!(lane & 12)) sts32(sb + F_RED + (t >> 4) * 16 + (lane & 3) * 4, fu(st[0]));
    }
    nbar_sync(NB_R, 128);
#pragma unroll
    for (int k = 0; k < 8; k++) {
        const uint4 q = lds128(sb + F_RED + k * 16);
        if (k == 0) { st[0] = uf(q.x); st[1] = uf(q.y); st[2] = uf(q.z); st[3] = uf(q.w); }
        else { st[0] += uf(q.x); st[1] += uf(q.y); st[2] += uf(q.z); st[3] += uf(q.w); }
    }
    stg128(SECOND ? r2 : r1, x);
    if (act) stg32((SECOND ? r2 : r1) + so, y);
    const float m0 = st[0] * (1.f / DM), m1 = st[1] * (1.f / DM);
    const float q0 = rsqrtf(fmaxf(st[2] * (1.f / DM) - m0 * m0, 0.f) + 1e-5f), q1 = rsqrtf(fmaxf(st[3] * (1.f / DM) - m1 * m1, 0.f) + 1e-5f);
    constexpr int KB = 8192;
    uint8_t* d = (SECOND ? g_x + (b + LAG) * XIMG + (USE_ONE && b + LAG >= NSEG ? 0 : 4096) : g_xf + ro * XIMG) + p * 256;
#pragma unroll
    for (int e = 0; e < 2; e++) {
        const float m = e ? m1 : m0, q = e ? q1 : q0;
#pragma unroll
        for (int h = 0; h < 2; h++)
            stg32(d + (fa >> 6) * KB + (t & 3) * 4 + e * 128 + (((((fa >> 3) & 6) + h) ^ ((2 * p + e) & 7)) << 4), pack2((f[2 * h + e] - m) * q, (f[4 + 2 * h + e] - m) * q));
    }
    stg16(d + 8 * KB + (t & 1) * 128 + ((((fs >> 3) & 7) ^ ((2 * p + (t & 1)) & 7)) << 4) + (fs & 7) * 2, pack2(act ? (f[8] - m0) * q0 : (f[9] - m1) * q1, 0.f));
}
template <bool CHAIN>
__device__ __forceinline__ void reducer(const Params& P) {
#pragma unroll 1
    for (int j = 0; j < 2 * NSEG; j++) {
        const int t = fresh_tid() - 256, p = fresh_bid() - NENG;
        mbar_wait(bars + FB_JOB * 8, j & 1);
        const int job = lds32(sb + F_RED + 192 + (j & 1) * 4);
        if (job >= 256) reduce_job<true, CHAIN>(P, job - 256, p, t);
        else reduce_job<false, CHAIN>(P, job, p, t);
        mbar_arrive_warp(bars + FB_RDONE * 8);
    }
}

__host__ __device__ constexpr int d_rf(int u) { return u < 48 ? ((u & 3) < 2 ? (u >> 2) * 2 + (u & 1) : -1) : u == 48 ? 24 : -1; }
__host__ __device__ constexpr int d_ss(int u) { return u < 48 ? (u >> 2) * 2 + (u & 1) : u - 25; }
template <bool WIDE, int wg>
__device__ __forceinline__ void d_main() {
    constexpr int NR = WIDE ? 24 : NRD;
    uint32_t w[NR][4];
    {
        const uint32_t fa = sb + wg * (NRD * 2048) + unit_frag_addr(threadIdx.x);
        mbar_wait(bars + DB_WL * 8, 0);
#pragma unroll
        for (int u = 0; u < NR; u++) ldsm4t(w[u], fa + u * 2048);
        nbar_arrive(NB_W, 416);
        mbar_wait(bars + DB_WL * 8, 1);
        if (threadIdx.x == 0) TG(79, 2);
    }
    const uint64_t da = mkdesc(wg * ((52 - NRD) * 2048), 1024, 1024, 1);
#pragma unroll 1
    for (int b = 0; b < NSTEP; b++) {
#pragma unroll
        for (int T = 0; T < (WIDE ? 3 : 1); T++) {
            float d[32];
            constexpr int NB = WIDE ? 4 : 13;
#pragma unroll
            for (int blk = 0; blk < NB; blk++) {
                const int c = blk;
                if (T == 0 || blk == 0) mbar_wait(bars + (DB_FULL + (c & 7)) * 8, WIDE || (c & 7) >= 5 ? b & 1 : c >> 3);
                if (T == 0 || blk == 0) wg_fence();
                const uint64_t db = mkdesc(D_B + (c & 7) * 8192, 8192, 1024, 1);
#pragma unroll
                for (int j = 0; j < 4; j++) {
                    const int u = T * 16 + blk * 4 + j;
                    if (d_rf(u) >= 0) wg_rs64<1>(d, w[d_rf(u) >= 0 ? d_rf(u) : 0], db + j * 128, blk + j > 0);
                    else wg_ss64<1>(d, da + d_ss(u) * 128, db + j * 128, blk + j > 0);
                }
                wg_commit();
                if (!WIDE && blk > 0) { wg_wait<1>(); mbar_arrive_warp(bars + (DB_EMPTY + ((c - 1) & 7)) * 8); }
            }
            const int tid = fresh_tid(), t = tid & 3, ds = fresh_bid() - NENG - NF1;
            const bool w2 = ds >= 15;
            const int tile = WIDE ? wg * 3 + T : (ds % 3) * 3 + wg;
            uint8_t* dst = (w2 ? g_p2 + ((b & (RING - 1)) * NP2 + (WIDE ? ds - 25 : (ds - 15) / 3)) * PART : g_p1 + ((b & (RING - 1)) * NP1 + ds / 3) * PART)
                         + (tile * 64 + ((tid >> 5) & 3) * 16 + ((tid & 31) >> 2) * 2) * 4 + (w2 ? 4 * t : t) * (DM * 4);
            const uint32_t js = w2 ? DM * 4 : DM * 16;
            if (T == 0) mbar_wait(bars + (DB_P + 1) * 8, (b & 1) ^ 1);
            wg_wait_acc<0, 32>(d);
            if (!WIDE) mbar_arrive_warp(bars + (DB_EMPTY + ((NB - 1) & 7)) * 8);
            else if (T == 2) {
#pragma unroll
                for (int blk = 0; blk < 4; blk++) mbar_arrive_warp(bars + (DB_EMPTY + blk) * 8);
            }
#pragma unroll
            for (int j = 0; j < 8; j++) stg64(dst + (j >> 2) * (DM * 64) + (j & 3) * js, pack2(d[4 * j], d[4 * j + 1]), pack2(d[4 * j + 2], d[4 * j + 3]));
        }
        mbar_arrive_warp(bars + DB_P * 8);
    }
}
__device__ __forceinline__ void d_helper(const Params& P, int ds) {
    const int lane = threadIdx.x & 31, hw = warp_in_group();
    const bool w2 = ds >= 15, wide = ds >= 30;
    const int kr = (w2 ? ds - 15 : ds) / 3, nb = wide ? 4 : 13;
    const int blk0 = wide ? 29 + (ds - 30) * 4 : kr * (w2 ? 6 : 13), n1 = w2 ? (kr == 4 ? 5 : 6) : 13, blk1 = 37 + kr * 7 - n1;
    if (hw == 0) {
        const int nu = wide ? 48 : 52;
        hold_back(w2 ? W2_DELAY : D_DELAY);
#pragma unroll 1
        for (int ph = 0; ph < 2; ph++) {
            if (ph) nbar_sync(NB_W, 416);
            if (lane == 0) mbar_expect(bars + DB_WL * 8, (wide ? 72 : ph ? 3 * (52 - NRD) : 3 * NRD) * 2048);
            __syncwarp();
#pragma unroll 1
            for (int x = lane; x < 3 * nu; x += 32) {
                const int wg = x / nu, u = x - wg * nu, j = (wide ? u & 15 : u) >> 2;
                const int kb = !w2 ? blk0 + j : j < n1 ? (blk0 + j) * 2 : (blk1 + j - 37) * 2 + 1;
                if ((d_rf(u) < 0) == (ph != 0))
                    tma_unit(sb + (ph ? wg * (52 - NRD) + d_ss(u) : wg * NRD + d_rf(u)) * 2048, w2 ? &P.tmW2 : &P.tmWo,
                             kb * 4 + (u & 3), wide ? wg * 3 + (u >> 4) : (ds % 3) * 3 + wg, bars + DB_WL * 8);
            }
        }
        __syncwarp();
        if (lane == 0) {
            const uint32_t target = (w2 ? NF1 : NENG) * this_launch();
#pragma unroll 1
            for (int b = 0; b < NSTEP; b++) {
                flag_wait(w2 ? F_H : F_O, b, target);
                TG(b, 29);
                const uint8_t* src = (w2 ? g_h + (b & (RING - 1)) * H_BYTES : g_o + (b & (RING - 1)) * O_BYTES);
#pragma unroll 1
                for (int blk = 0; blk < nb; blk++) {
                    const int c = blk;
                    if (blk == n1) flag_wait(F_H2, b, target);
                    mbar_wait(bars + (DB_EMPTY + (c & 7)) * 8, (wide || (c & 7) >= 5 ? b & 1 : c >> 3) ^ 1);
                    mbar_expect(bars + (DB_FULL + (c & 7)) * 8, 8192);
                    bulk_g2s(sb + D_B + (c & 7) * 8192, src + (blk + (blk < n1 ? blk0 : blk1)) * 8192, 8192, bars + (DB_FULL + (c & 7)) * 8);
                }
            }
        }
    } else if (hw == 1 && lane == 0) {
        publisher(bars + DB_P * 8, bars + (DB_P + 1) * 8, w2 ? F_P2 : F_P1);
    }
    __syncwarp();
}

__device__ __forceinline__ void sign_off() { mbar_arrive_warp(sb + SM_DONE); }
__device__ __forceinline__ void sign_off_helper() {
    if (warp_in_group() < 3) { sign_off(); return; }
    uint32_t ok;
    const uint32_t t0 = timer_lo(), ep = this_launch();
    do {
        __nanosleep(100);
        asm volatile("{.reg .pred p; mbarrier.test_wait.parity.shared::cta.b64 p, [%1], 0; selp.u32 %0, 1, 0, p;}" : "=r"(ok) : "r"(sb + SM_DONE) : "memory");
    } while (!ok && timer_lo() - t0 < TIME_LIMIT);
    if (!ok || (sb & 0x3ffff) != SM_ORG) __trap();
    if (fresh_tid() == NTHREADS - 32) { g_epoch[fresh_bid()][0] = ep; TG(79, 1); }
    __syncwarp();
}

__global__ void __cluster_dims__(2, 1, 1) __launch_bounds__(NTHREADS, 1) fused_kernel(const __grid_constant__ Params P) {
    const int wg = __shfl_sync(~0u, threadIdx.x >> 7, 0);
    const int bid = blockIdx.x;
    if (threadIdx.x >= NTHREADS - 32) sts32(sb + SM_ONES + (threadIdx.x & 31) * 4, 0x3f803f80u);
    if (threadIdx.x == 0) {
        TG(79, 0);
        mbar_init(sb + SM_DONE, 15);
        sts32(sb + SM_XRDY, 0);
        if (bid < NENG) {
            for (int i = 0; i < 9; i++) mbar_init(bars + (EB_FULL + i) * 8, i < 6 ? 1 : 12);
            mbar_init(bars + EB_V0 * 8, 4); mbar_init(bars + EB_WL * 8, 3); mbar_init(bars + EB_WO * 8, 2); mbar_init(bars + EB_STEP * 8, 8);
            mbar_init(bars + EB_SM * 8, 1); mbar_init(bars + EB_SX * 8, 1); mbar_init(bars + EB_OX * 8, 1);
            mbar_init(bars + EB_QF * 8, 4); mbar_init(bars + EB_KF * 8, 8); mbar_init(bars + EB_CONS * 8, 4); mbar_init(bars + EB_OST * 8, 4);
            mbar_init(bars + EB_OFREE * 8, 1); mbar_init(bars + EB_MEM0 * 8, 4); mbar_init(bars + EB_MEMA * 8, 1); mbar_init(bars + EB_MEM * 8, 5); mbar_init(bars + EB_PRDY * 8, 1);
        } else if (bid < NENG + NF1) {
            for (int i = 0; i < 9; i++) { mbar_init(bars + (FB_FULL + i) * 8, 1); mbar_init(bars + (FB_EMPTY + i) * 8, 8); }
            mbar_init(bars + FB_H * 8, 8); mbar_init(bars + FB_H2 * 8, 8); mbar_init(bars + FB_RACK * 8, 1); mbar_init(bars + FB_JOB * 8, 2); mbar_init(bars + FB_RDONE * 8, 4);
        } else {
            for (int i = 0; i < 8; i++) { mbar_init(bars + (DB_FULL + i) * 8, 1); mbar_init(bars + (DB_EMPTY + i) * 8, 12); }
            mbar_init(bars + DB_WL * 8, 1); mbar_init(bars + DB_P * 8, 12); mbar_init(bars + (DB_P + 1) * 8, 1);
        }
        asm volatile("fence.mbarrier_init.release.cluster;" ::: "memory");
    }
    __syncthreads();
    asm volatile("barrier.cluster.arrive.relaxed.aligned; barrier.cluster.wait.aligned;" ::: "memory");
    if (bid < NENG) {
        if (wg == 0) { reg_inc<REGQ>(); engine_main<0>(P); sign_off(); cluster_sync_all(); }
        else if (wg == 1) { reg_inc<REGK>(); engine_main<1>(P); sign_off(); cluster_sync_all(); }
        else if (wg == 2) { reg_inc<REGV>(); engine_main<2>(P); sign_off(); cluster_sync_all(); }
        else { reg_dec<24>(); engine_helper(P); sign_off_helper(); cluster_sync_all(); }
    } else if (bid < NENG + NF1) {
        if (wg < 2) {
            reg_inc<REGF>();
            if (wg == 0) f1_main<0>(P); else f1_main<1>(P);
            sign_off();
        } else if (wg == 2) {
            reg_dec<488 - 2 * REGF>();
            if (bid >= NENG + 32) ln0_rows(P, (bid - NENG - 32) * 4 + warp_in_group());
            else if (bid < NENG + 16) reducer<false>(P);
            else reducer<true>(P);
            sign_off();
        } else {
            reg_dec<24>();
            f1_helper(P);
            sign_off_helper();
        }
    } else {
        const int ds = bid - NENG - NF1;
        if (wg < 3) {
            reg_inc<160>();
            if (ds < 30) { if (wg == 0) d_main<false, 0>(); else if (wg == 1) d_main<false, 1>(); else d_main<false, 2>(); }
            else { if (wg == 0) d_main<true, 0>(); else if (wg == 1) d_main<true, 1>(); else d_main<true, 2>(); }
            sign_off();
        } else {
            reg_dec<32>();
            d_helper(P, ds);
            sign_off_helper();
        }
    }
}

typedef CUresult (*EncodeFn)(CUtensorMap*, CUtensorMapDataType, cuuint32_t, void*, const cuuint64_t*, const cuuint64_t*,
                             const cuuint32_t*, const cuuint32_t*, CUtensorMapInterleave, CUtensorMapSwizzle,
                             CUtensorMapL2promotion, CUtensorMapFloatOOBfill);

void make_map(EncodeFn enc, CUtensorMap* m, const void* p, int rows, int cols) {
    cuuint64_t dims[2] = {(cuuint64_t)cols, (cuuint64_t)rows};
    cuuint64_t strides[1] = {(cuuint64_t)cols * 2};
    cuuint32_t box[2] = {64, 16};
    cuuint32_t es[2] = {1, 1};
    enc(m, CU_TENSOR_MAP_DATA_TYPE_BFLOAT16, 2, (void*)p, dims, strides, box, es, CU_TENSOR_MAP_INTERLEAVE_NONE,
        CU_TENSOR_MAP_SWIZZLE_128B, CU_TENSOR_MAP_L2_PROMOTION_L2_128B, CU_TENSOR_MAP_FLOAT_OOB_FILL_NONE);
}

}

extern "C" void kernel_launch(void* const* d_in, const int* in_sizes, int n_in, void* d_out, int out_size) {
    (void)in_sizes; (void)n_in; (void)out_size;
    static EncodeFn enc = nullptr;
    if (!enc) {
        void* fn = nullptr;
        cudaDriverEntryPointQueryResult qr;
        cudaGetDriverEntryPoint("cuTensorMapEncodeTiled", &fn, cudaEnableDefault, &qr);
        enc = (EncodeFn)fn;
        cudaFuncSetAttribute(fused_kernel, cudaFuncAttributeMaxDynamicSharedMemorySize, SM_TOTAL);
    }
    Params P;
    make_map(enc, &P.tmWq, d_in[2], DM, 4096);
    make_map(enc, &P.tmWk, d_in[3], DM, 4096);
    make_map(enc, &P.tmWv, d_in[4], DM, 4096);
    make_map(enc, &P.tmWo, d_in[5], 4096, DM);
    make_map(enc, &P.tmW2, d_in[10], FF, DM);
    P.x = (const bf16*)d_in[0];
    P.mem0 = (const bf16*)d_in[1];
    P.w1 = (const bf16*)d_in[8];
    P.w3 = (const bf16*)d_in[9];
    P.w2 = (const bf16*)d_in[10];
    P.out = (bf16*)d_out;
    P.zero = 0;
    fused_kernel<<<NCTA, NTHREADS, SM_TOTAL>>>(P);
}
```

```cpp
#include <cuda_runtime.h>
#include <cuda_bf16.h>
#include <cuda.h>
#include <stdint.h>

typedef __nv_bfloat16 bf16;

namespace {

constexpr int DM = 576, FF = 4608, NSEG = 64;
constexpr int NENG = 64, NF1 = 36, ND = 32, NCTA = NENG + NF1 + ND;
constexpr int NTHREADS = 512;
#define LAG 7
#define RING 16
static_assert(RING >= 2 * LAG + 2, "ring too short");
#define USE_ONE 1
constexpr int NSTEP = NSEG + LAG;
constexpr int NJOB = 2 * NSEG;
__device__ __forceinline__ int job_chain(int q) { return q < LAG ? 0 : q < NJOB - LAG ? (q - LAG) & 1 : 1; }
__device__ __forceinline__ int job_batch(int q) { return q < LAG ? q : q < NJOB - LAG ? (q + LAG) >> 1 : q - NSEG + LAG; }
__device__ __forceinline__ int first_job(int b) { return b < LAG ? b : b < NSEG ? 2 * b - LAG : b + NSEG - LAG; }

enum { F_X0 = 0, F_X1, F_O, F_P1, F_XF, F_H, F_P2, F_H2, F_COUNT };
constexpr int B_ZERO = 95;
__device__ uint32_t g_flag[F_COUNT][NJOB + 4][8];
__device__ uint32_t g_epoch[NCTA][8];
constexpr int XIMG = 9 * 8192;
constexpr int XF_BYTES = 9 * 4096;
constexpr int O_BYTES = 65 * 4096;
constexpr int H_BYTES = 72 * 4096;
constexpr int PART = 16 * DM * 4;
constexpr int NP1 = 5, NP2 = 6;
__device__ __align__(1024) uint8_t g_x[NSTEP * XIMG];
__device__ __align__(1024) uint8_t g_xf[RING * XF_BYTES];
__device__ __align__(1024) uint8_t g_o[RING * O_BYTES];
__device__ __align__(1024) uint8_t g_h[RING * H_BYTES];
__device__ __align__(1024) uint8_t g_p1[RING * NP1 * PART];
__device__ __align__(1024) uint8_t g_p2[RING * NP2 * PART];
__device__ __align__(1024) uint8_t g_r1[RING * PART];
__device__ __align__(1024) uint8_t g_r2[NSEG * PART];
#define AR_STR 4352
constexpr int AR_SLOT = 144 * AR_STR;
__device__ __align__(1024) uint8_t g_ar[4 * AR_SLOT];

struct Params {
    CUtensorMap tmWq, tmWk, tmWv, tmWo, tmW2;
    const bf16 *x, *mem0, *w1, *w3, *w2;
    bf16* out;
    uint32_t zero;
};

constexpr uint32_t SM_ORG = 1024;
extern __shared__ __align__(1024) uint8_t smem_raw[];
#define sb ((uint32_t)__cvta_generic_to_shared(smem_raw))
#define bars (sb + SM_BAR)
constexpr int SM_BAR = 231936;
constexpr int SM_TOTAL = SM_BAR + 512;
#define NRQ 25
#define NRK 25
#define NRV 25
#define REGQ 160
#define REGK 168
#define REGV 160
constexpr int E_WQ = 0;
constexpr int E_WK = E_WQ + (36 - NRQ) * 2048;
constexpr int E_WV = E_WK + (36 - NRK) * 2048;
constexpr int E_WO = E_WV + (36 - NRV) * 2048;
constexpr int E_MEM = E_WO + 36 * 2048;
constexpr int E_R0 = E_MEM + 18432;
constexpr int E_R2 = E_R0 + 8192, E_R3 = E_R2 + 8192, E_R1 = E_R3 + 8192;
constexpr int E_SX = E_R1;
constexpr int E_QT = E_R1 + 8192;
constexpr int E_KT = E_QT + 8192;
constexpr int E_VT = E_KT + 10240;
constexpr int E_OM = E_VT + 10240;
constexpr int E_QM = E_OM + 4096;
constexpr int E_SR = E_QM + 2048;
constexpr int E_SL = E_SR + 2560;
constexpr int E_END = E_SL + 2048;
static_assert(E_END <= SM_BAR, "engine smem overflow");
static_assert(E_WO + (NRQ + NRK + NRV) * 2048 <= E_OM, "weight staging: the peer writes there without asking");
enum {
    EB_FULL = 0  , EB_EMPTY = 6  , EB_V0 = 9, EB_WL, EB_WO, EB_STEP, EB_SM, EB_SX, EB_OX,
    EB_QF, EB_KF, EB_CONS, EB_OST, EB_OFREE, EB_MEM0, EB_MEMA, EB_MEM, EB_PRDY
};
enum { NB_G = 1, NB_LEAD, NB_QK, NB_S, NB_OM, NB_W, NB_R, NB_T, NB_PV, NB_WO, NB_V, NB_KT, NB_S2, NB_VL };
constexpr int NB_VL2 = NB_LEAD;
constexpr int REGF = 208, NRF = 41;
constexpr int F_W = 0;
constexpr int F_X = 2 * (72 - NRF) * 2048;
constexpr int F_RED = F_X + 2 * XF_BYTES;
static_assert(F_RED + 512 <= SM_BAR && 2 * NRF * 2048 <= F_RED, "F1 smem overflow");
enum { FB_FULL = 0  , FB_EMPTY = 6  , FB_H = 8, FB_H2, FB_RACK, FB_JOB, FB_RDONE };
constexpr int D_STR = 29, D_STR2 = 31;
static_assert(3 * D_STR * 2048 + 13 * 4096 <= SM_BAR && 3 * D_STR2 * 2048 + 7 * 4096 <= SM_BAR, "D smem overflow");
enum { DB_FULL = 0, DB_EMPTY = 4, DB_WL = 8, DB_P };
constexpr int SM_DONE = SM_BAR + 248, SM_XRDY = SM_BAR + 376, SM_ONES = SM_BAR + 384;
constexpr uint32_t TIME_LIMIT = 2000000000u;

#define SPIN_CHECK(n, code)

#define TS(thr, step, k)
#define TX(thr, k)
#define TG(step, k)
#define PROF_INC(n, k)

#define jitter()
__device__ __forceinline__ uint32_t mapa(uint32_t a, uint32_t r) {
    uint32_t o; asm("mapa.shared::cluster.u32 %0, %1, %2;" : "=r"(o) : "r"(a), "r"(r)); return o;
}
__device__ __forceinline__ void mbar_init(uint32_t b, uint32_t cnt) {
    asm volatile("mbarrier.init.shared::cta.b64 [%0], %1;" :: "r"(b), "r"(cnt) : "memory");
}
__device__ __forceinline__ void mbar_arrive(uint32_t b) {
    jitter();
    asm volatile("mbarrier.arrive.shared::cta.b64 _, [%0];" :: "r"(b) : "memory");
}
__device__ __forceinline__ void mbar_arrive_warp(uint32_t b) {
    jitter();
    asm volatile("{.reg .pred p; bar.warp.sync -1; elect.sync _|p, -1; @p mbarrier.arrive.shared::cta.b64 _, [%0];}" :: "r"(b) : "memory");
}
__device__ __forceinline__ void mbar_arrive_remote(uint32_t b) {
    asm volatile("fence.release.sync_restrict::shared::cta.cluster; mbarrier.arrive.relaxed.cluster.shared::cluster.b64 _, [%0];" :: "r"(b) : "memory");
}
__device__ __forceinline__ void mbar_expect(uint32_t b, uint32_t bytes) {
    asm volatile("mbarrier.arrive.expect_tx.shared::cta.b64 _, [%0], %1;" :: "r"(b), "r"(bytes) : "memory");
}
__device__ __forceinline__ uint32_t mbar_wait(uint32_t b, uint32_t par) {
    uint32_t ok; [[maybe_unused]] int n = 0;
    jitter();
    while (true) {
        asm volatile("{.reg .pred p; mbarrier.try_wait.parity.shared::cta.b64 p, [%1], %2; selp.u32 %0, 1, 0, p;}"
                     : "=r"(ok) : "r"(b), "r"(par) : "memory");
        if (ok) break;
        SPIN_CHECK(n, 1000 + ((b & 511) >> 3));
    }
    return ok;
}
__device__ __forceinline__ bool mbar_test(uint32_t b, uint32_t par) {
    uint32_t ok;
    asm volatile("{.reg .pred p; mbarrier.test_wait.parity.shared::cta.b64 p, [%1], %2; selp.u32 %0, 1, 0, p;}" : "=r"(ok) : "r"(b), "r"(par) : "memory");
    return ok;
}
__device__ __forceinline__ void mbar_wait_cl(uint32_t b, uint32_t par) {
    uint32_t ok; [[maybe_unused]] int n = 0;
    jitter();
    while (true) {
        asm volatile("{.reg .pred p; mbarrier.try_wait.parity.relaxed.cluster.shared::cta.b64 p, [%1], %2; selp.u32 %0, 1, 0, p;}"
                     : "=r"(ok) : "r"(b), "r"(par) : "memory");
        if (ok) break;
        SPIN_CHECK(n, 1000 + ((b & 511) >> 3));
    }
    asm volatile("fence.acquire.sync_restrict::shared::cluster.cluster;" ::: "memory");
}
__device__ __forceinline__ void nbar_sync(int id, int n) { jitter(); asm volatile("bar.sync %0, %1;" :: "r"(id), "r"(n) : "memory"); }
__device__ __forceinline__ void nbar_arrive(int id, int n) { jitter(); asm volatile("bar.arrive %0, %1;" :: "r"(id), "r"(n) : "memory"); }
__device__ __forceinline__ void cluster_sync_all() {
    asm volatile("barrier.cluster.arrive.release.aligned; barrier.cluster.wait.acquire.aligned;" ::: "memory");
}
__device__ __forceinline__ void fence_async_smem() { asm volatile("fence.proxy.async.shared::cta;" ::: "memory"); }
__device__ __forceinline__ void fence_async_glb() { asm volatile("fence.proxy.async.global;" ::: "memory"); }
__device__ __forceinline__ void fence_rel_gpu() { asm volatile("fence.release.gpu;" ::: "memory"); }
__device__ __forceinline__ void fence_acq_gpu() { asm volatile("fence.acquire.gpu;" ::: "memory"); }
__device__ __forceinline__ void fence_gpu() { asm volatile("fence.acq_rel.gpu;" ::: "memory"); }
__device__ __forceinline__ int fresh_tid() { int t; asm volatile("mov.u32 %0, %%tid.x;" : "=r"(t)); return t; }
__device__ __forceinline__ int fresh_bid() { int t; asm volatile("mov.u32 %0, %%ctaid.x;" : "=r"(t)); return t; }
__device__ __forceinline__ uint32_t pin(uint32_t v) { asm volatile("" : "+r"(v)); return v; }
__device__ __forceinline__ int warp_in_group() { return __shfl_sync(~0u, (fresh_tid() >> 5) & 3, 0); }
__device__ __forceinline__ int cta_rank() { int t; asm volatile("mov.u32 %0, %%cluster_ctarank;" : "=r"(t)); return t; }
__device__ __forceinline__ uint32_t timer_lo() { uint32_t t; asm volatile("mov.u32 %0, %%globaltimer_lo;" : "=r"(t)); return t; }
__device__ __forceinline__ uint32_t keep(uint32_t v) { return __shfl_xor_sync(~0u, v, 0); }
__device__ __forceinline__ void red_add_u32(uint32_t* p, uint32_t v) {
    asm volatile("red.relaxed.gpu.global.add.u32 [%0], %1;" :: "l"(p), "r"(v) : "memory");
}
__device__ __forceinline__ uint32_t ld_rlx(const void* p) {
    uint32_t v; asm volatile("ld.relaxed.gpu.global.u32 %0, [%1];" : "=r"(v) : "l"(p) : "memory"); return v;
}
__device__ __forceinline__ uint2 ld_rlx64(const void* p) {
    uint2 v; asm volatile("ld.relaxed.gpu.global.v2.u32 {%0,%1}, [%2];" : "=r"(v.x), "=r"(v.y) : "l"(p) : "memory"); return v;
}
__device__ __forceinline__ uint4 ld_rlx128(const void* p) {
    uint4 v;
    asm volatile("ld.relaxed.gpu.global.v4.u32 {%0,%1,%2,%3}, [%4];" : "=r"(v.x), "=r"(v.y), "=r"(v.z), "=r"(v.w) : "l"(p) : "memory");
    return v;
}
__device__ __forceinline__ void stg128(void* p, uint4 v) {
    asm volatile("st.global.v4.b32 [%0], {%1,%2,%3,%4};" :: "l"(p), "r"(v.x), "r"(v.y), "r"(v.z), "r"(v.w) : "memory");
}
__device__ __forceinline__ void stg64(void* p, uint32_t a, uint32_t b) {
    asm volatile("st.global.v2.b32 [%0], {%1,%2};" :: "l"(p), "r"(a), "r"(b) : "memory");
}
__device__ __forceinline__ void stg16(void* p, uint32_t a) { asm volatile("st.global.b16 [%0], %1;" :: "l"(p), "h"((uint16_t)a) : "memory"); }
__device__ __forceinline__ void stg32(void* p, uint32_t a) { asm volatile("st.global.b32 [%0], %1;" :: "l"(p), "r"(a) : "memory"); }
__device__ __forceinline__ void st_async128(uint32_t a, uint32_t x, uint32_t y, uint32_t z, uint32_t w, uint32_t mb) {
    asm volatile("st.async.shared::cluster.mbarrier::complete_tx::bytes.v4.b32 [%0], {%1,%2,%3,%4}, [%5];"
                 :: "r"(a), "r"(x), "r"(y), "r"(z), "r"(w), "r"(mb) : "memory");
}
__device__ __forceinline__ void st_async64(uint32_t a, uint32_t x, uint32_t y, uint32_t mb) {
    asm volatile("st.async.shared::cluster.mbarrier::complete_tx::bytes.v2.b32 [%0], {%1,%2}, [%3];"
                 :: "r"(a), "r"(x), "r"(y), "r"(mb) : "memory");
}
__device__ __forceinline__ void sts128(uint32_t a, uint32_t x, uint32_t y, uint32_t z, uint32_t w) {
    asm volatile("st.shared.v4.b32 [%0], {%1,%2,%3,%4};" :: "r"(a), "r"(x), "r"(y), "r"(z), "r"(w) : "memory");
}
__device__ __forceinline__ void sts32(uint32_t a, uint32_t v) { asm volatile("st.shared.b32 [%0], %1;" :: "r"(a), "r"(v) : "memory"); }
__device__ __forceinline__ uint4 lds128(uint32_t a) {
    uint4 v; asm volatile("ld.shared.v4.b32 {%0,%1,%2,%3}, [%4];" : "=r"(v.x), "=r"(v.y), "=r"(v.z), "=r"(v.w) : "r"(a) : "memory"); return v;
}
__device__ __forceinline__ uint2 lds64(uint32_t a) {
    uint2 v; asm volatile("ld.shared.v2.b32 {%0,%1}, [%2];" : "=r"(v.x), "=r"(v.y) : "r"(a) : "memory"); return v;
}
__device__ __forceinline__ uint32_t lds32(uint32_t a) {
    uint32_t v; asm volatile("ld.shared.b32 %0, [%1];" : "=r"(v) : "r"(a) : "memory"); return v;
}
__device__ __forceinline__ void bulk_g2s(uint32_t dst, const void* src, uint32_t bytes, uint32_t mb) {
    asm volatile("cp.async.bulk.shared::cluster.global.mbarrier::complete_tx::bytes [%0], [%1], %2, [%3];"
                 :: "r"(dst), "l"(src), "r"(bytes), "r"(mb) : "memory");
}
__device__ __forceinline__ void bulk_s2g(void* dst, uint32_t src, uint32_t bytes) {
    asm volatile("cp.async.bulk.global.shared::cta.bulk_group [%0], [%1], %2;" :: "l"(dst), "r"(src), "r"(bytes) : "memory");
}
__device__ __forceinline__ void bulk_s2peer(uint32_t dst, uint32_t src, uint32_t bytes, uint32_t mb) {
    asm volatile("cp.async.bulk.shared::cluster.shared::cta.mbarrier::complete_tx::bytes [%0], [%1], %2, [%3];"
                 :: "r"(dst), "r"(src), "r"(bytes), "r"(mb) : "memory");
}
__device__ __forceinline__ void tma_unit(uint32_t dst, const CUtensorMap* tm, int kstep, int mgroup, uint32_t mb) {
    asm volatile("cp.async.bulk.tensor.2d.shared::cluster.global.mbarrier::complete_tx::bytes [%0], [%1, {%2,%3}], [%4];"
                 :: "r"(dst), "l"(tm), "r"(mgroup * 64), "r"(kstep * 16), "r"(mb) : "memory");
}
__device__ __forceinline__ void ldsm4(uint32_t* r, uint32_t a) {
    asm volatile("ldmatrix.sync.aligned.m8n8.x4.shared.b16 {%0,%1,%2,%3}, [%4];"
                 : "=r"(r[0]), "=r"(r[1]), "=r"(r[2]), "=r"(r[3]) : "r"(a) : "memory");
}
__device__ __forceinline__ void ldsm4t(uint32_t* r, uint32_t a) {
    asm volatile("ldmatrix.sync.aligned.m8n8.x4.trans.shared.b16 {%0,%1,%2,%3}, [%4];"
                 : "=r"(r[0]), "=r"(r[1]), "=r"(r[2]), "=r"(r[3]) : "r"(a) : "memory");
}
__device__ __forceinline__ void stsm4(uint32_t a, uint32_t r0, uint32_t r1, uint32_t r2, uint32_t r3) {
    asm volatile("stmatrix.sync.aligned.m8n8.x4.shared.b16 [%0], {%1,%2,%3,%4};" :: "r"(a), "r"(r0), "r"(r1), "r"(r2), "r"(r3) : "memory");
}
__device__ __forceinline__ void stsm4t(uint32_t a, uint32_t r0, uint32_t r1, uint32_t r2, uint32_t r3) {
    asm volatile("stmatrix.sync.aligned.m8n8.x4.trans.shared.b16 [%0], {%1,%2,%3,%4};" :: "r"(a), "r"(r0), "r"(r1), "r"(r2), "r"(r3) : "memory");
}
__device__ __forceinline__ uint32_t pack2(float lo, float hi) {
    uint32_t d; asm("cvt.rn.bf16x2.f32 %0, %1, %2;" : "=r"(d) : "f"(hi), "f"(lo)); return d;
}
__device__ __forceinline__ float bf_lo(uint32_t w) { return __uint_as_float(w << 16); }
__device__ __forceinline__ float bf_hi(uint32_t w) { return __uint_as_float(w & 0xffff0000u); }
__device__ __forceinline__ float ex2(float x) { float y; asm("ex2.approx.ftz.f32 %0, %1;" : "=f"(y) : "f"(x)); return y; }
__device__ __forceinline__ float rcp(float x) { float y; asm("rcp.approx.ftz.f32 %0, %1;" : "=f"(y) : "f"(x)); return y; }
__device__ __forceinline__ uint32_t fu(float x) { return __float_as_uint(x); }
__device__ __forceinline__ float uf(uint32_t x) { return __uint_as_float(x); }
__device__ __forceinline__ void mma16816(float* d, const uint32_t* a, uint32_t b0, uint32_t b1) {
    asm volatile("mma.sync.aligned.m16n8k16.row.col.f32.bf16.bf16.f32 {%0,%1,%2,%3}, {%4,%5,%6,%7}, {%8,%9}, {%0,%1,%2,%3};"
                 : "+f"(d[0]), "+f"(d[1]), "+f"(d[2]), "+f"(d[3]) : "r"(a[0]), "r"(a[1]), "r"(a[2]), "r"(a[3]), "r"(b0), "r"(b1));
}
__device__ __forceinline__ void mma1688(float* d, uint32_t a0, uint32_t a1, uint32_t b0) {
    asm volatile("mma.sync.aligned.m16n8k8.row.col.f32.bf16.bf16.f32 {%0,%1,%2,%3}, {%4,%5}, {%6}, {%0,%1,%2,%3};"
                 : "+f"(d[0]), "+f"(d[1]), "+f"(d[2]), "+f"(d[3]) : "r"(a0), "r"(a1), "r"(b0));
}
template <int N> __device__ __forceinline__ void reg_inc() { asm volatile("setmaxnreg.inc.sync.aligned.u32 %0;" :: "n"(N)); }
template <int N> __device__ __forceinline__ void reg_dec() { asm volatile("setmaxnreg.dec.sync.aligned.u32 %0;" :: "n"(N)); }

__device__ __forceinline__ uint64_t mkdesc(uint32_t addr, uint32_t lbo, uint32_t sbo, uint32_t swz) {
    return (uint64_t)((addr + SM_ORG) >> 4) | ((uint64_t)(lbo >> 4) << 16) | ((uint64_t)(sbo >> 4) << 32) | ((uint64_t)swz << 62);
}
__device__ __forceinline__ void wg_fence() { asm volatile("wgmma.fence.sync.aligned;" ::: "memory"); }
__device__ __forceinline__ void wg_commit() { asm volatile("wgmma.commit_group.sync.aligned;" ::: "memory"); }
template <int N> __device__ __forceinline__ void wg_wait() { asm volatile("wgmma.wait_group.sync.aligned %0;" :: "n"(N) : "memory"); }
template <int M> __device__ __forceinline__ void acc_ready(float* d) {
#pragma unroll
    for (int j = 0; j < M; j++) asm volatile("" : "+f"(d[j]) :: "memory");
}
template <int N, int M> __device__ __forceinline__ void wg_wait_acc(float* d) { wg_wait<N>(); acc_ready<M>(d); }

#define F8(c, d, o) c(d[o]), c(d[o + 1]), c(d[o + 2]), c(d[o + 3]), c(d[o + 4]), c(d[o + 5]), c(d[o + 6]), c(d[o + 7])
#define R8L "%0,%1,%2,%3,%4,%5,%6,%7"
#define R16L R8L ",%8,%9,%10,%11,%12,%13,%14,%15"
#define R32L R16L ",%16,%17,%18,%19,%20,%21,%22,%23,%24,%25,%26,%27,%28,%29,%30,%31"
#define R40L R32L ",%32,%33,%34,%35,%36,%37,%38,%39"
#define WG_BOTH(TXT_PRE, TXT_POST, OUTS, ...)                                                   \
    if (acc) asm volatile(TXT_PRE "1" TXT_POST : OUTS("+f") : __VA_ARGS__);                     \
    else asm volatile(TXT_PRE "0" TXT_POST : OUTS("=f") : __VA_ARGS__)
#define O8(c) F8(c, d, 0)
#define O16(c) F8(c, d, 0), F8(c, d, 8)
#define O32(c) O16(c), F8(c, d, 16), F8(c, d, 24)
#define O40(c) O32(c), F8(c, d, 32)
#define WGM(n) "wgmma.mma_async.sync.aligned.m64n" #n "k16.f32.bf16.bf16 "
__device__ __forceinline__ void wg_rs16(float* d, const uint32_t* a, uint64_t db, bool acc) {
    WG_BOTH(WGM(16) "{" R8L "}, {%8,%9,%10,%11}, %12, ", ", 1, 1, 1;", O8, "r"(a[0]), "r"(a[1]), "r"(a[2]), "r"(a[3]), "l"(db));
}
__device__ __forceinline__ void wg_ss16(float* d, uint64_t da, uint64_t db, bool acc) {
    WG_BOTH(WGM(16) "{" R8L "}, %8, %9, ", ", 1, 1, 1, 1;", O8, "l"(da), "l"(db));
}
__device__ __forceinline__ void wg_rs8(float* d, const uint32_t* a, uint64_t db, bool acc) {
#define O4(c) c(d[0]), c(d[1]), c(d[2]), c(d[3])
    WG_BOTH(WGM(8) "{%0,%1,%2,%3}, {%4,%5,%6,%7}, %8, ", ", 1, 1, 0;", O4, "r"(a[0]), "r"(a[1]), "r"(a[2]), "r"(a[3]), "l"(db));
}
template <int TB = 0> __device__ __forceinline__ void wg_rs32(float* d, const uint32_t* a, uint64_t db, bool acc) {
    WG_BOTH(WGM(32) "{" R16L "}, {%16,%17,%18,%19}, %20, ", ", 1, 1, %21;", O16, "r"(a[0]), "r"(a[1]), "r"(a[2]), "r"(a[3]), "l"(db), "n"(TB));
}
template <int TB = 0> __device__ __forceinline__ void wg_ss32(float* d, uint64_t da, uint64_t db, bool acc) {
    WG_BOTH(WGM(32) "{" R16L "}, %16, %17, ", ", 1, 1, 1, %18;", O16, "l"(da), "l"(db), "n"(TB));
}
template <int TB> __device__ __forceinline__ void wg_rs64(float* d, const uint32_t* a, uint64_t db, bool acc) {
    WG_BOTH(WGM(64) "{" R32L "}, {%32,%33,%34,%35}, %36, ", ", 1, 1, %37;", O32, "r"(a[0]), "r"(a[1]), "r"(a[2]), "r"(a[3]), "l"(db), "n"(TB));
}
template <int TB> __device__ __forceinline__ void wg_ss64(float* d, uint64_t da, uint64_t db, bool acc) {
    WG_BOTH(WGM(64) "{" R32L "}, %32, %33, ", ", 1, 1, 1, %34;", O32, "l"(da), "l"(db), "n"(TB));
}
__device__ __forceinline__ void wg_ss80(float* d, uint64_t da, uint64_t db, bool acc) {
    WG_BOTH(WGM(80) "{" R40L "}, %40, %41, ", ", 1, 1, 1, 1;", O40, "l"(da), "l"(db));
}

constexpr float SM_SCALE = 0.08838834764831845f;
constexpr float LOG2E = 1.4426950408889634f;

#define WO_DELAY 3000
#define D_DELAY 7000
#define F1_DELAY 7000
#define W2_DELAY 16500
#define F1_DEPTH 30
#define PF_DELAY 6000
#define PF_PACE 400
__device__ __forceinline__ void hold_back(uint32_t ns) {
    const uint32_t t0 = timer_lo();
    while (timer_lo() - t0 < ns) __nanosleep(50);
}

__device__ __forceinline__ uint32_t* flag_ptr(int stage, int b) { return &g_flag[stage][b][0]; }
__device__ __forceinline__ uint32_t this_launch() { return ld_rlx(&g_epoch[fresh_bid()][0]) + 1; }
__device__ __forceinline__ bool flag_up(int stage, int b, uint32_t target) { return (int)(ld_rlx(flag_ptr(stage, b)) - target) >= 0; }
__device__ __forceinline__ void flag_wait(int stage, int b, uint32_t target) {
    [[maybe_unused]] int n = 0;
    while (!flag_up(stage, b, target)) {
        __nanosleep(20);
        SPIN_CHECK(n, 10 + stage);
    }
    fence_acq_gpu();
    fence_async_glb();
}
__device__ __forceinline__ void publish(int stage, int b) {
    fence_async_glb();
    fence_rel_gpu();
    red_add_u32(flag_ptr(stage, b), 1);
}
__device__ __forceinline__ uint32_t unit_frag_addr(int tid) {
    const int lane = tid & 31, w = (tid >> 5) & 3, i = lane & 7, j = lane >> 3;
    return ((j >> 1) * 8 + i) * 128 + ((((w << 1) + (j & 1)) ^ i) << 4);
}

#define V_BURST1 3
#define V_BURST2 1
#define V_CUT 2
#define V_PRE 9
#define SX_BF16 0
#define V_REV 1
#define K_GATE 1
#define WO_R8 1
#define OX_V4 0
#define V_LEAD 9
static_assert((V_BURST1 + V_BURST2 >= 2 || V_PRE == 7) && V_BURST1 <= 3 && V_LEAD > V_BURST1 + V_BURST2, "q and k rely on v for the arrival of the blocks");
#define K_LEAD 0
#define Q_LEAD 36
#define V_FIRST 8
#define SX_GATE 1
static_assert(SX_GATE, "EB_QF also stands for the K tile");
#define V_EARLY 1
__host__ __device__ constexpr int x_order(int mat, int j) {
    return mat == 2 ? j : j < 3 ? j + 5 : j < 5 ? j : j == 5 ? 2 : j == 6 ? 8 : 8 - j;
}
#define SS0Q 0
#define SS0K 0
#define SS0V 22
#define SSLQ 36
#define SSLK 36
#define SSLV 14
__host__ __device__ constexpr uint64_t ss_mask(int mat) {
    const int ns = 36 - (mat == 0 ? NRQ : mat == 1 ? NRK : NRV);
    const int j0 = mat == 0 ? SS0Q : mat == 1 ? SS0K : SS0V, len = mat == 0 ? SSLQ : mat == 1 ? SSLK : SSLV;
    uint64_t m = 0;
    for (int j = j0; j < j0 + len; j++)
        if ((j - j0) * ns / len != (j - j0 + 1) * ns / len) m |= 1ull << (x_order(mat, j >> 2) * 4 + (j & 3));
    return m;
}
__device__ __forceinline__ int popc_below(uint64_t m, int k) { return __popcll(m & ((1ull << k) - 1)); }
__host__ __device__ constexpr int x_slot(int f) {
    return f < 3 ? E_R0 + f * 8192 : f == 3 ? E_QT : f == 4 ? E_KT : f < 7 ? E_MEM + (f - 5) * 8192 : f == 8 ? E_R2 : f == 10 ? E_R1 : E_R0;
}
__host__ __device__ constexpr int x_full(int f) { return f < 3 ? 0 : f < 9 ? (f - 1) / 2 : 14 - f; }
__host__ __device__ constexpr bool x_first(int f) { return f == 0 || x_full(f) != x_full(f - 1); }
__host__ __device__ constexpr int x_empty(int blk) { return blk == 6 ? 0 : blk == 7 ? 1 : blk == 4 ? 2 : -1; }
__host__ __device__ constexpr int ar_tile(int j) { return j == 0 ? 8 : ((j - 1) & 1) * 4 + ((j - 1) >> 1); }
__host__ __device__ constexpr int sx_off(int u) { return u == 0 ? 0 : u == 1 ? 1536 : u == 2 ? 2560 : u == 3 ? 3072 : 5120; }

template <int MAT, int NR, int K0, int K1>
__device__ __forceinline__ void proj_mem(float* d, const uint32_t (&w)[NR][4]) {
    constexpr uint64_t M = ss_mask(MAT);
    const uint64_t db = mkdesc(E_MEM, 128, 9216, 0);
    const uint64_t da = mkdesc((MAT == 0 ? E_WQ : MAT == 1 ? E_WK : E_WV), 1024, 1024, 1);
#pragma unroll
    for (int j = K0; j < K1; j++) {
        const int ks = MAT != 2 ? ar_tile(j >> 2) * 4 + (j & 3) : V_REV ? 35 - j : j, s = popc_below(M, ks);
        if ((M >> ks) & 1) wg_ss16(d, da + s * 128, db + ks * 16, j > 0);
        else wg_rs16(d, w[ks - s], db + ks * 16, j > 0);
    }
}
__device__ __forceinline__ uint32_t tl_lane(int tid, int group_bytes) {
    return ((tid >> 4) & 1) * group_bytes + (((tid >> 5) & 3) * 16 + (tid & 15)) * 16;
}
struct ArWords {
    uint32_t w[5];
    __device__ __forceinline__ ArWords(const float* y) {
        w[0] = pack2(y[0], y[1]); w[1] = pack2(y[2], y[3]); w[2] = pack2(y[4], y[5]); w[3] = pack2(y[6], 1.f); w[4] = pack2(y[7], 1.f);
    }
    __device__ __forceinline__ void force(uint32_t zero) {
        asm volatile("{.reg .pred p; setp.ne.u32 p, %0, 0; @p st.shared.v4.b32 [%5], {%1,%2,%3,%4};}" :: "r"(zero), "r"(w[0]), "r"(w[1]), "r"(w[2]), "r"(w[3]), "r"(w[4]) : "memory");
    }
    __device__ __forceinline__ void red(uint8_t* p, uint8_t* q) {
        asm volatile("red.relaxed.gpu.global.add.noftz.v4.bf16x2 [%0], {%1,%2,%3,%4};" :: "l"(p), "r"(w[0]), "r"(w[1]), "r"(w[2]), "r"(w[3]) : "memory");
        asm volatile("red.relaxed.gpu.global.add.noftz.bf16x2 [%0], %1;" :: "l"(q), "r"(w[4]) : "memory");
    }
};
__device__ __forceinline__ uint32_t ar_main(int tid) { return ((tid & 127) >> 3) * AR_STR + (tid & 7) * 16; }
__device__ __forceinline__ uint32_t ar_side(int tid) { return ((tid & 127) >> 5) * (4 * AR_STR) + AR_STR / 2 + (tid & 31) * 4; }

#define AR_VA 0
#define AR_VA1 1
#define AR_SPLIT 5
template <bool B> struct Bool { static constexpr bool value = B; };
template <int J0, int J1>
__device__ __forceinline__ int ar_fetch(const Params& P, int i, int tid, uint32_t gate, uint32_t done) {
    const uint8_t* pm = g_ar + ((i & 3) * AR_SLOT + ar_main(tid));
    const uint8_t* ps = g_ar + ((i & 3) * AR_SLOT + ar_side(tid));
    const uint32_t a = sb + E_MEM + tl_lane(tid, 9216);
    asm volatile("{.reg .pred p; setp.ne.u32 p, %0, 0; @p st.shared.v2.b64 [%3], {%1,%2};}" :: "r"(P.zero), "l"(pm), "l"(ps), "r"(a) : "memory");
    if (J0 == 0) mbar_wait(gate, (i & 1) ^ 1);
    int n = -1;
    bool bad = i >= 0;
    while (bad) {
        uint4 av[J1 - J0];
        uint32_t as[J1 - J0];
#pragma unroll
        for (int j = J0; j < J1; j++) { av[j - J0] = ld_rlx128(pm + ar_tile(j) * (16 * AR_STR)); as[j - J0] = ld_rlx(ps + ar_tile(j) * (16 * AR_STR)); }
        bad = false;
#pragma unroll
        for (int j = J0; j < J1; j++) {
            bad |= __byte_perm(av[j - J0].w, as[j - J0], 0x7632) != (ar_tile(j) == 8 ? 0x42804280u : 0x42004200u);
            stsm4(a + ar_tile(j) * 1024, av[j - J0].x, av[j - J0].y, av[j - J0].z, __byte_perm(av[j - J0].w, as[j - J0], 0x5410));
        }
        bad = __any_sync(~0u, bad);
        SPIN_CHECK(n, 2);
        PROF_INC(n, 1);
    }
    if (i < 0 || i + 1 == LAG) {
        const uint16_t* m = (const uint16_t*)P.mem0 + (tid & 3) * (2 * DM) + (tid >> 5) * 16 + ((tid & 31) >> 2);
        const uint32_t a2 = sb + E_MEM + (tid >> 5) * 256 + (tid & 31) * 4;
        uint32_t v[18];
#pragma unroll
        for (int T = 2 * J0; T < 2 * J1; T++) v[T] = (uint32_t)__ldg(m + ar_tile(T >> 1) * 64 + (T & 1) * 8) | ((uint32_t)__ldg(m + ar_tile(T >> 1) * 64 + (T & 1) * 8 + DM) << 16);
        __syncwarp();
#pragma unroll
        for (int T = 2 * J0; T < 2 * J1; T++) {
            sts32(a2 + 9216 + ar_tile(T >> 1) * 1024 + (T & 1) * 128, v[T]);
            if (i < 0) sts32(a2 + ar_tile(T >> 1) * 1024 + (T & 1) * 128, v[T]);
        }
    }
    if (J0) fence_async_smem();
    mbar_arrive_warp(done);
    return n;
}

__device__ __forceinline__ void attn_mem(float* d, uint32_t par, int i, int tid) {
    const int lane = tid & 31, warp = tid >> 5, c = warp >> 1, hf = warp & 1;
    const int rank = cta_rank();
    const uint32_t peer = mapa(sb, rank ^ 1);
    const uint32_t l4 = (lane >> 4) * 1024 + (lane & 15) * 16;
    uint32_t kb[4][4];
    {
        const uint32_t aK = sb + E_KT + (c * 6 + hf * 2) * 1024 + l4;
#pragma unroll
        for (int ks = 0; ks < 4; ks++) ldsm4t(kb[ks], aK + ks * 256);
    }
    const uint32_t aQs = pin(sb + E_QM + tl_lane(tid, 1024));
    const uint32_t aQ = pin(sb + E_QM + c * 1024 + (((lane >> 3) & 1) * 16 + (lane >> 4) * 8 + (lane & 7)) * 16);
    const uint32_t aM = pin(sb + E_KT + (4 + c) * 1024 + lane * 16);
    const uint32_t oS = pin(tid * 16);
    wg_wait_acc<0, 8>(d);
    stsm4(aQs, pack2(d[0], d[1]), pack2(d[2], d[3]), pack2(d[4], d[5]), pack2(d[6], d[7]));
    nbar_sync(NB_QK, 256);
    TS(0, i, 1);
    float s[6];
    {
        uint32_t q[2][4], km[2][4];
        ldsm4t(q[0], aQ); ldsm4t(km[0], aM); ldsm4t(q[1], aQ + 512); ldsm4t(km[1], aM + 512);
        float a[6][4];
#pragma unroll
        for (int m = 0; m < 6; m++) a[m][0] = a[m][1] = a[m][2] = a[m][3] = 0.f;
#pragma unroll
        for (int j = 0; j < 2; j++) {
#pragma unroll
            for (int o = 0; o < 2; o++) {
                mma16816(a[o * 3], q[j], kb[2 * j + o][0], kb[2 * j + o][1]);
                mma16816(a[o * 3 + 1], q[j], kb[2 * j + o][2], kb[2 * j + o][3]);
            }
            mma16816(a[2], q[j], km[j][0], km[j][1]);
            mma16816(a[5], q[j], km[j][2], km[j][3]);
        }
        nbar_arrive(NB_S, 256);
        if (SX_GATE) nbar_arrive(NB_S2, 256);
#pragma unroll
        for (int m = 0; m < 3; m++) { s[2 * m] = a[m][0] + a[3 + m][2]; s[2 * m + 1] = a[m][1] + a[3 + m][3]; }
    }
    st_async128(peer + E_SR + oS, fu(s[0]), fu(s[1]), fu(s[2]), fu(s[3]), peer + SM_BAR + EB_SM * 8);
    const uint32_t oM = E_SR + 2048 + c * 256 + lane * 8;
    asm volatile("st.async.shared::cluster.mbarrier::complete_tx::bytes.b32 [%0], %1, [%2];"
                 :: "r"(peer + oM + hf * 4), "r"(fu(hf ? s[5] : s[4])), "r"(peer + SM_BAR + EB_SM * 8) : "memory");
    sts128(sb + E_SL + oS, fu(s[0]), fu(s[1]), fu(s[2]), fu(s[3]));
    mbar_arrive_warp(bars + EB_KF * 8);
    TS(0, i, 2);
#pragma unroll
    for (int j = 0; j < 4; j++) ldsm4(kb[j], sb + E_VT + c * 6144 + l4 + hf * 512 + ((j >> 1) ^ hf) * 2048 + (j & 1) * 256);
    nbar_sync(NB_G, 128);
    const uint32_t aR = sb + E_SR + oS, aR1 = sb + E_SR + (oS ^ 512), aRm = sb + oM;
    const uint4 l1 = lds128(aR1 + (E_SL - E_SR));
    mbar_wait_cl(bars + EB_SM * 8, par);
    TS(0, i, 3);
    float p[10];
    {
        const uint4 r0 = lds128(aR), r1 = lds128(aR1);
        const uint2 rm = lds64(aRm);
        p[0] = s[0] + uf(r0.x); p[1] = s[1] + uf(r0.y); p[2] = s[2] + uf(r0.z); p[3] = s[3] + uf(r0.w);
        p[4] = uf(l1.x) + uf(r1.x); p[5] = uf(l1.y) + uf(r1.y); p[6] = uf(l1.z) + uf(r1.z); p[7] = uf(l1.w) + uf(r1.w);
        p[8] = s[4] + uf(rm.x); p[9] = s[5] + uf(rm.y);
    }
    float mx = fmaxf(fmaxf(fmaxf(p[0], p[1]), fmaxf(p[2], p[3])), fmaxf(fmaxf(fmaxf(p[4], p[5]), fmaxf(p[6], p[7])), fmaxf(p[8], p[9])));
    mx = fmaxf(mx, __shfl_xor_sync(~0u, mx, 1));
    mx = fmaxf(mx, __shfl_xor_sync(~0u, mx, 2));
    const float mo = mx * (SM_SCALE * LOG2E);
    mbar_wait(bars + EB_KF * 8, par);
    uint32_t vm[4], pb[5];
    ldsm4(vm, aM + (E_VT - E_KT) + hf * 512);
    float o[3][4];
    const uint32_t ones[4] = {0x3f803f80u, 0x3f803f80u, 0x3f803f80u, 0x3f803f80u};
#pragma unroll
    for (int T = 0; T < 3; T++) o[T][0] = o[T][1] = o[T][2] = o[T][3] = 0.f;
#pragma unroll
    for (int j = 0; j < 2; j++) {
#pragma unroll
        for (int m = 2 * j; m < 2 * j + 2; m++) pb[m] = pack2(ex2(fmaf(p[2 * m], SM_SCALE * LOG2E, -mo)), ex2(fmaf(p[2 * m + 1], SM_SCALE * LOG2E, -mo)));
        mma16816(o[2], ones, pb[2 * j], pb[2 * j + 1]);
#pragma unroll
        for (int T = 0; T < 2; T++) mma16816(o[T], kb[2 * j + T], pb[2 * j], pb[2 * j + 1]);
    }
    pb[4] = pack2(ex2(fmaf(p[8], SM_SCALE * LOG2E, -mo)), ex2(fmaf(p[9], SM_SCALE * LOG2E, -mo)));
    mma1688(o[2], ones[0], ones[1], pb[4]);
#pragma unroll
    for (int T = 0; T < 2; T++) mma1688(o[T], vm[2 * T], vm[2 * T + 1], pb[4]);
    nbar_arrive(NB_PV, 256);
    mbar_arrive_warp(bars + EB_CONS * 8);
    const float i0 = rcp(o[2][0]), i1 = rcp(o[2][1]);
    uint32_t ow[4];
#pragma unroll
    for (int j = 0; j < 4; j++) ow[j] = pack2(o[j >> 1][2 * (j & 1)] * i0, o[j >> 1][2 * (j & 1) + 1] * i1);
    const uint32_t oO = E_OM + c * 2048 + hf * 512;
    stsm4(sb + oO + lane * 16, ow[0], ow[1], ow[2], ow[3]);
    if (OX_V4) {
        __syncwarp();
        const uint4 r = lds128(sb + oO + lane * 16);
        nbar_sync(NB_G, 128);
        st_async128(peer + oO + 1024 + lane * 16, r.x, r.y, r.z, r.w, peer + SM_BAR + EB_OX * 8);
    } else {
#pragma unroll
        for (int j = 0; j < 4; j++)
            asm volatile("st.async.shared::cluster.mbarrier::complete_tx::bytes.b32 [%0], %1, [%2];"
                         :: "r"(peer + oO + 1024 + j * 128 + lane * 4), "r"(ow[j]), "r"(peer + SM_BAR + EB_OX * 8) : "memory");
    }
}

__device__ __forceinline__ void attn_x_scores(float (&p)[2][10], uint32_t par, int i, int tid) {
    {
        float s[40];
        const uint64_t da = mkdesc(E_QT, 128, 1024, 0), db = mkdesc(E_KT, 128, 1024, 0);
        wg_fence();
#pragma unroll
        for (int ks = 0; ks < 4; ks++) wg_ss80(s, da + ks * 16, db + ks * 16, ks > 0);
        wg_commit();
        const int dq = (tid >> 2) - 2 * (tid & 3);
        float mask[8];
#pragma unroll
        for (int j = 0; j < 8; j++) mask[j] = (j >> 1) * 8 + (j & 1) > dq ? -1e9f * LOG2E : 0.f;
        mbar_wait_cl(bars + EB_PRDY * 8, par);
        wg_wait_acc<0, 40>(s);
#pragma unroll
        for (int u = 0; u < 5; u++) {
            const int v = u < 4 ? 6 + u : 5;
            constexpr float C = SM_SCALE * LOG2E;
            const float m0 = u < 4 ? mask[2 * u & 7] : 0.f, m1 = u < 4 ? mask[(2 * u + 1) & 7] : 0.f;
            p[0][2 * u] = fmaf(s[4 * u], C, m0); p[0][2 * u + 1] = fmaf(s[4 * u + 1], C, m1); p[1][2 * u] = fmaf(s[4 * v + 2], C, m0); p[1][2 * u + 1] = fmaf(s[4 * v + 3], C, m1);
        }
    }
    mbar_arrive_warp(bars + EB_QF * 8);
    const int w = tid >> 5;
    if (!SX_BF16) {
        const uint32_t peer = mapa(sb, cta_rank() ^ 1);
#pragma unroll
        for (int u = 0; u < 5; u++)
            if (u == 0 || u <= w || u == 4) st_async128(peer + E_SX + sx_off(u) + tid * 16, fu(p[0][2 * u]), fu(p[0][2 * u + 1]), fu(p[1][2 * u]), fu(p[1][2 * u + 1]), peer + SM_BAR + EB_SX * 8);
    } else {
        const uint32_t peer = mapa(sb, cta_rank() ^ 1), a = peer + E_SX + tid * 16, mb = peer + SM_BAR + EB_SX * 8;
        st_async128(a, pack2(p[0][0], p[0][1]), pack2(p[1][0], p[1][1]), pack2(p[0][8], p[0][9]), pack2(p[1][8], p[1][9]), mb);
        if (w >= 1) st_async128(a + 2048, pack2(p[0][2], p[0][3]), pack2(p[1][2], p[1][3]), pack2(p[0][4], p[0][5]), pack2(p[1][4], p[1][5]), mb);
        if (w >= 3) st_async64(a + 4096, pack2(p[0][6], p[0][7]), pack2(p[1][6], p[1][7]), mb);
    }
    TS(128, i, 10);
}
__device__ __forceinline__ void attn_x_finish(float (&p)[2][10], uint32_t par, int i, int& tid, uint32_t zero) {
    const int w = tid >> 5;
    mbar_wait_cl(bars + EB_SX * 8, par);
    TS(128, i, 11);
    if (SX_BF16) {
        const uint32_t a = sb + E_SX + tid * 16;
        const uint4 r0 = lds128(a), r1 = lds128(a + (w >= 1 ? 2048 : 0));
        const uint2 r2 = lds64(a + (w >= 3 ? 4096 : 0));
        const uint32_t r[10] = {r0.x, r0.y, r1.x, r1.y, r1.z, r1.w, r2.x, r2.y, r0.z, r0.w};
#pragma unroll
        for (int j = 0; j < 10; j++) { p[j & 1][j & ~1] += bf_lo(r[j]); p[j & 1][j | 1] += bf_hi(r[j]); }
    } else
#pragma unroll
    for (int u = 0; u < 5; u++) {
        const uint4 r = lds128(pin(sb + tid * 16 + (u == 0 || u <= w ? sx_off(u) : sx_off(4))) + E_SX);
        p[0][2 * u] += uf(r.x); p[0][2 * u + 1] += uf(r.y); p[1][2 * u] += uf(r.z); p[1][2 * u + 1] += uf(r.w);
    }
    nbar_sync(NB_W, 128);
    uint32_t pa[5][4];
    float mx[2], inv[2];
#pragma unroll
    for (int h = 0; h < 2; h++) {
        const float* q = p[h];
        mx[h] = fmaxf(fmaxf(fmaxf(q[0], q[1]), fmaxf(q[2], q[3])), fmaxf(fmaxf(fmaxf(q[4], q[5]), fmaxf(q[6], q[7])), fmaxf(q[8], q[9])));
    }
#pragma unroll
    for (int o = 1; o < 4; o <<= 1) { mx[0] = fmaxf(mx[0], __shfl_xor_sync(~0u, mx[0], o)); mx[1] = fmaxf(mx[1], __shfl_xor_sync(~0u, mx[1], o)); }
#pragma unroll
    for (int h = 0; h < 2; h++) {
        float* q = p[h];
#pragma unroll
        for (int j = 0; j < 10; j++) q[j] = ex2(q[j] - mx[h]);
#pragma unroll
        for (int u = 0; u < 4; u++) {
            pa[h * 3 + (u >> 1)][(u & 1) * 2 + h] = pack2(q[2 * u], q[2 * u + 1]);
            pa[h * 3 + (u >> 1)][(u & 1) * 2 + (h ^ 1)] = zero << (h * 5 + u + 1);
        }
        pa[2][h * 3] = pack2(q[8], q[9]);
        pa[2][1 + h] = zero << (h * 5 + 5);
    }
    mbar_wait(bars + EB_CONS * 8, par);
    fence_async_smem();
    tid = pin(tid << zero);
    const uint32_t aO = pin(sb + ((tid >> 3) & 1) * 4096 + (((tid >> 4) & 1) * 8 + (tid & 7)) * 64 + (((tid >> 5) ^ ((tid & 7) >> 1)) << 4)) + E_R1;
    TS(128, i, 12);
#pragma unroll
    for (int nh = 0; nh < 2; nh++) {
        float o[16], sum[4];
        const uint64_t db = mkdesc(E_VT + nh * 512, 1024, 128, 0);
        wg_fence();
#pragma unroll
        for (int kk = 0; kk < 5; kk++) {
            if (nh == 0) wg_rs8(sum, pa[kk], mkdesc(SM_ONES, 0, 0, 0), kk > 0);
            wg_rs32(o, pa[kk], db + kk * 128, kk > 0);
        }
        wg_commit();
        wg_wait_acc<0, 16>(o);
        if (nh == 0) { acc_ready<4>(sum); inv[0] = rcp(sum[0]); inv[1] = rcp(sum[2]); }
#pragma unroll
        for (int j = 0; j < 2; j++) {
            const float* y = &o[8 * j];
            stsm4t(aO + nh * 2048 + j * 1024, pack2(y[0] * inv[0], y[1] * inv[0]), pack2(y[2] * inv[1], y[3] * inv[1]), pack2(y[4] * inv[0], y[5] * inv[0]), pack2(y[6] * inv[1], y[7] * inv[1]));
        }
    }
    mbar_arrive_warp(bars + EB_OST * 8);
    TS(128, i, 13);
}

template <int MAT>
__device__ __forceinline__ void engine_main(const Params& P) {
    constexpr int NR = MAT == 0 ? NRQ : MAT == 1 ? NRK : NRV;
    constexpr uint64_t M = ss_mask(MAT);
    uint32_t w[NR][4];
    {
        const uint32_t a = sb + E_WO + (MAT == 0 ? 0 : MAT == 1 ? NRQ : NRQ + NRK) * 2048 + unit_frag_addr(fresh_tid());
        mbar_wait(bars + EB_WL * 8, 0);
        if (MAT == 0 && threadIdx.x == 0) TG(79, 2);
#pragma unroll
        for (int u = 0; u < NR; u++) ldsm4t(w[u], a + u * 2048);
    }
    nbar_arrive(NB_T, 448);
    int tid = fresh_tid() - MAT * 128;
#define TID (tid = pin(tid << P.zero))
    if (MAT == 0) { if (V_FIRST == 36) nbar_arrive(NB_S, 256); nbar_arrive(NB_PV, 256); nbar_arrive(NB_WO, 256); }
    auto project = [&](auto one, const int i) {
        constexpr bool ONE = decltype(one)::value;
        const uint32_t par = i & 1;
        {
            float d[ONE ? 16 : 32];
            const uint64_t da = mkdesc((MAT == 0 ? E_WQ : MAT == 1 ? E_WK : E_WV), 1024, 1024, 1);
            constexpr int R1 = V_BURST1, R2 = V_BURST1 + V_BURST2;
#pragma unroll
            for (int n = 0; n < 9; n++) {
                const int blk = x_order(MAT, n), prev = n ? x_order(MAT, n - 1) : -1, f = MAT != 2 && blk < 2 ? 9 + blk : blk;
                if (MAT == 2) {
                    if (!V_CUT && R2 >= 2 && n == (R1 >= 2 ? R1 : R2)) { wg_wait<0>(); mbar_arrive_warp(bars + EB_V0 * 8); }
                    if ((n == 0 && (V_FIRST == 36 || i == 0)) || n == R1 || n == R2) {
#pragma unroll
                        for (int j = n; j < (n < R1 ? R1 : n < R2 ? R2 : V_PRE); j++) if (x_first(j)) mbar_wait(bars + (EB_FULL + x_full(j)) * 8, par);
                    }
                    if (n == 0 && V_FIRST == 36) nbar_sync(NB_S, 256);
                    if (n == R1 && !V_CUT) nbar_sync(NB_PV, 256);
                    if (n == R2) nbar_sync(NB_WO, 256);
                } else {
                    if (n == 0) nbar_sync(MAT ? NB_VL : NB_VL2, 256);
                }
                static_assert(V_PRE == 9 || (V_PRE == 7 && V_LEAD > 7), "see the barriers");
                const bool wt = MAT == 2 ? f == V_PRE : f >= 9;
                if (wt) mbar_wait(bars + (EB_FULL + x_full(f)) * 8, par);
                TX(MAT * 128, 1 + MAT * 9 + n);
                if (wt || n == 0 || (MAT == 2 && (n == R1 || n == R2))) wg_fence();
                if (n == 0) TS(MAT * 128, i, 20 + MAT);
                const uint64_t db = mkdesc(x_slot(f), 16, 1024, 1);
#pragma unroll
                for (int j = 0; j < 4; j++) {
                    const int ks = blk * 4 + j, s = popc_below(M, ks);
                    if (MAT == 2 && V_CUT && ks == R1 * 4 - V_CUT) { wg_commit(); wg_wait<0>(); mbar_arrive_warp(bars + EB_V0 * 8); nbar_sync(NB_PV, 256); wg_fence(); }
                    if constexpr (ONE) {
                        if ((M >> ks) & 1) wg_ss32(d, da + s * 128, db + j * 2, n + j > 0);
                        else wg_rs32(d, w[ks - s], db + j * 2, n + j > 0);
                    } else {
                        if ((M >> ks) & 1) wg_ss64<0>(d, da + s * 128, db + j * 2, n + j > 0);
                        else wg_rs64<0>(d, w[ks - s], db + j * 2, n + j > 0);
                    }
                }
                wg_commit();
                if (MAT == 2 && n + 1 == V_LEAD) { nbar_arrive(NB_VL, 256); if (!K_LEAD) nbar_arrive(NB_VL2, 256); }
                if (MAT == 1 && n + 1 == K_LEAD) nbar_arrive(NB_VL2, 256);
                if (MAT == 2 && R2 < 2 && n == 3) { wg_wait<2>(); mbar_arrive_warp(bars + EB_V0 * 8); }
                if (MAT != 2 && x_empty(prev) >= 0) { wg_wait<1>(); mbar_arrive_warp(bars + (EB_EMPTY + x_empty(prev)) * 8); }
            }
            const uint32_t a = sb + (MAT == 0 ? E_QT : MAT == 1 ? E_KT : E_VT) + tl_lane(TID, MAT == 0 ? 2048 : 1024) + (ONE && i >= NSEG ? (MAT == 0 ? 1024 : 6144) : 0);
            if (MAT != 2) {
                mbar_wait(bars + (EB_EMPTY + 2) * 8, par);
                if (!ONE) mbar_wait(bars + EB_MEMA * 8, par);
            } else {
                mbar_wait(bars + EB_OST * 8, par ^ 1);
            }
            wg_wait_acc<0, ONE ? 16 : 32>(d);
            TS(MAT * 128, i, 23 + MAT);
#pragma unroll
            for (int j = 0; j < (ONE ? 4 : 8); j += 2) {
                const int grp = MAT == 0 ? 2 * (j & 3) + (j >> 2) : j < 4 ? j : j + 2;
                stsm4(a + grp * 1024, pack2(d[4 * j], d[4 * j + 1]), pack2(d[4 * j + 2], d[4 * j + 3]), pack2(d[4 * j + 4], d[4 * j + 5]), pack2(d[4 * j + 6], d[4 * j + 7]));
            }
        }
        if (MAT != 2) {
            if (ONE) mbar_arrive_warp(bars + EB_STEP * 8);
            if (ONE) mbar_wait(bars + EB_MEMA * 8, par);
        } else {
            __syncwarp();
            if ((TID & 31) < 3) mbar_arrive(bars + (EB_EMPTY + (tid & 31)) * 8);
        }
    };
    auto step = [&](const int i) {
        const uint32_t par = i & 1;
        if (MAT == 2) {
            if (Q_LEAD) nbar_sync(NB_OM, K_GATE ? 384 : 256);
            else mbar_wait(bars + EB_MEM * 8, par);
        }
        float d[8];
        TS(MAT * 128, i, MAT == 2 ? 26 : 14 + MAT);
        wg_fence();
        constexpr int MID = MAT == 2 ? V_FIRST : Q_LEAD;
        if (MAT != 2) {
            static_assert(Q_LEAD >= AR_SPLIT * 4, "v relies on q for the rest");
            proj_mem<MAT, NR, 0, AR_SPLIT * 4>(d, w);
            mbar_wait(bars + EB_MEM * 8, par);
            wg_fence();
        }
        proj_mem<MAT, NR, MAT != 2 ? AR_SPLIT * 4 : 0, MID>(d, w);
        if ((MAT == 0 || (MAT == 1 && K_GATE)) && Q_LEAD) nbar_arrive(NB_OM, K_GATE ? 384 : 256);
        if (MAT == 2 && V_FIRST < 36) {
            if (V_BURST1) mbar_wait(bars + EB_FULL * 8, i == NSTEP - 1 ? par : par ^ 1);
            nbar_sync(NB_S, 256);
            wg_fence();
        }
        proj_mem<MAT, NR, MID, 36>(d, w);
        wg_commit();
        if (MAT == 0) {
            mbar_wait(bars + EB_WO * 8, 0);
            tid *= mbar_wait(bars + EB_STEP * 8, par);
            attn_mem(d, par, i, tid);
        } else if (MAT == 1) {
            tid *= mbar_wait(bars + EB_STEP * 8, par);
            const uint32_t a = pin(sb + E_KT + 4096 + tl_lane(tid, 1024));
            wg_wait_acc<0, 8>(d);
            stsm4(a, pack2(d[0], d[1]), pack2(d[2], d[3]), pack2(d[4], d[5]), pack2(d[6], d[7]));
            nbar_arrive(NB_QK, 256);
            TS(128, i, 18);
            fence_async_smem();
            nbar_sync(SX_GATE ? NB_S2 : NB_W, SX_GATE ? 256 : 128);
            float p[2][10];
            attn_x_scores(p, par, i, TID);
            attn_x_finish(p, par, i, TID, pin(P.zero));
        } else {
            const uint32_t a = pin(sb + E_VT + 4096 + tl_lane(TID, 1024));
            wg_wait_acc<0, 8>(d);
            stsm4(a, pack2(d[0], d[1]), pack2(d[2], d[3]), pack2(d[4], d[5]), pack2(d[6], d[7]));
            mbar_arrive_warp(bars + EB_KF * 8);
            TS(256, i, 16);
        }
        if (MAT == 0) {
            const int rank = cta_rank();
            uint8_t* const ar = g_ar + (i & 3) * AR_SLOT;
            uint8_t* const pm = ar + pin(ar_main(TID) + rank * (64 * AR_STR));
            uint8_t* const ps = ar + pin(ar_side(tid) + rank * (64 * AR_STR));
            const uint32_t o8 = (128 - rank * 64) * AR_STR;
            const uint64_t db = mkdesc(E_OM, 128, 2048, 0), da = mkdesc(E_WO, 1024, 1024, 1);
            if (!OX_V4) nbar_sync(NB_G, 128);
            fence_async_smem();
            TS(0, i, 6);
            if (i == NSTEP - 1) { mbar_wait_cl(bars + EB_OX * 8, par); return; }
            float y[4][8];
            wg_fence();
#pragma unroll
            for (int ks = 0; ks < 4; ks++) wg_ss16(y[3], da + (32 + ks) * 128, db + ks * 16, ks > 0);
            wg_commit();
#pragma unroll
            for (int j = 0; j < 12; j++) wg_ss16(y[j % 3], da + ((j % 3) * 8 + j / 3) * 128, db + (j / 3) * 16, j >= 3);
            wg_commit();
            wg_wait_acc<1, 8>(y[3]);
            ArWords z(y[3]);
            if (WO_R8) z.red(pm + o8, ps + o8); else z.force(P.zero);
            mbar_wait_cl(bars + EB_OX * 8, par);
            fence_async_smem();
            wg_fence();
#pragma unroll
            for (int T = 0; T < 4; T++) {
#pragma unroll
                for (int ks = T < 3 ? 4 : 0; ks < 8; ks++) wg_ss16(y[T], da + (T * 8 + ks) * 128, db + ks * 16, ks > 0);
                wg_commit();
            }
            if (V_EARLY) nbar_arrive(NB_WO, 256);
            if (!WO_R8) z.red(pm + o8, ps + o8);
            wg_wait_acc<1, 8>(y[0]); acc_ready<8>(y[1]); acc_ready<8>(y[2]);
#pragma unroll
            for (int T = 0; T < 3; T++) ArWords(y[T]).red(pm + T * 16 * AR_STR, ps + T * 16 * AR_STR);
            wg_wait_acc<0, 8>(y[3]);
            ArWords(y[3]).red(pm + 48 * AR_STR, ps + 48 * AR_STR);
            if (!V_EARLY) nbar_arrive(NB_WO, 256);
            TS(0, i, 7);
        }
    };
    auto either = [&](const int i) {
        if (__builtin_expect(USE_ONE == 2 || (USE_ONE && (i < LAG || i >= NSEG)), MAT != 2)) project(Bool<true>(), i);
        else project(Bool<false>(), i);
    };
    if (MAT != 2) {
#pragma unroll 1
        for (int i = 0; i < NSTEP; i++) {
            either(i);
            if (!USE_ONE || (USE_ONE == 1 && i >= LAG && i < NSEG)) mbar_arrive_warp(bars + EB_STEP * 8);
            step(i);
        }
    } else {
#pragma unroll 1
        for (int i = -1; i < NSTEP; i++) {
            if (i >= 0) step(i);
            if (i < NSTEP - 1) {
                either(i + 1);
                const bool one = USE_ONE == 2 || (USE_ONE && (i + 1 < LAG || i + 1 >= NSEG));
                [[maybe_unused]] const int n0 = ar_fetch<0, AR_SPLIT>(P, i, TID, bars + (EB_EMPTY + (one ? AR_VA1 : AR_VA)) * 8, bars + EB_MEM0 * 8);
                [[maybe_unused]] const int n1 = ar_fetch<AR_SPLIT, 9>(P, i, tid, bars + EB_EMPTY * 8, bars + EB_MEM * 8);
            }
        }
    }
    if (MAT == 2) { if (V_FIRST == 36) nbar_sync(NB_S, 256); nbar_sync(NB_PV, 256); }
}

__device__ __forceinline__ void engine_helper(const Params& P) {
    const int lane = threadIdx.x & 31, hw = warp_in_group(), e = blockIdx.x, rank = e & 1;
    if (hw < 3) {
        constexpr uint64_t M0 = ss_mask(0), M1 = ss_mask(1), M2 = ss_mask(2);
        const uint64_t m = hw == 0 ? M0 : hw == 1 ? M1 : M2;
        const uint32_t ws = sb + (hw == 0 ? E_WQ : hw == 1 ? E_WK : E_WV), wr = sb + E_WO + (hw == 0 ? 0 : hw == 1 ? NRQ : NRQ + NRK) * 2048;
        if (lane == 0) mbar_expect(bars + EB_WL * 8, 36 * 2048);
        __syncwarp();
        for (int ks = lane; ks < 36; ks += 32) {
            const int s = __popcll(m & ((1ull << ks) - 1));
            tma_unit(((m >> ks) & 1) ? ws + s * 2048 : wr + (ks - s) * 2048, hw == 0 ? &P.tmWq : hw == 1 ? &P.tmWk : &P.tmWv, ks, e, bars + EB_WL * 8);
        }
    }
    if (hw == 1) {
        hold_back(WO_DELAY);
        for (int u = lane; u < 36; u += 32)
            asm volatile("cp.async.bulk.prefetch.tensor.2d.L2.global [%0, {%1,%2}];"
                         :: "l"(&P.tmWo), "r"((u < 32 ? rank * 4 + (u >> 3) : 8) * 64), "r"(((e >> 1) * 8 + (u < 32 ? u & 7 : rank * 4 + (u & 3))) * 16) : "memory");
    }
    __syncwarp();
    if (hw < 2) nbar_sync(NB_T, 448);
    if (lane == 0) TG(79, 3);
    if (hw == 0) {
        if (lane == 0) {
#pragma unroll 1
            for (int n = 0; n < NSTEP; n++) {
                const uint32_t par = (n & 1) ^ 1;
                uint32_t rdy;
                do { asm volatile("ld.acquire.cta.shared.u32 %0, [%1];" : "=r"(rdy) : "r"(sb + SM_XRDY) : "memory"); } while (rdy <= n && (__nanosleep(20), true));
                fence_async_glb();
                TG(n, 30);
                const uint8_t* src = g_x + n * XIMG;
#pragma unroll
                for (int j = 0; j < 6; j++) {
                    const int f = j == 0 ? 0 : j < 4 ? 2 * j + 1 : 14 - j, blk = f < 9 ? f : f - 9, bytes = j == 0 ? 24576 : j < 4 ? 16384 : 8192;
                    if (j == 3 || j == 5) mbar_wait(bars + (j == 3 ? EB_V0 : EB_EMPTY + 1) * 8, par ^ 1);
                    else mbar_wait(bars + (j == 0 ? EB_STEP : j == 1 ? EB_QF : j == 2 ? EB_KF : EB_OFREE) * 8, par);
                    const uint32_t fb = bars + (EB_FULL + j) * 8;
                    mbar_expect(fb, bytes);
                    bulk_g2s(sb + x_slot(f), src + blk * 8192, bytes, fb);
                }
            }
        }
    } else if (hw == 1) {
        if (lane == 0) mbar_expect(bars + EB_WO * 8, 36 * 2048);
        __syncwarp();
        for (int u = lane; u < 36; u += 32)
            tma_unit(sb + E_WO + u * 2048, &P.tmWo, (e >> 1) * 8 + ((u & 7) ^ (rank * 4)), u < 32 ? rank * 4 + (u >> 3) : 8, bars + EB_WO * 8);
        __syncwarp();
        if (lane == 0) {
#pragma unroll 1
            for (int i = 0; i < NSTEP; i++) {
                mbar_wait(bars + EB_STEP * 8, i & 1);
                mbar_arrive_remote(mapa(sb, rank ^ 1) + SM_BAR + EB_PRDY * 8);
                mbar_wait(bars + EB_OST * 8, i & 1);
                fence_async_smem();
                const int q = first_job(i);
                bulk_s2g(g_o + (q & (RING - 1)) * O_BYTES + e * 4096, sb + E_R1 + (i < NSEG ? 0 : 4096), 4096);
                if (i >= LAG && i < NSEG) bulk_s2g(g_o + ((q + 1) & (RING - 1)) * O_BYTES + e * 4096, sb + E_R1 + 4096, 4096);
                asm volatile("cp.async.bulk.commit_group;" ::: "memory");
                asm volatile("cp.async.bulk.wait_group.read 0;" ::: "memory");
                mbar_arrive(bars + EB_OFREE * 8);
                asm volatile("cp.async.bulk.wait_group 0;" ::: "memory");
                publish(F_O, i);
                TG(i, 31);
            }
        }
    } else if (hw == 2) {
        const int idx = e * 23 + lane, line = idx >> 3;
        uint8_t* z = g_ar + (line < 144 ? line * AR_STR : (line - 144) * (4 * AR_STR) + AR_STR / 2) + (idx & 7) * 16;
        if (lane < 23 && idx < 1440) { stg128(z, make_uint4(0, 0, 0, 0)); stg128(z + AR_SLOT, make_uint4(0, 0, 0, 0)); }
        __syncwarp();
        if (lane == 0) {
            publish(F_X0, B_ZERO);
            mbar_arrive(bars + EB_MEM * 8);
            flag_wait(F_X0, B_ZERO, NENG * this_launch());
            mbar_arrive(bars + EB_WO * 8);
            TG(79, 5);
        }
        __syncwarp();
#pragma unroll 1
        for (int i = 0; i < NSTEP; i++) {
            mbar_wait(bars + EB_MEM0 * 8, i & 1);
            fence_async_smem();
            if (lane == 0) mbar_arrive(bars + EB_MEMA * 8);
            if (lane < 3) mbar_expect(bars + (EB_SM + lane) * 8, lane == 0 ? 2560 : lane == 1 ? (SX_BF16 ? 3840 : 7168) : 2048);
            mbar_wait(bars + EB_MEM * 8, i & 1);
            if (lane < 23 && idx < 1440) stg128(z + ((i + 2) & 3) * AR_SLOT, make_uint4(0, 0, 0, 0));
            __syncwarp();
            if (lane == 0) { fence_gpu(); mbar_arrive(bars + EB_MEM * 8); }
            __syncwarp();
        }
    } else {
        for (int j = lane; j < 72; j += 32) asm volatile("prefetch.global.L2 [%0];" :: "l"(P.mem0 + j * 64));
        const uint32_t ep = this_launch(), t0 = timer_lo();
        if (lane == 0) {
#pragma unroll 1
            for (int n = 0; n < NSTEP; n++) {
                while ((n < NSEG && !flag_up(F_X0, n, 16 * ep)) || (n >= LAG && !flag_up(F_X1, n - LAG, 16 * ep))) {
                    __nanosleep(20);
                    if (timer_lo() - t0 > TIME_LIMIT) break;
                }
                fence_acq_gpu();
                asm volatile("st.release.cta.shared.u32 [%0], %1;" :: "r"(sb + SM_XRDY), "r"(n + 1) : "memory");
            }
        }
    }
    __syncwarp();
}

__device__ __forceinline__ void f1_fetch(const Params& P, uint32_t dst, int f0, int ks0, int n) {
    const int tid = threadIdx.x & 127, r = tid >> 3, c = (tid & 3) * 2 + ((tid >> 2) & 1);
    const bf16* src = ((c & 1) ? P.w3 : P.w1) + (size_t)(ks0 * 16 + r) * FF + f0 + (c >> 1) * 8;
    dst += r * 128 + ((c ^ (r & 7)) << 4);
#pragma unroll 1
    for (int u = 0; u < n; u++) {
        asm volatile("cp.async.cg.shared.global [%0], [%1], 16;" :: "r"(dst + u * 2048), "l"(src + (size_t)u * 16 * FF) : "memory");
        asm volatile("cp.async.commit_group; cp.async.wait_group %0;" :: "n"(F1_DEPTH) : "memory");
    }
}
#define F1_LEAD 1
template <int a, bool second, int buf>
__device__ __forceinline__ void f1_tile(const uint32_t (&w)[NRF][4], uint32_t ws, int q) {
    constexpr bool RF = (a == 1) == second;
    const uint32_t par = (q >> 1) & 1;
    float d[16];
    const uint64_t da = mkdesc(ws, 1024, 1024, 1), db = mkdesc(F_X + buf * XF_BYTES, 16, 1024, 1);
#pragma unroll
    for (int g = 0; g < 3; g++) {
        if (a == 1 && !second && g == 0 && F1_LEAD) nbar_sync(NB_OM + buf, 256);
        if (g == 0 || (!second && (a == 0 || g >= F1_LEAD))) {
            mbar_wait(bars + (FB_FULL + buf * 3 + g) * 8, par);
            wg_fence();
        }
#pragma unroll
        for (int ks = g * 12; ks < g * 12 + 12; ks++) {
            const int u = RF ? ks : 36 + ks;
            if (u < NRF) wg_rs32(d, w[u < NRF ? u : 0], db + (ks >> 2) * 256 + (ks & 3) * 2, ks > 0);
            else wg_ss32(d, da + (u - NRF) * 128, db + (ks >> 2) * 256 + (ks & 3) * 2, ks > 0);
        }
        if (a == 0 && !second && g + 1 == F1_LEAD) nbar_arrive(NB_OM + buf, 256);
    }
    wg_commit();
    if (!second) mbar_wait(bars + FB_RACK * 8, (q & 1) ^ 1);
    const int tid = fresh_tid(), g = (tid & 31) >> 2;
    uint8_t* dst = g_h + (q & (RING - 1)) * H_BYTES + ((fresh_bid() - NENG + (second ? 36 : 0)) * 64 + a * 32 + ((tid >> 5) & 3) * 8 + g) * 64 + (((tid & 3) ^ (g >> 1)) << 4);
    wg_wait_acc<0, 16>(d);
    if (second) mbar_arrive_warp(bars + (FB_EMPTY + buf) * 8);
    uint32_t h[4];
#pragma unroll
    for (int j = 0; j < 4; j++) {
        const float g0 = d[4 * j], g1 = d[4 * j + 1];
        const float e0 = 1.f + ex2(fminf(-LOG2E * g0, 60.f)), e1 = 1.f + ex2(fminf(-LOG2E * g1, 60.f));
        const float r = rcp(e0 * e1);
        h[j] = pack2(g0 * d[4 * j + 2] * (e1 * r), g1 * d[4 * j + 3] * (e0 * r));
    }
    stg128(dst, make_uint4(h[0], h[1], h[2], h[3]));
    mbar_arrive_warp(bars + (second ? FB_H2 : FB_H) * 8);
}
template <int a>
__device__ __forceinline__ void f1_main(const Params& P) {
    constexpr uint32_t ws = F_W + a * (72 - NRF) * 2048, st = a * NRF * 2048;
    const int f0 = (blockIdx.x - NENG) * 128 + a * 96, f1 = f0 + (a ? -64 : 64);
    uint32_t w[NRF][4];
    hold_back(F1_DELAY);
    f1_fetch(P, sb + st, f0, 0, 36);
    f1_fetch(P, sb + st + 36 * 2048, f1, 0, NRF - 36);
    asm volatile("cp.async.wait_all;" ::: "memory");
    nbar_sync(NB_G + a, 128);
    {
        const uint32_t fa = sb + st + unit_frag_addr(threadIdx.x);
#pragma unroll
        for (int u = 0; u < NRF; u++) ldsm4t(w[u], fa + u * 2048);
    }
    nbar_sync(NB_S, 288);
    f1_fetch(P, sb + ws, f1, NRF - 36, 72 - NRF);
    asm volatile("cp.async.wait_all;" ::: "memory");
    fence_async_smem();
    nbar_sync(NB_G + a, 128);
    if (threadIdx.x == 0) TG(79, 2);
#pragma unroll 1
    for (int q = 0; q < NJOB; q += 2) {
        f1_tile<a, false, 0>(w, ws, q);
        f1_tile<a, true, 0>(w, ws, q);
        f1_tile<a, false, 1>(w, ws, q + 1);
        f1_tile<a, true, 1>(w, ws, q + 1);
    }
}
#define TJ(q, k) do { if ((q) == first_job(job_batch(q))) TG(job_batch(q), k); } while (0)
__device__ __forceinline__ void publisher(uint32_t done, uint32_t ack, int stage) {
#pragma unroll 1
    for (int q = 0; q < NJOB; q++) {
        if (stage == F_H2) { mbar_wait(done - 8, q & 1); publish(F_H, q); }
        mbar_wait(done, q & 1);
        mbar_arrive(ack);
        TJ(q, 30);
        publish(stage, q);
        TJ(q, 31);
    }
}
__device__ __forceinline__ void f1_helper(const Params& P) {
    const int hw = warp_in_group();
    if (hw == 0) nbar_sync(NB_S, 288);
    if ((threadIdx.x & 31) == 0) {
        const bool second = blockIdx.x >= NENG + 16;
        if (hw == 0) {
            const uint32_t ep = this_launch();
#pragma unroll 1
            for (int q = 0; q < NJOB; q++) {
                const uint8_t* src = g_xf + (q & (RING - 1)) * XF_BYTES;
                const uint32_t fb = bars + (FB_FULL + (q & 1) * 3) * 8;
                mbar_wait(bars + (FB_EMPTY + (q & 1)) * 8, ((q >> 1) & 1) ^ 1);
#pragma unroll
                for (int g = 0; g < 3; g++) mbar_expect(fb + g * 8, 12288);
                flag_wait(F_XF, q, 16 * ep);
                TJ(q, 29);
#pragma unroll
                for (int g = 0; g < 3; g++) bulk_g2s(sb + F_X + (q & 1) * XF_BYTES + g * 12288, src + g * 12288, 12288, fb + g * 8);
            }
        } else if (hw == 1) {
            const uint32_t target = (second ? 17 : 15) * this_launch();
#pragma unroll 1
            for (int q = blockIdx.x < NENG + 32 ? 0 : NJOB; q < NJOB; q++) {
                [[maybe_unused]] int n = 0;
                while (!flag_up(second ? F_P2 : F_P1, q, target)) { SPIN_CHECK(n, 20); }
                fence_acq_gpu();
                mbar_arrive(bars + FB_JOB * 8);
                TJ(q, 25);
                mbar_wait(bars + FB_JOB * 8, q & 1);
            }
        } else if (hw == 2) {
#pragma unroll 1
            for (int q = blockIdx.x < NENG + 32 ? 0 : NJOB; q < NJOB; q++) {
                if (q == 0) mbar_arrive(bars + FB_JOB * 8);
                mbar_wait(bars + FB_RDONE * 8, q & 1);
                mbar_arrive(bars + FB_JOB * 8);
                TJ(q, 23);
                if (!second) publish(F_XF, q);
                else if (!job_chain(q)) publish(F_X1, job_batch(q));
                TJ(q, 26);
            }
        } else {
            hold_back(PF_DELAY);
#pragma unroll 1
            for (int j = 0; j < 24; j++) {
                const bf16* w = j >= 16 ? P.w2 : (j & 1) ? P.w3 : P.w1;
                asm volatile("cp.async.bulk.prefetch.L2.global [%0], %1;" :: "l"(w + (size_t)((j >= 16 ? j - 16 : j >> 1) * NF1 + blockIdx.x - NENG) * (2 * FF)), "r"(4 * FF) : "memory");
                hold_back(PF_PACE);
            }
            publisher(bars + FB_H2 * 8, bars + FB_RACK * 8, F_H2);
        }
    }
    __syncwarp();
}

__device__ __forceinline__ void add8(float* f, uint4 a) {
    f[0] += bf_lo(a.x); f[1] += bf_hi(a.x); f[2] += bf_lo(a.y); f[3] += bf_hi(a.y);
    f[4] += bf_lo(a.z); f[5] += bf_hi(a.z); f[6] += bf_lo(a.w); f[7] += bf_hi(a.w);
}
__device__ __forceinline__ void set8(float* f, uint4 a) {
    f[0] = bf_lo(a.x); f[1] = bf_hi(a.x); f[2] = bf_lo(a.y); f[3] = bf_hi(a.y);
    f[4] = bf_lo(a.z); f[5] = bf_hi(a.z); f[6] = bf_lo(a.w); f[7] = bf_hi(a.w);
}
__device__ __forceinline__ void ln0_rows(const Params& P, int r) {
    const int lane = threadIdx.x & 31, l = lane < 24 ? lane : 0;
    const uint4* xrow = (const uint4*)(P.x + r * DM) + l;
    uint4 xw[3];
#pragma unroll
    for (int k = 0; k < 3; k++) xw[k] = __ldg(xrow + 24 * k);
    asm volatile("prefetch.global.L2 [%0];" :: "l"(P.x + (r + 16) * DM + (lane < 9 ? lane : 0) * 64));
#pragma unroll 1
    for (int seg = 0; seg < NSEG; seg++) {
#pragma unroll 1
        for (int h = 0; h < 2; h++) {
            float f[24];
#pragma unroll
            for (int k = 0; k < 3; k++) set8(&f[k * 8], xw[k]);
            if (2 * seg + h + 1 < 2 * NSEG) {
#pragma unroll
                for (int k = 0; k < 3; k++) xw[k] = __ldg(xrow + (2 * seg + h + 1) * (16 * DM / 8) + 24 * k);
            }
            float s = 0.f, q = 0.f;
#pragma unroll
            for (int j = 0; j < 24; j++) s += f[j];
            if (lane >= 24) s = 0.f;
#pragma unroll
            for (int o = 16; o; o >>= 1) s += __shfl_xor_sync(~0u, s, o);
            const float mean = s * (1.f / DM);
#pragma unroll
            for (int j = 0; j < 24; j++) { f[j] -= mean; q += f[j] * f[j]; }
            if (lane >= 24) q = 0.f;
#pragma unroll
            for (int o = 16; o; o >>= 1) q += __shfl_xor_sync(~0u, q, o);
            const float rstd = rsqrtf(q * (1.f / DM) + 1e-5f);
            if (lane < 24) {
                uint8_t* d = g_x + seg * XIMG + (l >> 3) * 8192 + (r + 16 * h) * 128 + (((l & 7) ^ (r & 7)) << 4);
#pragma unroll
                for (int k = 0; k < 3; k++) {
                    const float* y = &f[8 * k];
                    stg128(d + k * 24576, make_uint4(pack2(y[0] * rstd, y[1] * rstd), pack2(y[2] * rstd, y[3] * rstd), pack2(y[4] * rstd, y[5] * rstd), pack2(y[6] * rstd, y[7] * rstd)));
                }
            }
        }
        __syncwarp();
        if (lane == 0 && seg == 0) TG(79, 4);
        if (lane == 0) publish(F_X0, seg);
        if (lane == 0 && seg == 0) TG(79, 5);
        __syncwarp();
    }
}

template <bool SECOND, bool CHAIN>
__device__ __forceinline__ void reduce_job(const Params& P, int q) {
    constexpr int NP = SECOND ? NP2 : NP1;
    const int t = fresh_tid() - 256, p = (fresh_bid() - NENG) & 15;
    const int b = job_batch(q), seg = CHAIN ? b - LAG : b, lane = t & 31;
    const bool act = !(t & 1);
    const uint32_t ro = q & (RING - 1), po = p * (DM * 4) + t * 16, so = 2048 - t * 16 + (t >> 1) * 4;
    const int fa = (t >> 2) * 16 + (t & 3) * 2, fs = 512 + (t >> 5) * 16 + ((t >> 2) & 7) + (t & 2) * 4;
    const uint32_t row = (seg * 32 + p * 2) * DM;
    uint8_t* const r1 = g_r1 + ro * PART + po;
    uint8_t* const r2 = g_r2 + seg * PART + po;
    float f[10];
    uint4 x;
    uint32_t y;
    {
        const uint8_t* src = (SECOND ? g_p2 : g_p1) + ro * (NP * PART) + po;
        uint4 a[NP];
        uint32_t c[NP];
        mbar_wait(bars + FB_JOB * 8, q & 1);
#pragma unroll
        for (int k = 0; k < NP; k++) { a[k] = ld_rlx128(src + k * PART); c[k] = ld_rlx(src + so + k * PART); }
        if (SECOND || CHAIN) {
            x = ld_rlx128(SECOND ? r1 : r2); y = ld_rlx((SECOND ? r1 : r2) + so);
        } else {
            const bf16* xr = P.x + row;
            const uint32_t a0 = ld_rlx(xr + fa), b0 = ld_rlx(xr + fa + 8), a1 = ld_rlx(xr + fa + DM), b1 = ld_rlx(xr + fa + DM + 8);
            const uint32_t s0 = ld_rlx(xr + (fs & ~1)), s1 = ld_rlx(xr + (fs & ~1) + DM);
            x = make_uint4(__byte_perm(a0, a1, 0x5410), __byte_perm(b0, b1, 0x5410), __byte_perm(a0, a1, 0x7632), __byte_perm(b0, b1, 0x7632));
            y = __byte_perm(s0, s1, (fs & 1) ? 0x7632 : 0x5410);
        }
        set8(f, a[0]); f[8] = bf_lo(c[0]); f[9] = bf_hi(c[0]);
#pragma unroll
        for (int k = 1; k < NP; k++) { add8(f, a[k]); f[8] += bf_lo(c[k]); f[9] += bf_hi(c[k]); }
    }
    add8(f, x);
    x = make_uint4(pack2(f[0], f[1]), pack2(f[2], f[3]), pack2(f[4], f[5]), pack2(f[6], f[7]));
    y = pack2(f[8] + bf_lo(y), f[9] + bf_hi(y));
    if (SECOND && CHAIN) {
        bf16* o = P.out + row;
        stg32(o + fa, __byte_perm(x.x, x.z, 0x5410));
        stg32(o + fa + 8, __byte_perm(x.y, x.w, 0x5410));
        stg32(o + fa + DM, __byte_perm(x.x, x.z, 0x7632));
        stg32(o + fa + DM + 8, __byte_perm(x.y, x.w, 0x7632));
        stg16(o + fs + (act ? 0 : DM), act ? y : y >> 16);
        return;
    }
    set8(f, x);
    f[8] = act ? bf_lo(y) : 0.f; f[9] = act ? 0.f : bf_hi(y);
    float st[4];
    st[0] = (f[0] + f[2]) + (f[4] + f[6]) + f[8]; st[2] = (f[0] * f[0] + f[2] * f[2]) + (f[4] * f[4] + f[6] * f[6]) + f[8] * f[8];
    st[1] = (f[1] + f[3]) + (f[5] + f[7]) + f[9]; st[3] = (f[1] * f[1] + f[3] * f[3]) + (f[5] * f[5] + f[7] * f[7]) + f[9] * f[9];
    {
        const bool u = lane & 1, v = lane & 2;
        st[0] = (u ? st[1] : st[0]) + __shfl_xor_sync(~0u, u ? st[0] : st[1], 1);
        st[2] = (u ? st[3] : st[2]) + __shfl_xor_sync(~0u, u ? st[2] : st[3], 1);
        st[0] = (v ? st[2] : st[0]) + __shfl_xor_sync(~0u, v ? st[0] : st[2], 2);
        st[0] = (st[0] + __shfl_xor_sync(~0u, st[0], 4)) + (__shfl_xor_sync(~0u, st[0], 8) + __shfl_xor_sync(~0u, st[0], 12));
        if (!(lane & 12)) sts32(sb + F_RED + (t >> 4) * 16 + (lane & 3) * 4, fu(st[0]));
    }
    nbar_sync(NB_R, 128);
#pragma unroll
    for (int k = 0; k < 8; k++) {
        const uint4 z = lds128(sb + F_RED + k * 16);
        if (k == 0) { st[0] = uf(z.x); st[1] = uf(z.y); st[2] = uf(z.z); st[3] = uf(z.w); }
        else { st[0] += uf(z.x); st[1] += uf(z.y); st[2] += uf(z.z); st[3] += uf(z.w); }
    }
    stg128(SECOND ? r2 : r1, x);
    if (act) stg32((SECOND ? r2 : r1) + so, y);
    const float m0 = st[0] * (1.f / DM), m1 = st[1] * (1.f / DM);
    const float q0 = rsqrtf(fmaxf(st[2] * (1.f / DM) - m0 * m0, 0.f) + 1e-5f), q1 = rsqrtf(fmaxf(st[3] * (1.f / DM) - m1 * m1, 0.f) + 1e-5f);
    constexpr int KB = SECOND ? 8192 : 4096;
    uint8_t* d = (SECOND ? g_x + (b + LAG) * XIMG + (USE_ONE && b + LAG >= NSEG ? 0 : 4096) : g_xf + ro * XF_BYTES) + p * 256;
#pragma unroll
    for (int e = 0; e < 2; e++) {
        const float m = e ? m1 : m0, r = e ? q1 : q0;
#pragma unroll
        for (int h = 0; h < 2; h++)
            stg32(d + (fa >> 6) * KB + (t & 3) * 4 + e * 128 + (((((fa >> 3) & 6) + h) ^ ((2 * p + e) & 7)) << 4), pack2((f[2 * h + e] - m) * r, (f[4 + 2 * h + e] - m) * r));
    }
    stg16(d + 8 * KB + (t & 1) * 128 + ((((fs >> 3) & 7) ^ ((2 * p + (t & 1)) & 7)) << 4) + (fs & 7) * 2, pack2(act ? (f[8] - m0) * q0 : (f[9] - m1) * q1, 0.f));
}
template <bool SECOND>
__device__ __forceinline__ void reducer(const Params& P) {
#pragma unroll 1
    for (int q = 0; q < NJOB; q++) {
        if (job_chain(q)) reduce_job<SECOND, true>(P, q);
        else reduce_job<SECOND, false>(P, q);
        mbar_arrive_warp(bars + FB_RDONE * 8);
    }
}

__host__ __device__ constexpr int d_units(int kind) { return kind ? 28 * kind : 52; }
__host__ __device__ constexpr int d_regs(int kind) { return kind == 0 ? 29 : kind == 1 ? 28 : 25; }
__host__ __device__ constexpr uint64_t d_mask(int kind) {
    uint64_t m = 0;
    for (int u = 0; u < d_units(kind); u++) if (u * d_regs(kind) / d_units(kind) != (u + 1) * d_regs(kind) / d_units(kind)) m |= 1ull << u;
    return m;
}
__host__ __device__ constexpr int d_group(bool side, int g) { return g < 3 ? 12 * g : side ? 20 + 2 * g : 4 + 12 * g; }
__device__ __forceinline__ int d_tile(int ds, int wg) { return ds < 30 ? (ds % 3) * 3 + wg : ds == 30 ? 2 * wg : wg ? 6 + wg : 5; }
template <int KIND, int wg>
__device__ __forceinline__ void d_main() {
    constexpr int NR = d_regs(KIND), NT = KIND ? KIND : 1, NG = 4, STR = KIND ? D_STR2 : D_STR;
    constexpr uint64_t M = d_mask(KIND);
    uint32_t w[NR][4];
    {
        const uint32_t fa = sb + wg * (STR * 2048) + unit_frag_addr(threadIdx.x);
        mbar_wait(bars + DB_WL * 8, 0);
#pragma unroll
        for (int u = 0; u < NR; u++) ldsm4t(w[u], fa + u * 2048);
        nbar_arrive(NB_W, 416);
        mbar_wait(bars + DB_WL * 8, 1);
        if (threadIdx.x == 0) TG(79, 2);
    }
    const uint64_t da = mkdesc(wg * (STR * 2048), 1024, 1024, 1), db = mkdesc(3 * STR * 2048, 512, 512, 2);
    const int tid = fresh_tid(), ds = fresh_bid() - NENG - NF1;
    const bool w2 = ds >= 15;
    uint8_t* const dst0 = (w2 ? g_p2 + ((ds - 15) / 3) * PART : g_p1 + (ds / 3) * PART)
                        + (d_tile(ds, wg) * 64 + ((tid >> 5) & 3) * 16 + ((tid & 31) >> 2) * 2) * 4 + (w2 ? 4 : 1) * (tid & 3) * (DM * 4);
    const uint32_t js = w2 ? DM * 4 : DM * 16, qs = (w2 ? NP2 : NP1) * PART;
#pragma unroll 1
    for (int q = 0; q < NJOB; q++) {
        float d[NT][16];
#pragma unroll
        for (int g = 0; g < NG; g++) {
            mbar_wait(bars + (DB_FULL + g) * 8, q & 1);
            wg_fence();
#pragma unroll
            for (int j = 0; j < 24; j++) {
                const int u = d_group(KIND, g) * NT + j, r = popc_below(M, u < 64 ? u : 0);
                if (u >= d_group(KIND, g + 1) * NT) continue;
                if ((M >> u) & 1) wg_rs32<1>(d[u % NT], w[r < NR ? r : 0], db + (u / NT) * 64, u >= NT);
                else wg_ss32<1>(d[u % NT], da + (u - r) * 128, db + (u / NT) * 64, u >= NT);
            }
            wg_commit();
            if (g > 0) { wg_wait<1>(); mbar_arrive_warp(bars + (DB_EMPTY + g - 1) * 8); }
        }
        mbar_wait(bars + (DB_P + 1) * 8, (q & 1) ^ 1);
        uint8_t* const dst = dst0 + (q & (RING - 1)) * qs;
        wg_wait_acc<0, 16 * NT>(&d[0][0]);
        mbar_arrive_warp(bars + (DB_EMPTY + NG - 1) * 8);
#pragma unroll
        for (int j = 0; j < 4 * NT; j++) {
            const float* y = &d[j >> 2][4 * (j & 3)];
            stg64(dst + (j >> 2) * 256 + (j & 3) * js, pack2(y[0], y[1]), pack2(y[2], y[3]));
        }
        mbar_arrive_warp(bars + DB_P * 8);
    }
}
template <bool W2, bool SIDE>
__device__ __forceinline__ void d_producer(int blk0, int blk1) {
    const uint32_t target = (W2 ? NF1 : NENG) * this_launch();
    uint32_t rdy = 0;
#pragma unroll 1
    for (int q = 0; q < NJOB; q++) {
        const uint32_t so = (q & (RING - 1)) * (W2 ? H_BYTES : O_BYTES);
#pragma unroll
        for (int g = 0; g < 4; g++) {
            if (g == 0 || (g == 2 && W2)) {
                if (!(rdy & 1)) {
                    [[maybe_unused]] int n = 0;
                    do {
                        if (W2) {
                            const bool r0 = flag_up(g ? F_H2 : F_H, q, target), r1 = flag_up(g ? F_H : F_H2, q + g / 2, target), r2 = flag_up(g ? F_H2 : F_H, q + 1, target);
                            rdy = !r0 ? 0 : !r1 ? 1 : !r2 ? 3 : 7;
                        } else {
                            rdy = !flag_up(F_O, job_batch(q), target) ? 0 : q >= LAG && q < NJOB - LAG ? 3 : 1;
                        }
                        SPIN_CHECK(n, 30);
                    } while (!rdy);
                    fence_acq_gpu();
                    fence_async_glb();
                }
                rdy >>= 1;
            }
            constexpr uint32_t slots = 3 * (SIDE ? D_STR2 : D_STR) * 2048;
            const uint32_t off = d_group(SIDE, g) * 1024, bytes = d_group(SIDE, g + 1) * 1024 - off;
            mbar_wait(bars + (DB_EMPTY + g) * 8, (q & 1) ^ 1);
            mbar_expect(bars + (DB_FULL + g) * 8, bytes);
            bulk_g2s(sb + slots + off, (W2 ? g_h : g_o) + (so + (g < 2 ? blk0 : blk1) * 4096 + off), bytes, bars + (DB_FULL + g) * 8);
            if (g == 0) TJ(q, 29);
        }
    }
}
__device__ __forceinline__ void d_helper(const Params& P, int ds) {
    const int lane = threadIdx.x & 31, hw = warp_in_group();
    const bool w2 = ds >= 15, side = ds >= 30;
    const int kr = (w2 ? ds - 15 : ds) / 3, blk0 = kr * (w2 ? 6 : 13), blk1 = w2 ? 30 + kr * 7 : blk0, str = side ? D_STR2 : D_STR;
    if (hw == 0) {
        hold_back(w2 ? W2_DELAY : D_DELAY);
#pragma unroll 1
        for (int ph = 0; ph < 2; ph++) {
            if (ph) nbar_sync(NB_W, 416);
            if (lane == 0) mbar_expect(bars + DB_WL * 8, (!side ? (ph ? 69 : 87) : ds == 30 ? (ph ? 62 : 78) : (ph ? 31 : 81)) * 2048);
            __syncwarp();
#pragma unroll 1
            for (int x = lane; x < 192; x += 32) {
                constexpr uint64_t M0 = d_mask(0), M1 = d_mask(1), M2 = d_mask(2);
                const int wg = x >> 6, u = x & 63, kind = !side ? 0 : wg < 32 - ds ? 2 : 1;
                const uint64_t m = kind == 0 ? M0 : kind == 1 ? M1 : M2;
                const int ks = kind == 2 ? u >> 1 : u, j = ks >> 2, r = popc_below(m, u);
                const int pos = (j < 6 ? blk0 : blk1) + j, kb = !w2 ? pos : pos < 36 ? pos * 2 : (pos - 36) * 2 + 1;
                if (u < d_units(kind) && ((m >> u) & 1) != ph)
                    tma_unit(sb + (wg * str + (ph ? u - r : r)) * 2048, w2 ? &P.tmW2 : &P.tmWo,
                             kb * 4 + (ks & 3), d_tile(ds, wg) + (kind == 2 ? u & 1 : 0), bars + DB_WL * 8);
            }
        }
        __syncwarp();
        if (lane == 0) {
            if (!w2) d_producer<false, false>(blk0, blk1);
            else if (!side) d_producer<true, false>(blk0, blk1);
            else d_producer<true, true>(blk0, blk1);
        }
    } else if (hw == 1 && lane == 0) {
        publisher(bars + DB_P * 8, bars + (DB_P + 1) * 8, w2 ? F_P2 : F_P1);
    }
    __syncwarp();
}

__device__ __forceinline__ void sign_off() { mbar_arrive_warp(sb + SM_DONE); }
__device__ __forceinline__ void sign_off_helper(uint32_t nap) {
    if (warp_in_group() < 3) { sign_off(); return; }
    uint32_t ok;
    const uint32_t t0 = timer_lo(), ep = this_launch();
    do {
        __nanosleep(nap);
        asm volatile("{.reg .pred p; mbarrier.test_wait.parity.shared::cta.b64 p, [%1], 0; selp.u32 %0, 1, 0, p;}" : "=r"(ok) : "r"(sb + SM_DONE) : "memory");
    } while (!ok && timer_lo() - t0 < TIME_LIMIT);
    if (!ok || (sb & 0x3ffff) != SM_ORG) __trap();
    if (fresh_tid() == NTHREADS - 32) { g_epoch[fresh_bid()][0] = ep; TG(79, 1); }
    __syncwarp();
}

__global__ void __cluster_dims__(2, 1, 1) __launch_bounds__(NTHREADS, 1) fused_kernel(const __grid_constant__ Params P) {
    const int wg = __shfl_sync(~0u, threadIdx.x >> 7, 0);
    const int bid = blockIdx.x;
    if (threadIdx.x >= NTHREADS - 32) sts32(sb + SM_ONES + (threadIdx.x & 31) * 4, 0x3f803f80u);
    if (threadIdx.x == 0) {
        TG(79, 0);
        mbar_init(sb + SM_DONE, 15);
        sts32(sb + SM_XRDY, 0);
        if (bid < NENG) {
            for (int i = 0; i < 9; i++) mbar_init(bars + (EB_FULL + i) * 8, i < 6 ? 1 : 12);
            mbar_init(bars + EB_V0 * 8, 4); mbar_init(bars + EB_WL * 8, 3); mbar_init(bars + EB_WO * 8, 2); mbar_init(bars + EB_STEP * 8, 8);
            mbar_init(bars + EB_SM * 8, 1); mbar_init(bars + EB_SX * 8, 1); mbar_init(bars + EB_OX * 8, 1);
            mbar_init(bars + EB_QF * 8, 4); mbar_init(bars + EB_KF * 8, 8); mbar_init(bars + EB_CONS * 8, 4); mbar_init(bars + EB_OST * 8, 4);
            mbar_init(bars + EB_OFREE * 8, 1); mbar_init(bars + EB_MEM0 * 8, 4); mbar_init(bars + EB_MEMA * 8, 1); mbar_init(bars + EB_MEM * 8, 5); mbar_init(bars + EB_PRDY * 8, 1);
        } else if (bid < NENG + NF1) {
            for (int i = 0; i < 8; i++) mbar_init(bars + (FB_FULL + i) * 8, i < 6 ? 1 : 8);
            mbar_init(bars + FB_H * 8, 8); mbar_init(bars + FB_H2 * 8, 8); mbar_init(bars + FB_RACK * 8, 1); mbar_init(bars + FB_JOB * 8, 2); mbar_init(bars + FB_RDONE * 8, 4);
        } else {
            for (int i = 0; i < 4; i++) { mbar_init(bars + (DB_FULL + i) * 8, 1); mbar_init(bars + (DB_EMPTY + i) * 8, 12); }
            mbar_init(bars + DB_WL * 8, 1); mbar_init(bars + DB_P * 8, 12); mbar_init(bars + (DB_P + 1) * 8, 1);
        }
        asm volatile("fence.mbarrier_init.release.cluster;" ::: "memory");
    }
    __syncthreads();
    asm volatile("barrier.cluster.arrive.relaxed.aligned; barrier.cluster.wait.aligned;" ::: "memory");
    if (bid < NENG) {
        if (wg == 0) { reg_inc<REGQ>(); engine_main<0>(P); sign_off(); cluster_sync_all(); }
        else if (wg == 1) { reg_inc<REGK>(); engine_main<1>(P); sign_off(); cluster_sync_all(); }
        else if (wg == 2) { reg_inc<REGV>(); engine_main<2>(P); sign_off(); cluster_sync_all(); }
        else { reg_dec<24>(); engine_helper(P); sign_off_helper(1000); cluster_sync_all(); }
    } else if (bid < NENG + NF1) {
        if (wg < 2) {
            reg_inc<REGF>();
            if (wg == 0) f1_main<0>(P); else f1_main<1>(P);
            sign_off();
        } else if (wg == 2) {
            reg_dec<488 - 2 * REGF>();
            if (bid >= NENG + 32) ln0_rows(P, (bid - NENG - 32) * 4 + warp_in_group());
            else if (bid < NENG + 16) reducer<false>(P);
            else reducer<true>(P);
            sign_off();
        } else {
            reg_dec<24>();
            f1_helper(P);
            sign_off_helper(100);
        }
    } else {
        const int ds = bid - NENG - NF1;
        if (wg < 3) {
            reg_inc<160>();
            if (ds < 30) { if (wg == 0) d_main<0, 0>(); else if (wg == 1) d_main<0, 1>(); else d_main<0, 2>(); }
            else { if (wg == 0) d_main<2, 0>(); else if (wg == 2) d_main<1, 2>(); else if (ds == 30) d_main<2, 1>(); else d_main<1, 1>(); }
            sign_off();
        } else {
            reg_dec<32>();
            d_helper(P, ds);
            sign_off_helper(500);
        }
    }
}

typedef CUresult (*EncodeFn)(CUtensorMap*, CUtensorMapDataType, cuuint32_t, void*, const cuuint64_t*, const cuuint64_t*,
                             const cuuint32_t*, const cuuint32_t*, CUtensorMapInterleave, CUtensorMapSwizzle,
                             CUtensorMapL2promotion, CUtensorMapFloatOOBfill);

void make_map(EncodeFn enc, CUtensorMap* m, const void* p, int rows, int cols) {
    cuuint64_t dims[2] = {(cuuint64_t)cols, (cuuint64_t)rows};
    cuuint64_t strides[1] = {(cuuint64_t)cols * 2};
    cuuint32_t box[2] = {64, 16};
    cuuint32_t es[2] = {1, 1};
    enc(m, CU_TENSOR_MAP_DATA_TYPE_BFLOAT16, 2, (void*)p, dims, strides, box, es, CU_TENSOR_MAP_INTERLEAVE_NONE,
        CU_TENSOR_MAP_SWIZZLE_128B, CU_TENSOR_MAP_L2_PROMOTION_L2_128B, CU_TENSOR_MAP_FLOAT_OOB_FILL_NONE);
}

}

extern "C" void kernel_launch(void* const* d_in, const int* in_sizes, int n_in, void* d_out, int out_size) {
    (void)in_sizes; (void)n_in; (void)out_size;
    static EncodeFn enc = nullptr;
    if (!enc) {
        void* fn = nullptr;
        cudaDriverEntryPointQueryResult qr;
        cudaGetDriverEntryPoint("cuTensorMapEncodeTiled", &fn, cudaEnableDefault, &qr);
        enc = (EncodeFn)fn;
        cudaFuncSetAttribute(fused_kernel, cudaFuncAttributeMaxDynamicSharedMemorySize, SM_TOTAL);
    }
    Params P;
    make_map(enc, &P.tmWq, d_in[2], DM, 4096);
    make_map(enc, &P.tmWk, d_in[3], DM, 4096);
    make_map(enc, &P.tmWv, d_in[4], DM, 4096);
    make_map(enc, &P.tmWo, d_in[5], 4096, DM);
    make_map(enc, &P.tmW2, d_in[10], FF, DM);
    P.x = (const bf16*)d_in[0];
    P.mem0 = (const bf16*)d_in[1];
    P.w1 = (const bf16*)d_in[8];
    P.w3 = (const bf16*)d_in[9];
    P.w2 = (const bf16*)d_in[10];
    P.out = (bf16*)d_out;
    P.zero = 0;
    fused_kernel<<<NCTA, NTHREADS, SM_TOTAL>>>(P);
}
```

```cpp
#include <cuda_runtime.h>
#include <cuda_bf16.h>
#include <cuda.h>
#include <stdint.h>

typedef __nv_bfloat16 bf16;

namespace {

constexpr int DM = 576, FF = 4608, NSEG = 64;
constexpr int NENG = 64, NF1 = 36, ND = 32, NCTA = NENG + NF1 + ND;
constexpr int NTHREADS = 512;
#define LAG 7
#define RING 16
static_assert(RING >= 2 * LAG + 2, "ring too short");
#define USE_ONE 1
constexpr int NSTEP = NSEG + LAG;
constexpr int NJOB = 2 * NSEG;
__device__ __forceinline__ int job_chain(int q) { return q < LAG ? 0 : q < NJOB - LAG ? (q - LAG) & 1 : 1; }
__device__ __forceinline__ int job_batch(int q) { return q < LAG ? q : q < NJOB - LAG ? (q + LAG) >> 1 : q - NSEG + LAG; }
__device__ __forceinline__ int first_job(int b) { return b < LAG ? b : b < NSEG ? 2 * b - LAG : b + NSEG - LAG; }

enum { F_X0 = 0, F_X1, F_O, F_P1, F_XF, F_H, F_P2, F_H2, F_COUNT };
constexpr int B_ZERO = 95;
__device__ uint32_t g_flag[F_COUNT][NJOB + 4][8];
__device__ uint32_t g_epoch[NCTA][8];
constexpr int XIMG = 9 * 8192;
constexpr int XF_BYTES = 9 * 4096;
constexpr int O_BYTES = 65 * 4096;
constexpr int H_BYTES = 72 * 4096;
constexpr int PART = 16 * DM * 4;
constexpr int NP1 = 5, NP2 = 6;
__device__ __align__(1024) uint8_t g_x[NSTEP * XIMG];
__device__ __align__(1024) uint8_t g_xf[RING * XF_BYTES];
__device__ __align__(1024) uint8_t g_o[RING * O_BYTES];
__device__ __align__(1024) uint8_t g_h[RING * H_BYTES];
__device__ __align__(1024) uint8_t g_p1[RING * NP1 * PART];
__device__ __align__(1024) uint8_t g_p2[RING * NP2 * PART];
__device__ __align__(1024) uint8_t g_r1[RING * PART];
__device__ __align__(1024) uint8_t g_r2[NSEG * PART];
#define AR_STR 4352
constexpr int AR_SLOT = 144 * AR_STR;
__device__ __align__(1024) uint8_t g_ar[4 * AR_SLOT];

struct Params {
    CUtensorMap tmWq, tmWk, tmWv, tmWo, tmW2;
    const bf16 *x, *mem0, *w1, *w3, *w2;
    bf16* out;
    uint32_t zero;
};

constexpr uint32_t SM_ORG = 1024;
extern __shared__ __align__(1024) uint8_t smem_raw[];
#define sb ((uint32_t)__cvta_generic_to_shared(smem_raw))
#define bars (sb + SM_BAR)
constexpr int SM_BAR = 231936;
constexpr int SM_TOTAL = SM_BAR + 512;
#define NRQ 25
#define NRK 25
#define NRV 25
#define REGQ 160
#define REGK 168
#define REGV 160
constexpr int E_WQ = 0;
constexpr int E_WK = E_WQ + (36 - NRQ) * 2048;
constexpr int E_WV = E_WK + (36 - NRK) * 2048;
constexpr int E_WO = E_WV + (36 - NRV) * 2048;
constexpr int E_MEM = E_WO + 36 * 2048;
constexpr int E_R0 = E_MEM + 18432;
constexpr int E_R2 = E_R0 + 8192, E_R3 = E_R2 + 8192, E_R1 = E_R3 + 8192;
constexpr int E_SX = E_R1;
constexpr int E_QT = E_R1 + 8192;
constexpr int E_KT = E_QT + 8192;
constexpr int E_VT = E_KT + 10240;
constexpr int E_OM = E_VT + 10240;
constexpr int E_QM = E_OM + 4096;
constexpr int E_SR = E_QM + 2048;
constexpr int E_SL = E_SR + 2560;
constexpr int E_END = E_SL + 2048;
static_assert(E_END <= SM_BAR, "engine smem overflow");
static_assert(E_WO + (NRQ + NRK + NRV) * 2048 <= E_OM, "weight staging: the peer writes there without asking");
enum {
    EB_FULL = 0  , EB_EMPTY = 6  , EB_V0 = 9, EB_WL, EB_WO, EB_STEP, EB_SM, EB_SX, EB_OX,
    EB_QF, EB_KF, EB_CONS, EB_OST, EB_OFREE, EB_MEM0, EB_MEMA, EB_MEM, EB_PRDY, EB_XR
};
enum { NB_G = 1, NB_LEAD, NB_QK, NB_S, NB_OM, NB_W, NB_R, NB_T, NB_PV, NB_WO, NB_V, NB_KT, NB_S2, NB_VL };
constexpr int NB_VL2 = NB_LEAD;
constexpr int REGF = 208, NRF = 41;
constexpr int F_W = 0;
constexpr int F_X = 2 * (72 - NRF) * 2048;
constexpr int F_RED = F_X + 2 * XF_BYTES;
static_assert(F_RED + 512 <= SM_BAR && 2 * NRF * 2048 <= F_RED, "F1 smem overflow");
enum { FB_FULL = 0  , FB_EMPTY = 6  , FB_H = 8, FB_H2, FB_RACK, FB_JOB, FB_RDONE };
constexpr int D_STR = 29, D_STR2 = 31;
static_assert(3 * D_STR * 2048 + 13 * 4096 <= SM_BAR && 3 * D_STR2 * 2048 + 7 * 4096 <= SM_BAR, "D smem overflow");
enum { DB_FULL = 0, DB_EMPTY = 4, DB_WL = 8, DB_P };
constexpr int SM_DONE = SM_BAR + 248, SM_ONES = SM_BAR + 384;
constexpr uint32_t TIME_LIMIT = 2000000000u;

#define SPIN_CHECK(n, code)

#define TS(thr, step, k)
#define TX(thr, k)
#define TG(step, k)
#define PROF_INC(n, k)

#define jitter()
__device__ __forceinline__ uint32_t mapa(uint32_t a, uint32_t r) {
    uint32_t o; asm("mapa.shared::cluster.u32 %0, %1, %2;" : "=r"(o) : "r"(a), "r"(r)); return o;
}
__device__ __forceinline__ void mbar_init(uint32_t b, uint32_t cnt) {
    asm volatile("mbarrier.init.shared::cta.b64 [%0], %1;" :: "r"(b), "r"(cnt) : "memory");
}
__device__ __forceinline__ void mbar_arrive(uint32_t b) {
    jitter();
    asm volatile("mbarrier.arrive.shared::cta.b64 _, [%0];" :: "r"(b) : "memory");
}
__device__ __forceinline__ void mbar_arrive_warp(uint32_t b) {
    jitter();
    asm volatile("{.reg .pred p; bar.warp.sync -1; elect.sync _|p, -1; @p mbarrier.arrive.shared::cta.b64 _, [%0];}" :: "r"(b) : "memory");
}
__device__ __forceinline__ void mbar_arrive_remote(uint32_t b) {
    asm volatile("fence.release.sync_restrict::shared::cta.cluster; mbarrier.arrive.relaxed.cluster.shared::cluster.b64 _, [%0];" :: "r"(b) : "memory");
}
__device__ __forceinline__ void mbar_expect(uint32_t b, uint32_t bytes) {
    asm volatile("mbarrier.arrive.expect_tx.shared::cta.b64 _, [%0], %1;" :: "r"(b), "r"(bytes) : "memory");
}
__device__ __forceinline__ uint32_t mbar_wait(uint32_t b, uint32_t par) {
    uint32_t ok; [[maybe_unused]] int n = 0;
    jitter();
    while (true) {
        asm volatile("{.reg .pred p; mbarrier.try_wait.parity.shared::cta.b64 p, [%1], %2; selp.u32 %0, 1, 0, p;}"
                     : "=r"(ok) : "r"(b), "r"(par) : "memory");
        if (ok) break;
        SPIN_CHECK(n, 1000 + ((b & 511) >> 3));
    }
    return ok;
}
__device__ __forceinline__ bool mbar_test(uint32_t b, uint32_t par) {
    uint32_t ok;
    asm volatile("{.reg .pred p; mbarrier.test_wait.parity.shared::cta.b64 p, [%1], %2; selp.u32 %0, 1, 0, p;}" : "=r"(ok) : "r"(b), "r"(par) : "memory");
    return ok;
}
__device__ __forceinline__ void mbar_wait_cl(uint32_t b, uint32_t par) {
    uint32_t ok; [[maybe_unused]] int n = 0;
    jitter();
    while (true) {
        asm volatile("{.reg .pred p; mbarrier.try_wait.parity.relaxed.cluster.shared::cta.b64 p, [%1], %2; selp.u32 %0, 1, 0, p;}"
                     : "=r"(ok) : "r"(b), "r"(par) : "memory");
        if (ok) break;
        SPIN_CHECK(n, 1000 + ((b & 511) >> 3));
    }
    asm volatile("fence.acquire.sync_restrict::shared::cluster.cluster;" ::: "memory");
}
__device__ __forceinline__ void nbar_sync(int id, int n) { jitter(); asm volatile("bar.sync %0, %1;" :: "r"(id), "r"(n) : "memory"); }
__device__ __forceinline__ void nbar_arrive(int id, int n) { jitter(); asm volatile("bar.arrive %0, %1;" :: "r"(id), "r"(n) : "memory"); }
__device__ __forceinline__ void cluster_sync_all() {
    asm volatile("barrier.cluster.arrive.release.aligned; barrier.cluster.wait.acquire.aligned;" ::: "memory");
}
__device__ __forceinline__ void fence_async_smem() { asm volatile("fence.proxy.async.shared::cta;" ::: "memory"); }
__device__ __forceinline__ void fence_async_glb() { asm volatile("fence.proxy.async.global;" ::: "memory"); }
__device__ __forceinline__ void fence_rel_gpu() { asm volatile("fence.release.gpu;" ::: "memory"); }
__device__ __forceinline__ void fence_acq_gpu() { asm volatile("fence.acquire.gpu;" ::: "memory"); }
__device__ __forceinline__ void fence_gpu() { asm volatile("fence.acq_rel.gpu;" ::: "memory"); }
__device__ __forceinline__ int fresh_tid() { int t; asm volatile("mov.u32 %0, %%tid.x;" : "=r"(t)); return t; }
__device__ __forceinline__ int fresh_bid() { int t; asm volatile("mov.u32 %0, %%ctaid.x;" : "=r"(t)); return t; }
__device__ __forceinline__ uint32_t pin(uint32_t v) { asm volatile("" : "+r"(v)); return v; }
__device__ __forceinline__ int warp_in_group() { return __shfl_sync(~0u, (fresh_tid() >> 5) & 3, 0); }
__device__ __forceinline__ int cta_rank() { int t; asm volatile("mov.u32 %0, %%cluster_ctarank;" : "=r"(t)); return t; }
__device__ __forceinline__ uint32_t timer_lo() { uint32_t t; asm volatile("mov.u32 %0, %%globaltimer_lo;" : "=r"(t)); return t; }
__device__ __forceinline__ uint32_t keep(uint32_t v) { return __shfl_xor_sync(~0u, v, 0); }
__device__ __forceinline__ void red_add_u32(uint32_t* p, uint32_t v) {
    asm volatile("red.relaxed.gpu.global.add.u32 [%0], %1;" :: "l"(p), "r"(v) : "memory");
}
__device__ __forceinline__ uint32_t ld_rlx(const void* p) {
    uint32_t v; asm volatile("ld.relaxed.gpu.global.u32 %0, [%1];" : "=r"(v) : "l"(p) : "memory"); return v;
}
__device__ __forceinline__ uint2 ld_rlx64(const void* p) {
    uint2 v; asm volatile("ld.relaxed.gpu.global.v2.u32 {%0,%1}, [%2];" : "=r"(v.x), "=r"(v.y) : "l"(p) : "memory"); return v;
}
__device__ __forceinline__ uint4 ld_rlx128(const void* p) {
    uint4 v;
    asm volatile("ld.relaxed.gpu.global.v4.u32 {%0,%1,%2,%3}, [%4];" : "=r"(v.x), "=r"(v.y), "=r"(v.z), "=r"(v.w) : "l"(p) : "memory");
    return v;
}
__device__ __forceinline__ void stg128(void* p, uint4 v) {
    asm volatile("st.global.v4.b32 [%0], {%1,%2,%3,%4};" :: "l"(p), "r"(v.x), "r"(v.y), "r"(v.z), "r"(v.w) : "memory");
}
__device__ __forceinline__ void stg64(void* p, uint32_t a, uint32_t b) {
    asm volatile("st.global.v2.b32 [%0], {%1,%2};" :: "l"(p), "r"(a), "r"(b) : "memory");
}
__device__ __forceinline__ void stg16(void* p, uint32_t a) { asm volatile("st.global.b16 [%0], %1;" :: "l"(p), "h"((uint16_t)a) : "memory"); }
__device__ __forceinline__ void stg32(void* p, uint32_t a) { asm volatile("st.global.b32 [%0], %1;" :: "l"(p), "r"(a) : "memory"); }
__device__ __forceinline__ void st_async128(uint32_t a, uint32_t x, uint32_t y, uint32_t z, uint32_t w, uint32_t mb) {
    asm volatile("st.async.shared::cluster.mbarrier::complete_tx::bytes.v4.b32 [%0], {%1,%2,%3,%4}, [%5];"
                 :: "r"(a), "r"(x), "r"(y), "r"(z), "r"(w), "r"(mb) : "memory");
}
__device__ __forceinline__ void st_async64(uint32_t a, uint32_t x, uint32_t y, uint32_t mb) {
    asm volatile("st.async.shared::cluster.mbarrier::complete_tx::bytes.v2.b32 [%0], {%1,%2}, [%3];"
                 :: "r"(a), "r"(x), "r"(y), "r"(mb) : "memory");
}
__device__ __forceinline__ void sts128(uint32_t a, uint32_t x, uint32_t y, uint32_t z, uint32_t w) {
    asm volatile("st.shared.v4.b32 [%0], {%1,%2,%3,%4};" :: "r"(a), "r"(x), "r"(y), "r"(z), "r"(w) : "memory");
}
__device__ __forceinline__ void sts32(uint32_t a, uint32_t v) { asm volatile("st.shared.b32 [%0], %1;" :: "r"(a), "r"(v) : "memory"); }
__device__ __forceinline__ uint4 lds128(uint32_t a) {
    uint4 v; asm volatile("ld.shared.v4.b32 {%0,%1,%2,%3}, [%4];" : "=r"(v.x), "=r"(v.y), "=r"(v.z), "=r"(v.w) : "r"(a) : "memory"); return v;
}
__device__ __forceinline__ uint2 lds64(uint32_t a) {
    uint2 v; asm volatile("ld.shared.v2.b32 {%0,%1}, [%2];" : "=r"(v.x), "=r"(v.y) : "r"(a) : "memory"); return v;
}
__device__ __forceinline__ uint32_t lds32(uint32_t a) {
    uint32_t v; asm volatile("ld.shared.b32 %0, [%1];" : "=r"(v) : "r"(a) : "memory"); return v;
}
__device__ __forceinline__ void bulk_g2s(uint32_t dst, const void* src, uint32_t bytes, uint32_t mb) {
    asm volatile("cp.async.bulk.shared::cluster.global.mbarrier::complete_tx::bytes [%0], [%1], %2, [%3];"
                 :: "r"(dst), "l"(src), "r"(bytes), "r"(mb) : "memory");
}
__device__ __forceinline__ void bulk_s2g(void* dst, uint32_t src, uint32_t bytes) {
    asm volatile("cp.async.bulk.global.shared::cta.bulk_group [%0], [%1], %2;" :: "l"(dst), "r"(src), "r"(bytes) : "memory");
}
__device__ __forceinline__ void bulk_s2peer(uint32_t dst, uint32_t src, uint32_t bytes, uint32_t mb) {
    asm volatile("cp.async.bulk.shared::cluster.shared::cta.mbarrier::complete_tx::bytes [%0], [%1], %2, [%3];"
                 :: "r"(dst), "r"(src), "r"(bytes), "r"(mb) : "memory");
}
__device__ __forceinline__ void tma_unit(uint32_t dst, const CUtensorMap* tm, int kstep, int mgroup, uint32_t mb) {
    asm volatile("cp.async.bulk.tensor.2d.shared::cluster.global.mbarrier::complete_tx::bytes [%0], [%1, {%2,%3}], [%4];"
                 :: "r"(dst), "l"(tm), "r"(mgroup * 64), "r"(kstep * 16), "r"(mb) : "memory");
}
__device__ __forceinline__ void ldsm4(uint32_t* r, uint32_t a) {
    asm volatile("ldmatrix.sync.aligned.m8n8.x4.shared.b16 {%0,%1,%2,%3}, [%4];"
                 : "=r"(r[0]), "=r"(r[1]), "=r"(r[2]), "=r"(r[3]) : "r"(a) : "memory");
}
__device__ __forceinline__ void ldsm4t(uint32_t* r, uint32_t a) {
    asm volatile("ldmatrix.sync.aligned.m8n8.x4.trans.shared.b16 {%0,%1,%2,%3}, [%4];"
                 : "=r"(r[0]), "=r"(r[1]), "=r"(r[2]), "=r"(r[3]) : "r"(a) : "memory");
}
__device__ __forceinline__ void stsm4(uint32_t a, uint32_t r0, uint32_t r1, uint32_t r2, uint32_t r3) {
    asm volatile("stmatrix.sync.aligned.m8n8.x4.shared.b16 [%0], {%1,%2,%3,%4};" :: "r"(a), "r"(r0), "r"(r1), "r"(r2), "r"(r3) : "memory");
}
__device__ __forceinline__ void stsm4t(uint32_t a, uint32_t r0, uint32_t r1, uint32_t r2, uint32_t r3) {
    asm volatile("stmatrix.sync.aligned.m8n8.x4.trans.shared.b16 [%0], {%1,%2,%3,%4};" :: "r"(a), "r"(r0), "r"(r1), "r"(r2), "r"(r3) : "memory");
}
__device__ __forceinline__ uint32_t pack2(float lo, float hi) {
    uint32_t d; asm("cvt.rn.bf16x2.f32 %0, %1, %2;" : "=r"(d) : "f"(hi), "f"(lo)); return d;
}
__device__ __forceinline__ float bf_lo(uint32_t w) { return __uint_as_float(w << 16); }
__device__ __forceinline__ float bf_hi(uint32_t w) { return __uint_as_float(w & 0xffff0000u); }
__device__ __forceinline__ float ex2(float x) { float y; asm("ex2.approx.ftz.f32 %0, %1;" : "=f"(y) : "f"(x)); return y; }
__device__ __forceinline__ float rcp(float x) { float y; asm("rcp.approx.ftz.f32 %0, %1;" : "=f"(y) : "f"(x)); return y; }
__device__ __forceinline__ uint32_t fu(float x) { return __float_as_uint(x); }
__device__ __forceinline__ float uf(uint32_t x) { return __uint_as_float(x); }
__device__ __forceinline__ void mma16816(float* d, const uint32_t* a, uint32_t b0, uint32_t b1) {
    asm volatile("mma.sync.aligned.m16n8k16.row.col.f32.bf16.bf16.f32 {%0,%1,%2,%3}, {%4,%5,%6,%7}, {%8,%9}, {%0,%1,%2,%3};"
                 : "+f"(d[0]), "+f"(d[1]), "+f"(d[2]), "+f"(d[3]) : "r"(a[0]), "r"(a[1]), "r"(a[2]), "r"(a[3]), "r"(b0), "r"(b1));
}
__device__ __forceinline__ void mma1688(float* d, uint32_t a0, uint32_t a1, uint32_t b0) {
    asm volatile("mma.sync.aligned.m16n8k8.row.col.f32.bf16.bf16.f32 {%0,%1,%2,%3}, {%4,%5}, {%6}, {%0,%1,%2,%3};"
                 : "+f"(d[0]), "+f"(d[1]), "+f"(d[2]), "+f"(d[3]) : "r"(a0), "r"(a1), "r"(b0));
}
template <int N> __device__ __forceinline__ void reg_inc() { asm volatile("setmaxnreg.inc.sync.aligned.u32 %0;" :: "n"(N)); }
template <int N> __device__ __forceinline__ void reg_dec() { asm volatile("setmaxnreg.dec.sync.aligned.u32 %0;" :: "n"(N)); }

__device__ __forceinline__ uint64_t mkdesc(uint32_t addr, uint32_t lbo, uint32_t sbo, uint32_t swz) {
    return (uint64_t)((addr + SM_ORG) >> 4) | ((uint64_t)(lbo >> 4) << 16) | ((uint64_t)(sbo >> 4) << 32) | ((uint64_t)swz << 62);
}
__device__ __forceinline__ void wg_fence() { asm volatile("wgmma.fence.sync.aligned;" ::: "memory"); }
__device__ __forceinline__ void wg_commit() { asm volatile("wgmma.commit_group.sync.aligned;" ::: "memory"); }
template <int N> __device__ __forceinline__ void wg_wait() { asm volatile("wgmma.wait_group.sync.aligned %0;" :: "n"(N) : "memory"); }
template <int M> __device__ __forceinline__ void acc_ready(float* d) {
#pragma unroll
    for (int j = 0; j < M; j++) asm volatile("" : "+f"(d[j]) :: "memory");
}
template <int N, int M> __device__ __forceinline__ void wg_wait_acc(float* d) { wg_wait<N>(); acc_ready<M>(d); }

#define F8(c, d, o) c(d[o]), c(d[o + 1]), c(d[o + 2]), c(d[o + 3]), c(d[o + 4]), c(d[o + 5]), c(d[o + 6]), c(d[o + 7])
#define R8L "%0,%1,%2,%3,%4,%5,%6,%7"
#define R16L R8L ",%8,%9,%10,%11,%12,%13,%14,%15"
#define R32L R16L ",%16,%17,%18,%19,%20,%21,%22,%23,%24,%25,%26,%27,%28,%29,%30,%31"
#define R40L R32L ",%32,%33,%34,%35,%36,%37,%38,%39"
#define WG_BOTH(TXT_PRE, TXT_POST, OUTS, ...)                                                   \
    if (acc) asm volatile(TXT_PRE "1" TXT_POST : OUTS("+f") : __VA_ARGS__);                     \
    else asm volatile(TXT_PRE "0" TXT_POST : OUTS("=f") : __VA_ARGS__)
#define O8(c) F8(c, d, 0)
#define O16(c) F8(c, d, 0), F8(c, d, 8)
#define O32(c) O16(c), F8(c, d, 16), F8(c, d, 24)
#define O40(c) O32(c), F8(c, d, 32)
#define WGM(n) "wgmma.mma_async.sync.aligned.m64n" #n "k16.f32.bf16.bf16 "
__device__ __forceinline__ void wg_rs16(float* d, const uint32_t* a, uint64_t db, bool acc) {
    WG_BOTH(WGM(16) "{" R8L "}, {%8,%9,%10,%11}, %12, ", ", 1, 1, 1;", O8, "r"(a[0]), "r"(a[1]), "r"(a[2]), "r"(a[3]), "l"(db));
}
__device__ __forceinline__ void wg_ss16(float* d, uint64_t da, uint64_t db, bool acc) {
    WG_BOTH(WGM(16) "{" R8L "}, %8, %9, ", ", 1, 1, 1, 1;", O8, "l"(da), "l"(db));
}
__device__ __forceinline__ void wg_rs8(float* d, const uint32_t* a, uint64_t db, bool acc) {
#define O4(c) c(d[0]), c(d[1]), c(d[2]), c(d[3])
    WG_BOTH(WGM(8) "{%0,%1,%2,%3}, {%4,%5,%6,%7}, %8, ", ", 1, 1, 0;", O4, "r"(a[0]), "r"(a[1]), "r"(a[2]), "r"(a[3]), "l"(db));
}
template <int TB = 0> __device__ __forceinline__ void wg_rs32(float* d, const uint32_t* a, uint64_t db, bool acc) {
    WG_BOTH(WGM(32) "{" R16L "}, {%16,%17,%18,%19}, %20, ", ", 1, 1, %21;", O16, "r"(a[0]), "r"(a[1]), "r"(a[2]), "r"(a[3]), "l"(db), "n"(TB));
}
template <int TB = 0> __device__ __forceinline__ void wg_ss32(float* d, uint64_t da, uint64_t db, bool acc) {
    WG_BOTH(WGM(32) "{" R16L "}, %16, %17, ", ", 1, 1, 1, %18;", O16, "l"(da), "l"(db), "n"(TB));
}
template <int TB> __device__ __forceinline__ void wg_rs64(float* d, const uint32_t* a, uint64_t db, bool acc) {
    WG_BOTH(WGM(64) "{" R32L "}, {%32,%33,%34,%35}, %36, ", ", 1, 1, %37;", O32, "r"(a[0]), "r"(a[1]), "r"(a[2]), "r"(a[3]), "l"(db), "n"(TB));
}
template <int TB> __device__ __forceinline__ void wg_ss64(float* d, uint64_t da, uint64_t db, bool acc) {
    WG_BOTH(WGM(64) "{" R32L "}, %32, %33, ", ", 1, 1, 1, %34;", O32, "l"(da), "l"(db), "n"(TB));
}
__device__ __forceinline__ void wg_ss80(float* d, uint64_t da, uint64_t db, bool acc) {
    WG_BOTH(WGM(80) "{" R40L "}, %40, %41, ", ", 1, 1, 1, 1;", O40, "l"(da), "l"(db));
}

constexpr float SM_SCALE = 0.08838834764831845f;
constexpr float LOG2E = 1.4426950408889634f;

#define WO_DELAY 1000
#define D_DELAY 7000
#define F1_DELAY 7000
#define W2_DELAY 16500
#define F1_DEPTH 30
#define PF_DELAY 6000
#define PF_PACE 400
__device__ __forceinline__ void hold_back(uint32_t ns) {
    const uint32_t t0 = timer_lo();
    while (timer_lo() - t0 < ns) __nanosleep(50);
}

__device__ __forceinline__ uint32_t* flag_ptr(int stage, int b) { return &g_flag[stage][b][0]; }
__device__ __forceinline__ uint32_t this_launch() { return ld_rlx(&g_epoch[fresh_bid()][0]) + 1; }
__device__ __forceinline__ bool flag_up(int stage, int b, uint32_t target) { return (int)(ld_rlx(flag_ptr(stage, b)) - target) >= 0; }
__device__ __forceinline__ void flag_wait(int stage, int b, uint32_t target) {
    [[maybe_unused]] int n = 0;
    while (!flag_up(stage, b, target)) {
        __nanosleep(20);
        SPIN_CHECK(n, 10 + stage);
    }
    fence_acq_gpu();
    fence_async_glb();
}
__device__ __forceinline__ void publish(int stage, int b) {
    fence_async_glb();
    fence_rel_gpu();
    red_add_u32(flag_ptr(stage, b), 1);
}
__device__ __forceinline__ uint32_t unit_frag_addr(int tid) {
    const int lane = tid & 31, w = (tid >> 5) & 3, i = lane & 7, j = lane >> 3;
    return ((j >> 1) * 8 + i) * 128 + ((((w << 1) + (j & 1)) ^ i) << 4);
}

#define V_BURST1 3
#define V_BURST2 1
#define V_CUT 2
#define V_PRE 9
#define SX_BF16 0
#define V_REV 1
#define K_GATE 1
#define WO_R8 1
#define OX_V4 0
#define V_LEAD 9
static_assert((V_BURST1 + V_BURST2 >= 2 || V_PRE == 7) && V_BURST1 <= 3 && V_LEAD > V_BURST1 + V_BURST2, "q and k rely on v for the arrival of the blocks");
#define K_LEAD 0
#define Q_LEAD 36
#define V_FIRST 8
#define SX_GATE 1
static_assert(SX_GATE, "EB_QF also stands for the K tile");
#define V_EARLY 1
__host__ __device__ constexpr int x_order(int mat, int j) {
    return mat == 2 ? j : j < 3 ? j + 5 : j < 5 ? j : j == 5 ? 2 : j == 6 ? 8 : 8 - j;
}
#define SS0Q 0
#define SS0K 0
#define SS0V 22
#define SSLQ 36
#define SSLK 36
#define SSLV 14
__host__ __device__ constexpr uint64_t ss_mask(int mat) {
    const int ns = 36 - (mat == 0 ? NRQ : mat == 1 ? NRK : NRV);
    const int j0 = mat == 0 ? SS0Q : mat == 1 ? SS0K : SS0V, len = mat == 0 ? SSLQ : mat == 1 ? SSLK : SSLV;
    uint64_t m = 0;
    for (int j = j0; j < j0 + len; j++)
        if ((j - j0) * ns / len != (j - j0 + 1) * ns / len) m |= 1ull << (x_order(mat, j >> 2) * 4 + (j & 3));
    return m;
}
__device__ __forceinline__ int popc_below(uint64_t m, int k) { return __popcll(m & ((1ull << k) - 1)); }
__host__ __device__ constexpr int x_slot(int f) {
    return f < 3 ? E_R0 + f * 8192 : f == 3 ? E_QT : f == 4 ? E_KT : f < 7 ? E_MEM + (f - 5) * 8192 : f == 8 ? E_R2 : f == 10 ? E_R1 : E_R0;
}
__host__ __device__ constexpr int x_full(int f) { return f < 3 ? 0 : f < 9 ? (f - 1) / 2 : 14 - f; }
__host__ __device__ constexpr bool x_first(int f) { return f == 0 || x_full(f) != x_full(f - 1); }
__host__ __device__ constexpr int x_empty(int blk) { return blk == 6 ? 0 : blk == 7 ? 1 : blk == 4 ? 2 : -1; }
__host__ __device__ constexpr int ar_tile(int j) { return j == 0 ? 8 : ((j - 1) & 1) * 4 + ((j - 1) >> 1); }
__host__ __device__ constexpr int sx_off(int u) { return u == 0 ? 0 : u == 1 ? 1536 : u == 2 ? 2560 : u == 3 ? 3072 : 5120; }

template <int MAT, int NR, int K0, int K1>
__device__ __forceinline__ void proj_mem(float* d, const uint32_t (&w)[NR][4]) {
    constexpr uint64_t M = ss_mask(MAT);
    const uint64_t db = mkdesc(E_MEM, 128, 9216, 0);
    const uint64_t da = mkdesc((MAT == 0 ? E_WQ : MAT == 1 ? E_WK : E_WV), 1024, 1024, 1);
#pragma unroll
    for (int j = K0; j < K1; j++) {
        const int ks = MAT != 2 ? ar_tile(j >> 2) * 4 + (j & 3) : V_REV ? 35 - j : j, s = popc_below(M, ks);
        if ((M >> ks) & 1) wg_ss16(d, da + s * 128, db + ks * 16, j > 0);
        else wg_rs16(d, w[ks - s], db + ks * 16, j > 0);
    }
}
__device__ __forceinline__ uint32_t tl_lane(int tid, int group_bytes) {
    return ((tid >> 4) & 1) * group_bytes + (((tid >> 5) & 3) * 16 + (tid & 15)) * 16;
}
struct ArWords {
    uint32_t w[5];
    __device__ __forceinline__ ArWords(const float* y) {
        w[0] = pack2(y[0], y[1]); w[1] = pack2(y[2], y[3]); w[2] = pack2(y[4], y[5]); w[3] = pack2(y[6], 1.f); w[4] = pack2(y[7], 1.f);
    }
    __device__ __forceinline__ void force(uint32_t zero) {
        asm volatile("{.reg .pred p; setp.ne.u32 p, %0, 0; @p st.shared.v4.b32 [%5], {%1,%2,%3,%4};}" :: "r"(zero), "r"(w[0]), "r"(w[1]), "r"(w[2]), "r"(w[3]), "r"(w[4]) : "memory");
    }
    __device__ __forceinline__ void red(uint8_t* p, uint8_t* q) {
        asm volatile("red.relaxed.gpu.global.add.noftz.v4.bf16x2 [%0], {%1,%2,%3,%4};" :: "l"(p), "r"(w[0]), "r"(w[1]), "r"(w[2]), "r"(w[3]) : "memory");
        asm volatile("red.relaxed.gpu.global.add.noftz.bf16x2 [%0], %1;" :: "l"(q), "r"(w[4]) : "memory");
    }
};
__device__ __forceinline__ uint32_t ar_main(int tid) { return ((tid & 127) >> 3) * AR_STR + (tid & 7) * 16; }
__device__ __forceinline__ uint32_t ar_side(int tid) { return ((tid & 127) >> 5) * (4 * AR_STR) + AR_STR / 2 + (tid & 31) * 4; }

#define AR_VA 0
#define AR_VA1 1
#define AR_SPLIT 5
template <bool B> struct Bool { static constexpr bool value = B; };
template <int J0, int J1>
__device__ __forceinline__ int ar_fetch(const Params& P, int i, int tid, uint32_t gate, uint32_t done) {
    const uint8_t* pm = g_ar + ((i & 3) * AR_SLOT + ar_main(tid));
    const uint8_t* ps = g_ar + ((i & 3) * AR_SLOT + ar_side(tid));
    const uint32_t a = sb + E_MEM + tl_lane(tid, 9216);
    asm volatile("{.reg .pred p; setp.ne.u32 p, %0, 0; @p st.shared.v2.b64 [%3], {%1,%2};}" :: "r"(P.zero), "l"(pm), "l"(ps), "r"(a) : "memory");
    if (J0 == 0) mbar_wait(gate, (i & 1) ^ 1);
    int n = -1;
    bool bad = i >= 0;
    while (bad) {
        uint4 av[J1 - J0];
        uint32_t as[J1 - J0];
#pragma unroll
        for (int j = J0; j < J1; j++) { av[j - J0] = ld_rlx128(pm + ar_tile(j) * (16 * AR_STR)); as[j - J0] = ld_rlx(ps + ar_tile(j) * (16 * AR_STR)); }
        bad = false;
#pragma unroll
        for (int j = J0; j < J1; j++) {
            bad |= __byte_perm(av[j - J0].w, as[j - J0], 0x7632) != (ar_tile(j) == 8 ? 0x42804280u : 0x42004200u);
            stsm4(a + ar_tile(j) * 1024, av[j - J0].x, av[j - J0].y, av[j - J0].z, __byte_perm(av[j - J0].w, as[j - J0], 0x5410));
        }
        bad = __any_sync(~0u, bad);
        SPIN_CHECK(n, 2);
        PROF_INC(n, 1);
    }
    if (i < 0 || i + 1 == LAG) {
        const uint16_t* m = (const uint16_t*)P.mem0 + (tid & 3) * (2 * DM) + (tid >> 5) * 16 + ((tid & 31) >> 2);
        const uint32_t a2 = sb + E_MEM + (tid >> 5) * 256 + (tid & 31) * 4;
        uint32_t v[18];
#pragma unroll
        for (int T = 2 * J0; T < 2 * J1; T++) v[T] = (uint32_t)__ldg(m + ar_tile(T >> 1) * 64 + (T & 1) * 8) | ((uint32_t)__ldg(m + ar_tile(T >> 1) * 64 + (T & 1) * 8 + DM) << 16);
        __syncwarp();
#pragma unroll
        for (int T = 2 * J0; T < 2 * J1; T++) {
            sts32(a2 + 9216 + ar_tile(T >> 1) * 1024 + (T & 1) * 128, v[T]);
            if (i < 0) sts32(a2 + ar_tile(T >> 1) * 1024 + (T & 1) * 128, v[T]);
        }
    }
    if (J0) fence_async_smem();
    mbar_arrive_warp(done);
    return n;
}

__device__ __forceinline__ void attn_mem(float* d, uint32_t par, int i, int tid) {
    const int lane = tid & 31, warp = tid >> 5, c = warp >> 1, hf = warp & 1;
    const int rank = cta_rank();
    const uint32_t peer = mapa(sb, rank ^ 1);
    const uint32_t l4 = (lane >> 4) * 1024 + (lane & 15) * 16;
    uint32_t kb[4][4];
    {
        const uint32_t aK = sb + E_KT + (c * 6 + hf * 2) * 1024 + l4;
#pragma unroll
        for (int ks = 0; ks < 4; ks++) ldsm4t(kb[ks], aK + ks * 256);
    }
    const uint32_t aQs = pin(sb + E_QM + tl_lane(tid, 1024));
    const uint32_t aQ = pin(sb + E_QM + c * 1024 + (((lane >> 3) & 1) * 16 + (lane >> 4) * 8 + (lane & 7)) * 16);
    const uint32_t aM = pin(sb + E_KT + (4 + c) * 1024 + lane * 16);
    const uint32_t oS = pin(tid * 16);
    wg_wait_acc<0, 8>(d);
    stsm4(aQs, pack2(d[0], d[1]), pack2(d[2], d[3]), pack2(d[4], d[5]), pack2(d[6], d[7]));
    nbar_sync(NB_QK, 256);
    TS(0, i, 1);
    float s[6];
    {
        uint32_t q[2][4], km[2][4];
        ldsm4t(q[0], aQ); ldsm4t(km[0], aM); ldsm4t(q[1], aQ + 512); ldsm4t(km[1], aM + 512);
        float a[6][4];
#pragma unroll
        for (int m = 0; m < 6; m++) a[m][0] = a[m][1] = a[m][2] = a[m][3] = 0.f;
#pragma unroll
        for (int j = 0; j < 2; j++) {
#pragma unroll
            for (int o = 0; o < 2; o++) {
                mma16816(a[o * 3], q[j], kb[2 * j + o][0], kb[2 * j + o][1]);
                mma16816(a[o * 3 + 1], q[j], kb[2 * j + o][2], kb[2 * j + o][3]);
            }
            mma16816(a[2], q[j], km[j][0], km[j][1]);
            mma16816(a[5], q[j], km[j][2], km[j][3]);
        }
        nbar_arrive(NB_S, 256);
        if (SX_GATE) nbar_arrive(NB_S2, 256);
#pragma unroll
        for (int m = 0; m < 3; m++) { s[2 * m] = a[m][0] + a[3 + m][2]; s[2 * m + 1] = a[m][1] + a[3 + m][3]; }
    }
    st_async128(peer + E_SR + oS, fu(s[0]), fu(s[1]), fu(s[2]), fu(s[3]), peer + SM_BAR + EB_SM * 8);
    const uint32_t oM = E_SR + 2048 + c * 256 + lane * 8;
    asm volatile("st.async.shared::cluster.mbarrier::complete_tx::bytes.b32 [%0], %1, [%2];"
                 :: "r"(peer + oM + hf * 4), "r"(fu(hf ? s[5] : s[4])), "r"(peer + SM_BAR + EB_SM * 8) : "memory");
    sts128(sb + E_SL + oS, fu(s[0]), fu(s[1]), fu(s[2]), fu(s[3]));
    mbar_arrive_warp(bars + EB_KF * 8);
    TS(0, i, 2);
#pragma unroll
    for (int j = 0; j < 4; j++) ldsm4(kb[j], sb + E_VT + c * 6144 + l4 + hf * 512 + ((j >> 1) ^ hf) * 2048 + (j & 1) * 256);
    nbar_sync(NB_G, 128);
    const uint32_t aR = sb + E_SR + oS, aR1 = sb + E_SR + (oS ^ 512), aRm = sb + oM;
    const uint4 l1 = lds128(aR1 + (E_SL - E_SR));
    mbar_wait_cl(bars + EB_SM * 8, par);
    TS(0, i, 3);
    float p[10];
    {
        const uint4 r0 = lds128(aR), r1 = lds128(aR1);
        const uint2 rm = lds64(aRm);
        p[0] = s[0] + uf(r0.x); p[1] = s[1] + uf(r0.y); p[2] = s[2] + uf(r0.z); p[3] = s[3] + uf(r0.w);
        p[4] = uf(l1.x) + uf(r1.x); p[5] = uf(l1.y) + uf(r1.y); p[6] = uf(l1.z) + uf(r1.z); p[7] = uf(l1.w) + uf(r1.w);
        p[8] = s[4] + uf(rm.x); p[9] = s[5] + uf(rm.y);
    }
    float mx = fmaxf(fmaxf(fmaxf(p[0], p[1]), fmaxf(p[2], p[3])), fmaxf(fmaxf(fmaxf(p[4], p[5]), fmaxf(p[6], p[7])), fmaxf(p[8], p[9])));
    mx = fmaxf(mx, __shfl_xor_sync(~0u, mx, 1));
    mx = fmaxf(mx, __shfl_xor_sync(~0u, mx, 2));
    const float mo = mx * (SM_SCALE * LOG2E);
    mbar_wait(bars + EB_KF * 8, par);
    uint32_t vm[4], pb[5];
    ldsm4(vm, aM + (E_VT - E_KT) + hf * 512);
    float o[3][4];
    const uint32_t ones[4] = {0x3f803f80u, 0x3f803f80u, 0x3f803f80u, 0x3f803f80u};
#pragma unroll
    for (int T = 0; T < 3; T++) o[T][0] = o[T][1] = o[T][2] = o[T][3] = 0.f;
#pragma unroll
    for (int j = 0; j < 2; j++) {
#pragma unroll
        for (int m = 2 * j; m < 2 * j + 2; m++) pb[m] = pack2(ex2(fmaf(p[2 * m], SM_SCALE * LOG2E, -mo)), ex2(fmaf(p[2 * m + 1], SM_SCALE * LOG2E, -mo)));
        mma16816(o[2], ones, pb[2 * j], pb[2 * j + 1]);
#pragma unroll
        for (int T = 0; T < 2; T++) mma16816(o[T], kb[2 * j + T], pb[2 * j], pb[2 * j + 1]);
    }
    pb[4] = pack2(ex2(fmaf(p[8], SM_SCALE * LOG2E, -mo)), ex2(fmaf(p[9], SM_SCALE * LOG2E, -mo)));
    mma1688(o[2], ones[0], ones[1], pb[4]);
#pragma unroll
    for (int T = 0; T < 2; T++) mma1688(o[T], vm[2 * T], vm[2 * T + 1], pb[4]);
    nbar_arrive(NB_PV, 256);
    mbar_arrive_warp(bars + EB_CONS * 8);
    const float i0 = rcp(o[2][0]), i1 = rcp(o[2][1]);
    uint32_t ow[4];
#pragma unroll
    for (int j = 0; j < 4; j++) ow[j] = pack2(o[j >> 1][2 * (j & 1)] * i0, o[j >> 1][2 * (j & 1) + 1] * i1);
    const uint32_t oO = E_OM + c * 2048 + hf * 512;
    stsm4(sb + oO + lane * 16, ow[0], ow[1], ow[2], ow[3]);
    if (OX_V4) {
        __syncwarp();
        const uint4 r = lds128(sb + oO + lane * 16);
        nbar_sync(NB_G, 128);
        st_async128(peer + oO + 1024 + lane * 16, r.x, r.y, r.z, r.w, peer + SM_BAR + EB_OX * 8);
    } else {
#pragma unroll
        for (int j = 0; j < 4; j++)
            asm volatile("st.async.shared::cluster.mbarrier::complete_tx::bytes.b32 [%0], %1, [%2];"
                         :: "r"(peer + oO + 1024 + j * 128 + lane * 4), "r"(ow[j]), "r"(peer + SM_BAR + EB_OX * 8) : "memory");
    }
}

__device__ __forceinline__ void attn_x_scores(float (&p)[2][10], uint32_t par, int i, int tid) {
    {
        float s[40];
        const uint64_t da = mkdesc(E_QT, 128, 1024, 0), db = mkdesc(E_KT, 128, 1024, 0);
        wg_fence();
#pragma unroll
        for (int ks = 0; ks < 4; ks++) wg_ss80(s, da + ks * 16, db + ks * 16, ks > 0);
        wg_commit();
        const int dq = (tid >> 2) - 2 * (tid & 3);
        float mask[8];
#pragma unroll
        for (int j = 0; j < 8; j++) mask[j] = (j >> 1) * 8 + (j & 1) > dq ? -1e9f * LOG2E : 0.f;
        mbar_wait_cl(bars + EB_PRDY * 8, par);
        wg_wait_acc<0, 40>(s);
#pragma unroll
        for (int u = 0; u < 5; u++) {
            const int v = u < 4 ? 6 + u : 5;
            constexpr float C = SM_SCALE * LOG2E;
            const float m0 = u < 4 ? mask[2 * u & 7] : 0.f, m1 = u < 4 ? mask[(2 * u + 1) & 7] : 0.f;
            p[0][2 * u] = fmaf(s[4 * u], C, m0); p[0][2 * u + 1] = fmaf(s[4 * u + 1], C, m1); p[1][2 * u] = fmaf(s[4 * v + 2], C, m0); p[1][2 * u + 1] = fmaf(s[4 * v + 3], C, m1);
        }
    }
    mbar_arrive_warp(bars + EB_QF * 8);
    const int w = tid >> 5;
    if (!SX_BF16) {
        const uint32_t peer = mapa(sb, cta_rank() ^ 1);
#pragma unroll
        for (int u = 0; u < 5; u++)
            if (u == 0 || u <= w || u == 4) st_async128(peer + E_SX + sx_off(u) + tid * 16, fu(p[0][2 * u]), fu(p[0][2 * u + 1]), fu(p[1][2 * u]), fu(p[1][2 * u + 1]), peer + SM_BAR + EB_SX * 8);
    } else {
        const uint32_t peer = mapa(sb, cta_rank() ^ 1), a = peer + E_SX + tid * 16, mb = peer + SM_BAR + EB_SX * 8;
        st_async128(a, pack2(p[0][0], p[0][1]), pack2(p[1][0], p[1][1]), pack2(p[0][8], p[0][9]), pack2(p[1][8], p[1][9]), mb);
        if (w >= 1) st_async128(a + 2048, pack2(p[0][2], p[0][3]), pack2(p[1][2], p[1][3]), pack2(p[0][4], p[0][5]), pack2(p[1][4], p[1][5]), mb);
        if (w >= 3) st_async64(a + 4096, pack2(p[0][6], p[0][7]), pack2(p[1][6], p[1][7]), mb);
    }
    TS(128, i, 10);
}
__device__ __forceinline__ void attn_x_finish(float (&p)[2][10], uint32_t par, int i, int& tid, uint32_t zero) {
    const int w = tid >> 5;
    mbar_wait_cl(bars + EB_SX * 8, par);
    TS(128, i, 11);
    if (SX_BF16) {
        const uint32_t a = sb + E_SX + tid * 16;
        const uint4 r0 = lds128(a), r1 = lds128(a + (w >= 1 ? 2048 : 0));
        const uint2 r2 = lds64(a + (w >= 3 ? 4096 : 0));
        const uint32_t r[10] = {r0.x, r0.y, r1.x, r1.y, r1.z, r1.w, r2.x, r2.y, r0.z, r0.w};
#pragma unroll
        for (int j = 0; j < 10; j++) { p[j & 1][j & ~1] += bf_lo(r[j]); p[j & 1][j | 1] += bf_hi(r[j]); }
    } else
#pragma unroll
    for (int u = 0; u < 5; u++) {
        const uint4 r = lds128(pin(sb + tid * 16 + (u == 0 || u <= w ? sx_off(u) : sx_off(4))) + E_SX);
        p[0][2 * u] += uf(r.x); p[0][2 * u + 1] += uf(r.y); p[1][2 * u] += uf(r.z); p[1][2 * u + 1] += uf(r.w);
    }
    nbar_sync(NB_W, 128);
    uint32_t pa[5][4];
    float mx[2], inv[2];
#pragma unroll
    for (int h = 0; h < 2; h++) {
        const float* q = p[h];
        mx[h] = fmaxf(fmaxf(fmaxf(q[0], q[1]), fmaxf(q[2], q[3])), fmaxf(fmaxf(fmaxf(q[4], q[5]), fmaxf(q[6], q[7])), fmaxf(q[8], q[9])));
    }
#pragma unroll
    for (int o = 1; o < 4; o <<= 1) { mx[0] = fmaxf(mx[0], __shfl_xor_sync(~0u, mx[0], o)); mx[1] = fmaxf(mx[1], __shfl_xor_sync(~0u, mx[1], o)); }
#pragma unroll
    for (int h = 0; h < 2; h++) {
        float* q = p[h];
#pragma unroll
        for (int j = 0; j < 10; j++) q[j] = ex2(q[j] - mx[h]);
#pragma unroll
        for (int u = 0; u < 4; u++) {
            pa[h * 3 + (u >> 1)][(u & 1) * 2 + h] = pack2(q[2 * u], q[2 * u + 1]);
            pa[h * 3 + (u >> 1)][(u & 1) * 2 + (h ^ 1)] = zero << (h * 5 + u + 1);
        }
        pa[2][h * 3] = pack2(q[8], q[9]);
        pa[2][1 + h] = zero << (h * 5 + 5);
    }
    mbar_wait(bars + EB_CONS * 8, par);
    fence_async_smem();
    tid = pin(tid << zero);
    const uint32_t aO = pin(sb + ((tid >> 3) & 1) * 4096 + (((tid >> 4) & 1) * 8 + (tid & 7)) * 64 + (((tid >> 5) ^ ((tid & 7) >> 1)) << 4)) + E_R1;
    TS(128, i, 12);
#pragma unroll
    for (int nh = 0; nh < 2; nh++) {
        float o[16], sum[4];
        const uint64_t db = mkdesc(E_VT + nh * 512, 1024, 128, 0);
        wg_fence();
#pragma unroll
        for (int kk = 0; kk < 5; kk++) {
            if (nh == 0) wg_rs8(sum, pa[kk], mkdesc(SM_ONES, 0, 0, 0), kk > 0);
            wg_rs32(o, pa[kk], db + kk * 128, kk > 0);
        }
        wg_commit();
        wg_wait_acc<0, 16>(o);
        if (nh == 0) { acc_ready<4>(sum); inv[0] = rcp(sum[0]); inv[1] = rcp(sum[2]); }
#pragma unroll
        for (int j = 0; j < 2; j++) {
            const float* y = &o[8 * j];
            stsm4t(aO + nh * 2048 + j * 1024, pack2(y[0] * inv[0], y[1] * inv[0]), pack2(y[2] * inv[1], y[3] * inv[1]), pack2(y[4] * inv[0], y[5] * inv[0]), pack2(y[6] * inv[1], y[7] * inv[1]));
        }
    }
    mbar_arrive_warp(bars + EB_OST * 8);
    TS(128, i, 13);
}

template <int MAT>
__device__ __forceinline__ void engine_main(const Params& P) {
    constexpr int NR = MAT == 0 ? NRQ : MAT == 1 ? NRK : NRV;
    constexpr uint64_t M = ss_mask(MAT);
    uint32_t w[NR][4];
    {
        const uint32_t a = sb + E_WO + (MAT == 0 ? 0 : MAT == 1 ? NRQ : NRQ + NRK) * 2048 + unit_frag_addr(fresh_tid());
        mbar_wait(bars + EB_WL * 8, 0);
        if (MAT == 0 && threadIdx.x == 0) TG(79, 2);
#pragma unroll
        for (int u = 0; u < NR; u++) ldsm4t(w[u], a + u * 2048);
    }
    nbar_arrive(NB_T, 448);
    int tid = fresh_tid() - MAT * 128;
#define TID (tid = pin(tid << P.zero))
    if (MAT == 0) { if (V_FIRST == 36) nbar_arrive(NB_S, 256); nbar_arrive(NB_PV, 256); nbar_arrive(NB_WO, 256); }
    auto project = [&](auto one, const int i) {
        constexpr bool ONE = decltype(one)::value;
        const uint32_t par = i & 1;
        {
            float d[ONE ? 16 : 32];
            const uint64_t da = mkdesc((MAT == 0 ? E_WQ : MAT == 1 ? E_WK : E_WV), 1024, 1024, 1);
            constexpr int R1 = V_BURST1, R2 = V_BURST1 + V_BURST2;
#pragma unroll
            for (int n = 0; n < 9; n++) {
                const int blk = x_order(MAT, n), prev = n ? x_order(MAT, n - 1) : -1, f = MAT != 2 && blk < 2 ? 9 + blk : blk;
                if (MAT == 2) {
                    if (!V_CUT && R2 >= 2 && n == (R1 >= 2 ? R1 : R2)) { wg_wait<0>(); mbar_arrive_warp(bars + EB_V0 * 8); }
                    if ((n == 0 && (V_FIRST == 36 || i == 0)) || n == R1 || n == R2) {
#pragma unroll
                        for (int j = n; j < (n < R1 ? R1 : n < R2 ? R2 : V_PRE); j++) if (x_first(j)) mbar_wait(bars + (EB_FULL + x_full(j)) * 8, par);
                    }
                    if (n == 0 && V_FIRST == 36) nbar_sync(NB_S, 256);
                    if (n == R1 && !V_CUT) nbar_sync(NB_PV, 256);
                    if (n == R2) nbar_sync(NB_WO, 256);
                } else {
                    if (n == 0) nbar_sync(MAT ? NB_VL : NB_VL2, 256);
                }
                static_assert(V_PRE == 9 || (V_PRE == 7 && V_LEAD > 7), "see the barriers");
                const bool wt = MAT == 2 ? f == V_PRE : f >= 9;
                if (wt) mbar_wait(bars + (EB_FULL + x_full(f)) * 8, par);
                TX(MAT * 128, 1 + MAT * 9 + n);
                if (wt || n == 0 || (MAT == 2 && (n == R1 || n == R2))) wg_fence();
                if (n == 0) TS(MAT * 128, i, 20 + MAT);
                const uint64_t db = mkdesc(x_slot(f), 16, 1024, 1);
#pragma unroll
                for (int j = 0; j < 4; j++) {
                    const int ks = blk * 4 + j, s = popc_below(M, ks);
                    if (MAT == 2 && V_CUT && ks == R1 * 4 - V_CUT) { wg_commit(); wg_wait<0>(); mbar_arrive_warp(bars + EB_V0 * 8); nbar_sync(NB_PV, 256); wg_fence(); }
                    if constexpr (ONE) {
                        if ((M >> ks) & 1) wg_ss32(d, da + s * 128, db + j * 2, n + j > 0);
                        else wg_rs32(d, w[ks - s], db + j * 2, n + j > 0);
                    } else {
                        if ((M >> ks) & 1) wg_ss64<0>(d, da + s * 128, db + j * 2, n + j > 0);
                        else wg_rs64<0>(d, w[ks - s], db + j * 2, n + j > 0);
                    }
                }
                wg_commit();
                if (MAT == 2 && n + 1 == V_LEAD) { nbar_arrive(NB_VL, 256); if (!K_LEAD) nbar_arrive(NB_VL2, 256); }
                if (MAT == 1 && n + 1 == K_LEAD) nbar_arrive(NB_VL2, 256);
                if (MAT == 2 && R2 < 2 && n == 3) { wg_wait<2>(); mbar_arrive_warp(bars + EB_V0 * 8); }
                if (MAT != 2 && x_empty(prev) >= 0) { wg_wait<1>(); mbar_arrive_warp(bars + (EB_EMPTY + x_empty(prev)) * 8); }
            }
            const uint32_t a = sb + (MAT == 0 ? E_QT : MAT == 1 ? E_KT : E_VT) + tl_lane(TID, MAT == 0 ? 2048 : 1024) + (ONE && i >= NSEG ? (MAT == 0 ? 1024 : 6144) : 0);
            if (MAT != 2) {
                mbar_wait(bars + (EB_EMPTY + 2) * 8, par);
                if (!ONE) mbar_wait(bars + EB_MEMA * 8, par);
            } else {
                mbar_wait(bars + EB_OST * 8, par ^ 1);
            }
            wg_wait_acc<0, ONE ? 16 : 32>(d);
            TS(MAT * 128, i, 23 + MAT);
#pragma unroll
            for (int j = 0; j < (ONE ? 4 : 8); j += 2) {
                const int grp = MAT == 0 ? 2 * (j & 3) + (j >> 2) : j < 4 ? j : j + 2;
                stsm4(a + grp * 1024, pack2(d[4 * j], d[4 * j + 1]), pack2(d[4 * j + 2], d[4 * j + 3]), pack2(d[4 * j + 4], d[4 * j + 5]), pack2(d[4 * j + 6], d[4 * j + 7]));
            }
        }
        if (MAT != 2) {
            if (ONE) mbar_arrive_warp(bars + EB_STEP * 8);
            if (ONE) mbar_wait(bars + EB_MEMA * 8, par);
        } else {
            __syncwarp();
            if ((TID & 31) < 3) mbar_arrive(bars + (EB_EMPTY + (tid & 31)) * 8);
        }
    };
    auto step = [&](const int i) {
        const uint32_t par = i & 1;
        if (MAT == 2) {
            if (Q_LEAD) nbar_sync(NB_OM, K_GATE ? 384 : 256);
            else mbar_wait(bars + EB_MEM * 8, par);
        }
        float d[8];
        TS(MAT * 128, i, MAT == 2 ? 26 : 14 + MAT);
        wg_fence();
        constexpr int MID = MAT == 2 ? V_FIRST : Q_LEAD;
        if (MAT != 2) {
            static_assert(Q_LEAD >= AR_SPLIT * 4, "v relies on q for the rest");
            proj_mem<MAT, NR, 0, AR_SPLIT * 4>(d, w);
            mbar_wait(bars + EB_MEM * 8, par);
            wg_fence();
        }
        proj_mem<MAT, NR, MAT != 2 ? AR_SPLIT * 4 : 0, MID>(d, w);
        if ((MAT == 0 || (MAT == 1 && K_GATE)) && Q_LEAD) nbar_arrive(NB_OM, K_GATE ? 384 : 256);
        if (MAT == 2 && V_FIRST < 36) {
            if (V_BURST1) mbar_wait(bars + EB_FULL * 8, i == NSTEP - 1 ? par : par ^ 1);
            nbar_sync(NB_S, 256);
            wg_fence();
        }
        proj_mem<MAT, NR, MID, 36>(d, w);
        wg_commit();
        if (MAT == 0) {
            mbar_wait(bars + EB_WO * 8, 0);
            tid *= mbar_wait(bars + EB_STEP * 8, par);
            attn_mem(d, par, i, tid);
        } else if (MAT == 1) {
            tid *= mbar_wait(bars + EB_STEP * 8, par);
            const uint32_t a = pin(sb + E_KT + 4096 + tl_lane(tid, 1024));
            wg_wait_acc<0, 8>(d);
            stsm4(a, pack2(d[0], d[1]), pack2(d[2], d[3]), pack2(d[4], d[5]), pack2(d[6], d[7]));
            nbar_arrive(NB_QK, 256);
            TS(128, i, 18);
            fence_async_smem();
            nbar_sync(SX_GATE ? NB_S2 : NB_W, SX_GATE ? 256 : 128);
            float p[2][10];
            attn_x_scores(p, par, i, TID);
            attn_x_finish(p, par, i, TID, pin(P.zero));
        } else {
            const uint32_t a = pin(sb + E_VT + 4096 + tl_lane(TID, 1024));
            wg_wait_acc<0, 8>(d);
            stsm4(a, pack2(d[0], d[1]), pack2(d[2], d[3]), pack2(d[4], d[5]), pack2(d[6], d[7]));
            mbar_arrive_warp(bars + EB_KF * 8);
            TS(256, i, 16);
        }
        if (MAT == 0) {
            const int rank = cta_rank();
            uint8_t* const ar = g_ar + (i & 3) * AR_SLOT;
            uint8_t* const pm = ar + pin(ar_main(TID) + rank * (64 * AR_STR));
            uint8_t* const ps = ar + pin(ar_side(tid) + rank * (64 * AR_STR));
            const uint32_t o8 = (128 - rank * 64) * AR_STR;
            const uint64_t db = mkdesc(E_OM, 128, 2048, 0), da = mkdesc(E_WO, 1024, 1024, 1);
            if (!OX_V4) nbar_sync(NB_G, 128);
            fence_async_smem();
            TS(0, i, 6);
            if (i == NSTEP - 1) { mbar_wait_cl(bars + EB_OX * 8, par); return; }
            float y[4][8];
            wg_fence();
#pragma unroll
            for (int ks = 0; ks < 4; ks++) wg_ss16(y[3], da + (32 + ks) * 128, db + ks * 16, ks > 0);
            wg_commit();
#pragma unroll
            for (int j = 0; j < 12; j++) wg_ss16(y[j % 3], da + ((j % 3) * 8 + j / 3) * 128, db + (j / 3) * 16, j >= 3);
            wg_commit();
            wg_wait_acc<1, 8>(y[3]);
            ArWords z(y[3]);
            if (WO_R8) z.red(pm + o8, ps + o8); else z.force(P.zero);
            mbar_wait_cl(bars + EB_OX * 8, par);
            fence_async_smem();
            wg_fence();
#pragma unroll
            for (int T = 0; T < 4; T++) {
#pragma unroll
                for (int ks = T < 3 ? 4 : 0; ks < 8; ks++) wg_ss16(y[T], da + (T * 8 + ks) * 128, db + ks * 16, ks > 0);
                wg_commit();
            }
            if (V_EARLY) nbar_arrive(NB_WO, 256);
            if (!WO_R8) z.red(pm + o8, ps + o8);
            wg_wait_acc<1, 8>(y[0]); acc_ready<8>(y[1]); acc_ready<8>(y[2]);
#pragma unroll
            for (int T = 0; T < 3; T++) ArWords(y[T]).red(pm + T * 16 * AR_STR, ps + T * 16 * AR_STR);
            wg_wait_acc<0, 8>(y[3]);
            ArWords(y[3]).red(pm + 48 * AR_STR, ps + 48 * AR_STR);
            if (!V_EARLY) nbar_arrive(NB_WO, 256);
            TS(0, i, 7);
        }
    };
    auto either = [&](const int i) {
        if (__builtin_expect(USE_ONE == 2 || (USE_ONE && (i < LAG || i >= NSEG)), MAT != 2)) project(Bool<true>(), i);
        else project(Bool<false>(), i);
    };
    if (MAT != 2) {
#pragma unroll 1
        for (int i = 0; i < NSTEP; i++) {
            either(i);
            if (!USE_ONE || (USE_ONE == 1 && i >= LAG && i < NSEG)) mbar_arrive_warp(bars + EB_STEP * 8);
            step(i);
        }
    } else {
#pragma unroll 1
        for (int i = -1; i < NSTEP; i++) {
            if (i >= 0) step(i);
            if (i < NSTEP - 1) {
                either(i + 1);
                const bool one = USE_ONE == 2 || (USE_ONE && (i + 1 < LAG || i + 1 >= NSEG));
                [[maybe_unused]] const int n0 = ar_fetch<0, AR_SPLIT>(P, i, TID, bars + (EB_EMPTY + (one ? AR_VA1 : AR_VA)) * 8, bars + EB_MEM0 * 8);
                [[maybe_unused]] const int n1 = ar_fetch<AR_SPLIT, 9>(P, i, tid, bars + EB_EMPTY * 8, bars + EB_MEM * 8);
            }
        }
    }
    if (MAT == 2) { if (V_FIRST == 36) nbar_sync(NB_S, 256); nbar_sync(NB_PV, 256); }
}

__device__ __forceinline__ void engine_helper(const Params& P) {
    const int lane = threadIdx.x & 31, hw = warp_in_group(), e = blockIdx.x, rank = e & 1;
    if (hw < 3) {
        constexpr uint64_t M0 = ss_mask(0), M1 = ss_mask(1), M2 = ss_mask(2);
        const uint64_t m = hw == 0 ? M0 : hw == 1 ? M1 : M2;
        const uint32_t ws = sb + (hw == 0 ? E_WQ : hw == 1 ? E_WK : E_WV), wr = sb + E_WO + (hw == 0 ? 0 : hw == 1 ? NRQ : NRQ + NRK) * 2048;
        if (lane == 0) mbar_expect(bars + EB_WL * 8, 36 * 2048);
        __syncwarp();
        for (int ks = lane; ks < 36; ks += 32) {
            const int s = __popcll(m & ((1ull << ks) - 1));
            tma_unit(((m >> ks) & 1) ? ws + s * 2048 : wr + (ks - s) * 2048, hw == 0 ? &P.tmWq : hw == 1 ? &P.tmWk : &P.tmWv, ks, e, bars + EB_WL * 8);
        }
    }
    __syncwarp();
    if (hw < 2) nbar_sync(NB_T, 448);
    if (lane == 0) TG(79, 3);
    if (hw == 0) {
        if (lane == 0) {
#pragma unroll 1
            for (int n = 0; n < NSTEP; n++) {
                const uint32_t par = (n & 1) ^ 1;
                mbar_arrive(bars + EB_XR * 8);
                mbar_wait(bars + EB_XR * 8, n & 1);
                TG(n, 30);
                const uint8_t* src = g_x + n * XIMG;
#pragma unroll
                for (int j = 0; j < 6; j++) {
                    const int f = j == 0 ? 0 : j < 4 ? 2 * j + 1 : 14 - j, blk = f < 9 ? f : f - 9, bytes = j == 0 ? 24576 : j < 4 ? 16384 : 8192;
                    if (j == 3 || j == 5) mbar_wait(bars + (j == 3 ? EB_V0 : EB_EMPTY + 1) * 8, par ^ 1);
                    else mbar_wait(bars + (j == 0 ? EB_STEP : j == 1 ? EB_QF : j == 2 ? EB_KF : EB_OFREE) * 8, par);
                    const uint32_t fb = bars + (EB_FULL + j) * 8;
                    mbar_expect(fb, bytes);
                    bulk_g2s(sb + x_slot(f), src + blk * 8192, bytes, fb);
                }
            }
        }
    } else if (hw == 1) {
        if (lane == 0) mbar_expect(bars + EB_WO * 8, 36 * 2048);
        __syncwarp();
        for (int u = lane; u < 36; u += 32)
            tma_unit(sb + E_WO + u * 2048, &P.tmWo, (e >> 1) * 8 + ((u & 7) ^ (rank * 4)), u < 32 ? rank * 4 + (u >> 3) : 8, bars + EB_WO * 8);
        __syncwarp();
        if (lane == 0) {
#pragma unroll 1
            for (int i = 0; i < NSTEP; i++) {
                mbar_wait(bars + EB_STEP * 8, i & 1);
                mbar_arrive_remote(mapa(sb, rank ^ 1) + SM_BAR + EB_PRDY * 8);
                mbar_wait(bars + EB_OST * 8, i & 1);
                fence_async_smem();
                const int q = first_job(i);
                bulk_s2g(g_o + (q & (RING - 1)) * O_BYTES + e * 4096, sb + E_R1 + (i < NSEG ? 0 : 4096), 4096);
                if (i >= LAG && i < NSEG) bulk_s2g(g_o + ((q + 1) & (RING - 1)) * O_BYTES + e * 4096, sb + E_R1 + 4096, 4096);
                asm volatile("cp.async.bulk.commit_group;" ::: "memory");
                asm volatile("cp.async.bulk.wait_group.read 0;" ::: "memory");
                mbar_arrive(bars + EB_OFREE * 8);
                asm volatile("cp.async.bulk.wait_group 0;" ::: "memory");
                publish(F_O, i);
                TG(i, 31);
            }
        }
    } else if (hw == 2) {
        const int idx = e * 23 + lane, line = idx >> 3;
        uint8_t* z = g_ar + (line < 144 ? line * AR_STR : (line - 144) * (4 * AR_STR) + AR_STR / 2) + (idx & 7) * 16;
        if (lane < 23 && idx < 1440) { stg128(z, make_uint4(0, 0, 0, 0)); stg128(z + AR_SLOT, make_uint4(0, 0, 0, 0)); }
        __syncwarp();
        if (lane == 0) publish(F_X0, B_ZERO);
        __syncwarp();
        hold_back(WO_DELAY);
        for (int u = lane; u < 36; u += 32)
            asm volatile("cp.async.bulk.prefetch.tensor.2d.L2.global [%0, {%1,%2}];"
                         :: "l"(&P.tmWo), "r"((u < 32 ? rank * 4 + (u >> 3) : 8) * 64), "r"(((e >> 1) * 8 + (u < 32 ? u & 7 : rank * 4 + (u & 3))) * 16) : "memory");
        __syncwarp();
        if (lane == 0) {
            mbar_arrive(bars + EB_MEM * 8);
            flag_wait(F_X0, B_ZERO, NENG * this_launch());
            mbar_arrive(bars + EB_WO * 8);
            TG(79, 5);
        }
        __syncwarp();
#pragma unroll 1
        for (int i = 0; i < NSTEP; i++) {
            mbar_wait(bars + EB_MEM0 * 8, i & 1);
            fence_async_smem();
            if (lane == 0) mbar_arrive(bars + EB_MEMA * 8);
            if (lane < 3) mbar_expect(bars + (EB_SM + lane) * 8, lane == 0 ? 2560 : lane == 1 ? (SX_BF16 ? 3840 : 7168) : 2048);
            mbar_wait(bars + EB_MEM * 8, i & 1);
            if (lane < 23 && idx < 1440) stg128(z + ((i + 2) & 3) * AR_SLOT, make_uint4(0, 0, 0, 0));
            __syncwarp();
            if (lane == 0) { fence_gpu(); mbar_arrive(bars + EB_MEM * 8); }
            __syncwarp();
        }
    } else {
        for (int j = lane; j < 72; j += 32) asm volatile("prefetch.global.L2 [%0];" :: "l"(P.mem0 + j * 64));
        const uint32_t ep = this_launch(), t0 = timer_lo();
        if (lane == 0) {
#pragma unroll 1
            for (int n = 0; n < NSTEP; n++) {
                bool up;
                do {
                    const bool r0 = flag_up(F_X0, n, 16 * ep);
                    const bool r1 = flag_up(F_X1, max(n - LAG, 0), 16 * ep);
                    up = (r0 || n >= NSEG) && (r1 || n < LAG);
                } while (!up && timer_lo() - t0 < TIME_LIMIT);
                fence_acq_gpu();
                fence_async_glb();
                mbar_arrive(bars + EB_XR * 8);
                while (!mbar_test(bars + EB_XR * 8, n & 1) && timer_lo() - t0 < TIME_LIMIT) __nanosleep(200);
            }
        }
    }
    __syncwarp();
}

__device__ __forceinline__ void f1_fetch(const Params& P, uint32_t dst, int f0, int ks0, int n) {
    const int tid = threadIdx.x & 127, r = tid >> 3, c = (tid & 3) * 2 + ((tid >> 2) & 1);
    const bf16* src = ((c & 1) ? P.w3 : P.w1) + (size_t)(ks0 * 16 + r) * FF + f0 + (c >> 1) * 8;
    dst += r * 128 + ((c ^ (r & 7)) << 4);
#pragma unroll 1
    for (int u = 0; u < n; u++) {
        asm volatile("cp.async.cg.shared.global [%0], [%1], 16;" :: "r"(dst + u * 2048), "l"(src + (size_t)u * 16 * FF) : "memory");
        asm volatile("cp.async.commit_group; cp.async.wait_group %0;" :: "n"(F1_DEPTH) : "memory");
    }
}
#define F1_LEAD 1
template <int a, bool second, int buf>
__device__ __forceinline__ void f1_tile(const uint32_t (&w)[NRF][4], uint32_t ws, int q) {
    constexpr bool RF = (a == 1) == second;
    const uint32_t par = (q >> 1) & 1;
    float d[16];
    const uint64_t da = mkdesc(ws, 1024, 1024, 1), db = mkdesc(F_X + buf * XF_BYTES, 16, 1024, 1);
#pragma unroll
    for (int g = 0; g < 3; g++) {
        if (a == 1 && !second && g == 0 && F1_LEAD) nbar_sync(NB_OM + buf, 256);
        if (g == 0 || (!second && (a == 0 || g >= F1_LEAD))) {
            mbar_wait(bars + (FB_FULL + buf * 3 + g) * 8, par);
            wg_fence();
        }
#pragma unroll
        for (int ks = g * 12; ks < g * 12 + 12; ks++) {
            const int u = RF ? ks : 36 + ks;
            if (u < NRF) wg_rs32(d, w[u < NRF ? u : 0], db + (ks >> 2) * 256 + (ks & 3) * 2, ks > 0);
            else wg_ss32(d, da + (u - NRF) * 128, db + (ks >> 2) * 256 + (ks & 3) * 2, ks > 0);
        }
        if (a == 0 && !second && g + 1 == F1_LEAD) nbar_arrive(NB_OM + buf, 256);
    }
    wg_commit();
    if (!second) mbar_wait(bars + FB_RACK * 8, (q & 1) ^ 1);
    const int tid = fresh_tid(), g = (tid & 31) >> 2;
    uint8_t* dst = g_h + (q & (RING - 1)) * H_BYTES + ((fresh_bid() - NENG + (second ? 36 : 0)) * 64 + a * 32 + ((tid >> 5) & 3) * 8 + g) * 64 + (((tid & 3) ^ (g >> 1)) << 4);
    wg_wait_acc<0, 16>(d);
    if (second) mbar_arrive_warp(bars + (FB_EMPTY + buf) * 8);
    uint32_t h[4];
#pragma unroll
    for (int j = 0; j < 4; j++) {
        const float g0 = d[4 * j], g1 = d[4 * j + 1];
        const float e0 = 1.f + ex2(fminf(-LOG2E * g0, 60.f)), e1 = 1.f + ex2(fminf(-LOG2E * g1, 60.f));
        const float r = rcp(e0 * e1);
        h[j] = pack2(g0 * d[4 * j + 2] * (e1 * r), g1 * d[4 * j + 3] * (e0 * r));
    }
    stg128(dst, make_uint4(h[0], h[1], h[2], h[3]));
    mbar_arrive_warp(bars + (second ? FB_H2 : FB_H) * 8);
}
template <int a>
__device__ __forceinline__ void f1_main(const Params& P) {
    constexpr uint32_t ws = F_W + a * (72 - NRF) * 2048, st = a * NRF * 2048;
    const int f0 = (blockIdx.x - NENG) * 128 + a * 96, f1 = f0 + (a ? -64 : 64);
    uint32_t w[NRF][4];
    hold_back(F1_DELAY);
    f1_fetch(P, sb + st, f0, 0, 36);
    f1_fetch(P, sb + st + 36 * 2048, f1, 0, NRF - 36);
    asm volatile("cp.async.wait_all;" ::: "memory");
    nbar_sync(NB_G + a, 128);
    {
        const uint32_t fa = sb + st + unit_frag_addr(threadIdx.x);
#pragma unroll
        for (int u = 0; u < NRF; u++) ldsm4t(w[u], fa + u * 2048);
    }
    nbar_sync(NB_S, 288);
    f1_fetch(P, sb + ws, f1, NRF - 36, 72 - NRF);
    asm volatile("cp.async.wait_all;" ::: "memory");
    fence_async_smem();
    nbar_sync(NB_G + a, 128);
    if (threadIdx.x == 0) TG(79, 2);
#pragma unroll 1
    for (int q = 0; q < NJOB; q += 2) {
        f1_tile<a, false, 0>(w, ws, q);
        f1_tile<a, true, 0>(w, ws, q);
        f1_tile<a, false, 1>(w, ws, q + 1);
        f1_tile<a, true, 1>(w, ws, q + 1);
    }
}
#define TJ(q, k) do { if ((q) == first_job(job_batch(q))) TG(job_batch(q), k); } while (0)
__device__ __forceinline__ void publisher(uint32_t done, uint32_t ack, int stage) {
#pragma unroll 1
    for (int q = 0; q < NJOB; q++) {
        if (stage == F_H2) { mbar_wait(done - 8, q & 1); publish(F_H, q); }
        mbar_wait(done, q & 1);
        mbar_arrive(ack);
        TJ(q, 30);
        publish(stage, q);
        TJ(q, 31);
    }
}
__device__ __forceinline__ void f1_helper(const Params& P) {
    const int hw = warp_in_group();
    if (hw == 0) nbar_sync(NB_S, 288);
    if ((threadIdx.x & 31) == 0) {
        const bool second = blockIdx.x >= NENG + 16;
        if (hw == 0) {
            const uint32_t ep = this_launch();
#pragma unroll 1
            for (int q = 0; q < NJOB; q++) {
                const uint8_t* src = g_xf + (q & (RING - 1)) * XF_BYTES;
                const uint32_t fb = bars + (FB_FULL + (q & 1) * 3) * 8;
                mbar_wait(bars + (FB_EMPTY + (q & 1)) * 8, ((q >> 1) & 1) ^ 1);
#pragma unroll
                for (int g = 0; g < 3; g++) mbar_expect(fb + g * 8, 12288);
                flag_wait(F_XF, q, 16 * ep);
                TJ(q, 29);
#pragma unroll
                for (int g = 0; g < 3; g++) bulk_g2s(sb + F_X + (q & 1) * XF_BYTES + g * 12288, src + g * 12288, 12288, fb + g * 8);
            }
        } else if (hw == 1) {
            const uint32_t target = (second ? 17 : 15) * this_launch();
#pragma unroll 1
            for (int q = blockIdx.x < NENG + 32 ? 0 : NJOB; q < NJOB; q++) {
                [[maybe_unused]] int n = 0;
                while (!flag_up(second ? F_P2 : F_P1, q, target)) { SPIN_CHECK(n, 20); }
                fence_acq_gpu();
                mbar_arrive(bars + FB_JOB * 8);
                TJ(q, 25);
                mbar_wait(bars + FB_JOB * 8, q & 1);
            }
        } else if (hw == 2) {
#pragma unroll 1
            for (int q = blockIdx.x < NENG + 32 ? 0 : NJOB; q < NJOB; q++) {
                if (q == 0) mbar_arrive(bars + FB_JOB * 8);
                mbar_wait(bars + FB_RDONE * 8, q & 1);
                mbar_arrive(bars + FB_JOB * 8);
                TJ(q, 23);
                if (!second) publish(F_XF, q);
                else if (!job_chain(q)) publish(F_X1, job_batch(q));
                TJ(q, 26);
            }
        } else {
            hold_back(PF_DELAY);
#pragma unroll 1
            for (int j = 0; j < 24; j++) {
                const bf16* w = j >= 16 ? P.w2 : (j & 1) ? P.w3 : P.w1;
                asm volatile("cp.async.bulk.prefetch.L2.global [%0], %1;" :: "l"(w + (size_t)((j >= 16 ? j - 16 : j >> 1) * NF1 + blockIdx.x - NENG) * (2 * FF)), "r"(4 * FF) : "memory");
                hold_back(PF_PACE);
            }
            publisher(bars + FB_H2 * 8, bars + FB_RACK * 8, F_H2);
        }
    }
    __syncwarp();
}

__device__ __forceinline__ void add8(float* f, uint4 a) {
    f[0] += bf_lo(a.x); f[1] += bf_hi(a.x); f[2] += bf_lo(a.y); f[3] += bf_hi(a.y);
    f[4] += bf_lo(a.z); f[5] += bf_hi(a.z); f[6] += bf_lo(a.w); f[7] += bf_hi(a.w);
}
__device__ __forceinline__ void set8(float* f, uint4 a) {
    f[0] = bf_lo(a.x); f[1] = bf_hi(a.x); f[2] = bf_lo(a.y); f[3] = bf_hi(a.y);
    f[4] = bf_lo(a.z); f[5] = bf_hi(a.z); f[6] = bf_lo(a.w); f[7] = bf_hi(a.w);
}
__device__ __forceinline__ void ln0_rows(const Params& P, int r, int seg0, int seg1) {
    const int lane = threadIdx.x & 31, l = lane < 24 ? lane : 0;
    const uint4* xrow = (const uint4*)(P.x + r * DM) + l;
    uint4 xw[3];
#pragma unroll
    for (int k = 0; k < 3; k++) xw[k] = __ldg(xrow + seg0 * (32 * DM / 8) + 24 * k);
    asm volatile("prefetch.global.L2 [%0];" :: "l"(P.x + (seg0 * 32 + r + 16) * DM + (lane < 9 ? lane : 0) * 64));
#pragma unroll 1
    for (int seg = seg0; seg < seg1; seg++) {
#pragma unroll 1
        for (int h = 0; h < 2; h++) {
            float f[24];
#pragma unroll
            for (int k = 0; k < 3; k++) set8(&f[k * 8], xw[k]);
            if (2 * seg + h + 1 < 2 * seg1) {
#pragma unroll
                for (int k = 0; k < 3; k++) xw[k] = __ldg(xrow + (2 * seg + h + 1) * (16 * DM / 8) + 24 * k);
            }
            float s = 0.f, q = 0.f;
#pragma unroll
            for (int j = 0; j < 24; j++) s += f[j];
            if (lane >= 24) s = 0.f;
#pragma unroll
            for (int o = 16; o; o >>= 1) s += __shfl_xor_sync(~0u, s, o);
            const float mean = s * (1.f / DM);
#pragma unroll
            for (int j = 0; j < 24; j++) { f[j] -= mean; q += f[j] * f[j]; }
            if (lane >= 24) q = 0.f;
#pragma unroll
            for (int o = 16; o; o >>= 1) q += __shfl_xor_sync(~0u, q, o);
            const float rstd = rsqrtf(q * (1.f / DM) + 1e-5f);
            if (lane < 24) {
                uint8_t* d = g_x + seg * XIMG + (l >> 3) * 8192 + (r + 16 * h) * 128 + (((l & 7) ^ (r & 7)) << 4);
#pragma unroll
                for (int k = 0; k < 3; k++) {
                    const float* y = &f[8 * k];
                    stg128(d + k * 24576, make_uint4(pack2(y[0] * rstd, y[1] * rstd), pack2(y[2] * rstd, y[3] * rstd), pack2(y[4] * rstd, y[5] * rstd), pack2(y[6] * rstd, y[7] * rstd)));
                }
            }
        }
        __syncwarp();
        if (lane == 0 && seg == 0) TG(79, 4);
        if (lane == 0) publish(F_X0, seg);
        if (lane == 0 && seg == 0) TG(79, 5);
        __syncwarp();
    }
}

template <bool SECOND, bool CHAIN>
__device__ __forceinline__ void reduce_job(const Params& P, int q) {
    constexpr int NP = SECOND ? NP2 : NP1;
    const int t = fresh_tid() - 256, p = (fresh_bid() - NENG) & 15;
    const int b = job_batch(q), seg = CHAIN ? b - LAG : b, lane = t & 31;
    const bool act = !(t & 1);
    const uint32_t ro = q & (RING - 1), po = p * (DM * 4) + t * 16, so = 2048 - t * 16 + (t >> 1) * 4;
    const int fa = (t >> 2) * 16 + (t & 3) * 2, fs = 512 + (t >> 5) * 16 + ((t >> 2) & 7) + (t & 2) * 4;
    const uint32_t row = (seg * 32 + p * 2) * DM;
    uint8_t* const r1 = g_r1 + ro * PART + po;
    uint8_t* const r2 = g_r2 + seg * PART + po;
    float f[10];
    uint4 x;
    uint32_t y;
    {
        const uint8_t* src = (SECOND ? g_p2 : g_p1) + ro * (NP * PART) + po;
        uint4 a[NP];
        uint32_t c[NP];
        mbar_wait(bars + FB_JOB * 8, q & 1);
#pragma unroll
        for (int k = 0; k < NP; k++) { a[k] = ld_rlx128(src + k * PART); c[k] = ld_rlx(src + so + k * PART); }
        if (SECOND || CHAIN) {
            x = ld_rlx128(SECOND ? r1 : r2); y = ld_rlx((SECOND ? r1 : r2) + so);
        } else {
            const bf16* xr = P.x + row;
            const uint32_t a0 = ld_rlx(xr + fa), b0 = ld_rlx(xr + fa + 8), a1 = ld_rlx(xr + fa + DM), b1 = ld_rlx(xr + fa + DM + 8);
            const uint32_t s0 = ld_rlx(xr + (fs & ~1)), s1 = ld_rlx(xr + (fs & ~1) + DM);
            x = make_uint4(__byte_perm(a0, a1, 0x5410), __byte_perm(b0, b1, 0x5410), __byte_perm(a0, a1, 0x7632), __byte_perm(b0, b1, 0x7632));
            y = __byte_perm(s0, s1, (fs & 1) ? 0x7632 : 0x5410);
        }
        set8(f, a[0]); f[8] = bf_lo(c[0]); f[9] = bf_hi(c[0]);
#pragma unroll
        for (int k = 1; k < NP; k++) { add8(f, a[k]); f[8] += bf_lo(c[k]); f[9] += bf_hi(c[k]); }
    }
    add8(f, x);
    x = make_uint4(pack2(f[0], f[1]), pack2(f[2], f[3]), pack2(f[4], f[5]), pack2(f[6], f[7]));
    y = pack2(f[8] + bf_lo(y), f[9] + bf_hi(y));
    if (SECOND && CHAIN) {
        bf16* o = P.out + row;
        stg32(o + fa, __byte_perm(x.x, x.z, 0x5410));
        stg32(o + fa + 8, __byte_perm(x.y, x.w, 0x5410));
        stg32(o + fa + DM, __byte_perm(x.x, x.z, 0x7632));
        stg32(o + fa + DM + 8, __byte_perm(x.y, x.w, 0x7632));
        stg16(o + fs + (act ? 0 : DM), act ? y : y >> 16);
        return;
    }
    set8(f, x);
    f[8] = act ? bf_lo(y) : 0.f; f[9] = act ? 0.f : bf_hi(y);
    float st[4];
    st[0] = (f[0] + f[2]) + (f[4] + f[6]) + f[8]; st[2] = (f[0] * f[0] + f[2] * f[2]) + (f[4] * f[4] + f[6] * f[6]) + f[8] * f[8];
    st[1] = (f[1] + f[3]) + (f[5] + f[7]) + f[9]; st[3] = (f[1] * f[1] + f[3] * f[3]) + (f[5] * f[5] + f[7] * f[7]) + f[9] * f[9];
    {
        const bool u = lane & 1, v = lane & 2;
        st[0] = (u ? st[1] : st[0]) + __shfl_xor_sync(~0u, u ? st[0] : st[1], 1);
        st[2] = (u ? st[3] : st[2]) + __shfl_xor_sync(~0u, u ? st[2] : st[3], 1);
        st[0] = (v ? st[2] : st[0]) + __shfl_xor_sync(~0u, v ? st[0] : st[2], 2);
        st[0] = (st[0] + __shfl_xor_sync(~0u, st[0], 4)) + (__shfl_xor_sync(~0u, st[0], 8) + __shfl_xor_sync(~0u, st[0], 12));
        if (!(lane & 12)) sts32(sb + F_RED + (t >> 4) * 16 + (lane & 3) * 4, fu(st[0]));
    }
    nbar_sync(NB_R, 128);
#pragma unroll
    for (int k = 0; k < 8; k++) {
        const uint4 z = lds128(sb + F_RED + k * 16);
        if (k == 0) { st[0] = uf(z.x); st[1] = uf(z.y); st[2] = uf(z.z); st[3] = uf(z.w); }
        else { st[0] += uf(z.x); st[1] += uf(z.y); st[2] += uf(z.z); st[3] += uf(z.w); }
    }
    stg128(SECOND ? r2 : r1, x);
    if (act) stg32((SECOND ? r2 : r1) + so, y);
    const float m0 = st[0] * (1.f / DM), m1 = st[1] * (1.f / DM);
    const float q0 = rsqrtf(fmaxf(st[2] * (1.f / DM) - m0 * m0, 0.f) + 1e-5f), q1 = rsqrtf(fmaxf(st[3] * (1.f / DM) - m1 * m1, 0.f) + 1e-5f);
    constexpr int KB = SECOND ? 8192 : 4096;
    uint8_t* d = (SECOND ? g_x + (b + LAG) * XIMG + (USE_ONE && b + LAG >= NSEG ? 0 : 4096) : g_xf + ro * XF_BYTES) + p * 256;
#pragma unroll
    for (int e = 0; e < 2; e++) {
        const float m = e ? m1 : m0, r = e ? q1 : q0;
#pragma unroll
        for (int h = 0; h < 2; h++)
            stg32(d + (fa >> 6) * KB + (t & 3) * 4 + e * 128 + (((((fa >> 3) & 6) + h) ^ ((2 * p + e) & 7)) << 4), pack2((f[2 * h + e] - m) * r, (f[4 + 2 * h + e] - m) * r));
    }
    stg16(d + 8 * KB + (t & 1) * 128 + ((((fs >> 3) & 7) ^ ((2 * p + (t & 1)) & 7)) << 4) + (fs & 7) * 2, pack2(act ? (f[8] - m0) * q0 : (f[9] - m1) * q1, 0.f));
}
template <bool SECOND>
__device__ __forceinline__ void reducer(const Params& P) {
#pragma unroll 1
    for (int q = 0; q < NJOB; q++) {
        if (job_chain(q)) reduce_job<SECOND, true>(P, q);
        else reduce_job<SECOND, false>(P, q);
        mbar_arrive_warp(bars + FB_RDONE * 8);
    }
}

__host__ __device__ constexpr int d_units(int kind) { return kind ? 28 * kind : 52; }
__host__ __device__ constexpr int d_regs(int kind) { return kind == 0 ? 29 : kind == 1 ? 28 : 25; }
__host__ __device__ constexpr uint64_t d_mask(int kind) {
    uint64_t m = 0;
    for (int u = 0; u < d_units(kind); u++) if (u * d_regs(kind) / d_units(kind) != (u + 1) * d_regs(kind) / d_units(kind)) m |= 1ull << u;
    return m;
}
__host__ __device__ constexpr int d_group(bool side, int g) { return g < 3 ? 12 * g : side ? 20 + 2 * g : 4 + 12 * g; }
__device__ __forceinline__ int d_tile(int ds, int wg) { return ds < 30 ? (ds % 3) * 3 + wg : ds == 30 ? 2 * wg : wg ? 6 + wg : 5; }
template <int KIND, int wg>
__device__ __forceinline__ void d_main() {
    constexpr int NR = d_regs(KIND), NT = KIND ? KIND : 1, NG = 4, STR = KIND ? D_STR2 : D_STR;
    constexpr uint64_t M = d_mask(KIND);
    uint32_t w[NR][4];
    {
        const uint32_t fa = sb + wg * (STR * 2048) + unit_frag_addr(threadIdx.x);
        mbar_wait(bars + DB_WL * 8, 0);
#pragma unroll
        for (int u = 0; u < NR; u++) ldsm4t(w[u], fa + u * 2048);
        nbar_arrive(NB_W, 416);
        mbar_wait(bars + DB_WL * 8, 1);
        if (threadIdx.x == 0) TG(79, 2);
    }
    const uint64_t da = mkdesc(wg * (STR * 2048), 1024, 1024, 1), db = mkdesc(3 * STR * 2048, 512, 512, 2);
    const int tid = fresh_tid(), ds = fresh_bid() - NENG - NF1;
    const bool w2 = ds >= 15;
    uint8_t* const dst0 = (w2 ? g_p2 + ((ds - 15) / 3) * PART : g_p1 + (ds / 3) * PART)
                        + (d_tile(ds, wg) * 64 + ((tid >> 5) & 3) * 16 + ((tid & 31) >> 2) * 2) * 4 + (w2 ? 4 : 1) * (tid & 3) * (DM * 4);
    const uint32_t js = w2 ? DM * 4 : DM * 16, qs = (w2 ? NP2 : NP1) * PART;
#pragma unroll 1
    for (int q = 0; q < NJOB; q++) {
        float d[NT][16];
#pragma unroll
        for (int g = 0; g < NG; g++) {
            mbar_wait(bars + (DB_FULL + g) * 8, q & 1);
            wg_fence();
#pragma unroll
            for (int j = 0; j < 24; j++) {
                const int u = d_group(KIND, g) * NT + j, r = popc_below(M, u < 64 ? u : 0);
                if (u >= d_group(KIND, g + 1) * NT) continue;
                if ((M >> u) & 1) wg_rs32<1>(d[u % NT], w[r < NR ? r : 0], db + (u / NT) * 64, u >= NT);
                else wg_ss32<1>(d[u % NT], da + (u - r) * 128, db + (u / NT) * 64, u >= NT);
            }
            wg_commit();
            if (g > 0) { wg_wait<1>(); mbar_arrive_warp(bars + (DB_EMPTY + g - 1) * 8); }
        }
        mbar_wait(bars + (DB_P + 1) * 8, (q & 1) ^ 1);
        uint8_t* const dst = dst0 + (q & (RING - 1)) * qs;
        wg_wait_acc<0, 16 * NT>(&d[0][0]);
        mbar_arrive_warp(bars + (DB_EMPTY + NG - 1) * 8);
#pragma unroll
        for (int j = 0; j < 4 * NT; j++) {
            const float* y = &d[j >> 2][4 * (j & 3)];
            stg64(dst + (j >> 2) * 256 + (j & 3) * js, pack2(y[0], y[1]), pack2(y[2], y[3]));
        }
        mbar_arrive_warp(bars + DB_P * 8);
    }
}
template <bool W2, bool SIDE>
__device__ __forceinline__ void d_producer(int blk0, int blk1) {
    const uint32_t target = (W2 ? NF1 : NENG) * this_launch();
    uint32_t rdy = 0;
#pragma unroll 1
    for (int q = 0; q < NJOB; q++) {
        const uint32_t so = (q & (RING - 1)) * (W2 ? H_BYTES : O_BYTES);
#pragma unroll
        for (int g = 0; g < 4; g++) {
            if (g == 0 || (g == 2 && W2)) {
                if (!(rdy & 1)) {
                    [[maybe_unused]] int n = 0;
                    do {
                        if (W2) {
                            const bool r0 = flag_up(g ? F_H2 : F_H, q, target), r1 = flag_up(g ? F_H : F_H2, q + g / 2, target), r2 = flag_up(g ? F_H2 : F_H, q + 1, target);
                            rdy = !r0 ? 0 : !r1 ? 1 : !r2 ? 3 : 7;
                        } else {
                            rdy = !flag_up(F_O, job_batch(q), target) ? 0 : q >= LAG && q < NJOB - LAG ? 3 : 1;
                        }
                        SPIN_CHECK(n, 30);
                    } while (!rdy);
                    fence_acq_gpu();
                    fence_async_glb();
                }
                rdy >>= 1;
            }
            constexpr uint32_t slots = 3 * (SIDE ? D_STR2 : D_STR) * 2048;
            const uint32_t off = d_group(SIDE, g) * 1024, bytes = d_group(SIDE, g + 1) * 1024 - off;
            mbar_wait(bars + (DB_EMPTY + g) * 8, (q & 1) ^ 1);
            mbar_expect(bars + (DB_FULL + g) * 8, bytes);
            bulk_g2s(sb + slots + off, (W2 ? g_h : g_o) + (so + (g < 2 ? blk0 : blk1) * 4096 + off), bytes, bars + (DB_FULL + g) * 8);
            if (g == 0) TJ(q, 29);
        }
    }
}
__device__ __forceinline__ void d_helper(const Params& P, int ds) {
    const int lane = threadIdx.x & 31, hw = warp_in_group();
    const bool w2 = ds >= 15, side = ds >= 30;
    const int kr = (w2 ? ds - 15 : ds) / 3, blk0 = kr * (w2 ? 6 : 13), blk1 = w2 ? 30 + kr * 7 : blk0, str = side ? D_STR2 : D_STR;
    if (hw == 0) {
        hold_back(w2 ? W2_DELAY : D_DELAY);
#pragma unroll 1
        for (int ph = 0; ph < 2; ph++) {
            if (ph) nbar_sync(NB_W, 416);
            if (lane == 0) mbar_expect(bars + DB_WL * 8, (!side ? (ph ? 69 : 87) : ds == 30 ? (ph ? 62 : 78) : (ph ? 31 : 81)) * 2048);
            __syncwarp();
#pragma unroll 1
            for (int x = lane; x < 192; x += 32) {
                constexpr uint64_t M0 = d_mask(0), M1 = d_mask(1), M2 = d_mask(2);
                const int wg = x >> 6, u = x & 63, kind = !side ? 0 : wg < 32 - ds ? 2 : 1;
                const uint64_t m = kind == 0 ? M0 : kind == 1 ? M1 : M2;
                const int ks = kind == 2 ? u >> 1 : u, j = ks >> 2, r = popc_below(m, u);
                const int pos = (j < 6 ? blk0 : blk1) + j, kb = !w2 ? pos : pos < 36 ? pos * 2 : (pos - 36) * 2 + 1;
                if (u < d_units(kind) && ((m >> u) & 1) != ph)
                    tma_unit(sb + (wg * str + (ph ? u - r : r)) * 2048, w2 ? &P.tmW2 : &P.tmWo,
                             kb * 4 + (ks & 3), d_tile(ds, wg) + (kind == 2 ? u & 1 : 0), bars + DB_WL * 8);
            }
        }
        __syncwarp();
        if (lane == 0) {
            if (!w2) d_producer<false, false>(blk0, blk1);
            else if (!side) d_producer<true, false>(blk0, blk1);
            else d_producer<true, true>(blk0, blk1);
        }
    } else if (hw == 1 && lane == 0) {
        publisher(bars + DB_P * 8, bars + (DB_P + 1) * 8, w2 ? F_P2 : F_P1);
    }
    __syncwarp();
}

__device__ __forceinline__ void sign_off() { mbar_arrive_warp(sb + SM_DONE); }
__device__ __forceinline__ void sign_off_helper(uint32_t nap) {
    if (warp_in_group() < 3) { sign_off(); return; }
    uint32_t ok;
    const uint32_t t0 = timer_lo(), ep = this_launch();
    do {
        __nanosleep(nap);
        asm volatile("{.reg .pred p; mbarrier.test_wait.parity.shared::cta.b64 p, [%1], 0; selp.u32 %0, 1, 0, p;}" : "=r"(ok) : "r"(sb + SM_DONE) : "memory");
    } while (!ok && timer_lo() - t0 < TIME_LIMIT);
    if (!ok || (sb & 0x3ffff) != SM_ORG) __trap();
    if (fresh_tid() == NTHREADS - 32) { g_epoch[fresh_bid()][0] = ep; TG(79, 1); }
    __syncwarp();
}

__global__ void __cluster_dims__(2, 1, 1) __launch_bounds__(NTHREADS, 1) fused_kernel(const __grid_constant__ Params P) {
    const int wg = __shfl_sync(~0u, threadIdx.x >> 7, 0);
    const int bid = blockIdx.x;
    if (threadIdx.x >= NTHREADS - 32) sts32(sb + SM_ONES + (threadIdx.x & 31) * 4, 0x3f803f80u);
    if (threadIdx.x == 0) {
        TG(79, 0);
        mbar_init(sb + SM_DONE, 15);
        if (bid < NENG) {
            for (int i = 0; i < 9; i++) mbar_init(bars + (EB_FULL + i) * 8, i < 6 ? 1 : 12);
            mbar_init(bars + EB_V0 * 8, 4); mbar_init(bars + EB_WL * 8, 3); mbar_init(bars + EB_WO * 8, 2); mbar_init(bars + EB_STEP * 8, 8);
            mbar_init(bars + EB_SM * 8, 1); mbar_init(bars + EB_SX * 8, 1); mbar_init(bars + EB_OX * 8, 1);
            mbar_init(bars + EB_QF * 8, 4); mbar_init(bars + EB_KF * 8, 8); mbar_init(bars + EB_CONS * 8, 4); mbar_init(bars + EB_OST * 8, 4);
            mbar_init(bars + EB_OFREE * 8, 1); mbar_init(bars + EB_MEM0 * 8, 4); mbar_init(bars + EB_MEMA * 8, 1); mbar_init(bars + EB_MEM * 8, 5); mbar_init(bars + EB_PRDY * 8, 1); mbar_init(bars + EB_XR * 8, 2);
        } else if (bid < NENG + NF1) {
            for (int i = 0; i < 8; i++) mbar_init(bars + (FB_FULL + i) * 8, i < 6 ? 1 : 8);
            mbar_init(bars + FB_H * 8, 8); mbar_init(bars + FB_H2 * 8, 8); mbar_init(bars + FB_RACK * 8, 1); mbar_init(bars + FB_JOB * 8, 2); mbar_init(bars + FB_RDONE * 8, 4);
        } else {
            for (int i = 0; i < 4; i++) { mbar_init(bars + (DB_FULL + i) * 8, 1); mbar_init(bars + (DB_EMPTY + i) * 8, 12); }
            mbar_init(bars + DB_WL * 8, 1); mbar_init(bars + DB_P * 8, 12); mbar_init(bars + (DB_P + 1) * 8, 1);
        }
        asm volatile("fence.mbarrier_init.release.cluster;" ::: "memory");
    }
    __syncthreads();
    asm volatile("barrier.cluster.arrive.relaxed.aligned; barrier.cluster.wait.aligned;" ::: "memory");
    if (bid < NENG) {
        if (wg == 0) { reg_inc<REGQ>(); engine_main<0>(P); sign_off(); cluster_sync_all(); }
        else if (wg == 1) { reg_inc<REGK>(); engine_main<1>(P); sign_off(); cluster_sync_all(); }
        else if (wg == 2) { reg_inc<REGV>(); engine_main<2>(P); sign_off(); cluster_sync_all(); }
        else { reg_dec<24>(); engine_helper(P); sign_off_helper(1000); cluster_sync_all(); }
    } else if (bid < NENG + NF1) {
        if (wg < 2) {
            reg_inc<REGF>();
            if (wg == 0) f1_main<0>(P); else f1_main<1>(P);
            sign_off();
        } else if (wg == 2) {
            reg_dec<488 - 2 * REGF>();
            if (bid >= NENG + 32) ln0_rows(P, (bid - NENG - 32) * 4 + warp_in_group(), 12, NSEG);
            else if (bid < NENG + 16) reducer<false>(P);
            else reducer<true>(P);
            sign_off();
        } else {
            reg_dec<24>();
            f1_helper(P);
            sign_off_helper(100);
        }
    } else {
        const int ds = bid - NENG - NF1;
        if (wg < 3) {
            reg_inc<160>();
            if (ds >= 16) { const int seg = wg * 4 + warp_in_group(); ln0_rows(P, ds - 16, seg, seg + 1); }
            if (ds < 30) { if (wg == 0) d_main<0, 0>(); else if (wg == 1) d_main<0, 1>(); else d_main<0, 2>(); }
            else { if (wg == 0) d_main<2, 0>(); else if (wg == 2) d_main<1, 2>(); else if (ds == 30) d_main<2, 1>(); else d_main<1, 1>(); }
            sign_off();
        } else {
            reg_dec<32>();
            d_helper(P, ds);
            sign_off_helper(500);
        }
    }
}

typedef CUresult (*EncodeFn)(CUtensorMap*, CUtensorMapDataType, cuuint32_t, void*, const cuuint64_t*, const cuuint64_t*,
                             const cuuint32_t*, const cuuint32_t*, CUtensorMapInterleave, CUtensorMapSwizzle,
                             CUtensorMapL2promotion, CUtensorMapFloatOOBfill);

void make_map(EncodeFn enc, CUtensorMap* m, const void* p, int rows, int cols) {
    cuuint64_t dims[2] = {(cuuint64_t)cols, (cuuint64_t)rows};
    cuuint64_t strides[1] = {(cuuint64_t)cols * 2};
    cuuint32_t box[2] = {64, 16};
    cuuint32_t es[2] = {1, 1};
    enc(m, CU_TENSOR_MAP_DATA_TYPE_BFLOAT16, 2, (void*)p, dims, strides, box, es, CU_TENSOR_MAP_INTERLEAVE_NONE,
        CU_TENSOR_MAP_SWIZZLE_128B, CU_TENSOR_MAP_L2_PROMOTION_L2_128B, CU_TENSOR_MAP_FLOAT_OOB_FILL_NONE);
}

}

extern "C" void kernel_launch(void* const* d_in, const int* in_sizes, int n_in, void* d_out, int out_size) {
    (void)in_sizes; (void)n_in; (void)out_size;
    static EncodeFn enc = nullptr;
    if (!enc) {
        void* fn = nullptr;
        cudaDriverEntryPointQueryResult qr;
        cudaGetDriverEntryPoint("cuTensorMapEncodeTiled", &fn, cudaEnableDefault, &qr);
        enc = (EncodeFn)fn;
        cudaFuncSetAttribute(fused_kernel, cudaFuncAttributeMaxDynamicSharedMemorySize, SM_TOTAL);
    }
    Params P;
    make_map(enc, &P.tmWq, d_in[2], DM, 4096);
    make_map(enc, &P.tmWk, d_in[3], DM, 4096);
    make_map(enc, &P.tmWv, d_in[4], DM, 4096);
    make_map(enc, &P.tmWo, d_in[5], 4096, DM);
    make_map(enc, &P.tmW2, d_in[10], FF, DM);
    P.x = (const bf16*)d_in[0];
    P.mem0 = (const bf16*)d_in[1];
    P.w1 = (const bf16*)d_in[8];
    P.w3 = (const bf16*)d_in[9];
    P.w2 = (const bf16*)d_in[10];
    P.out = (bf16*)d_out;
    P.zero = 0;
    fused_kernel<<<NCTA, NTHREADS, SM_TOTAL>>>(P);
}
```
